```python
import torch

def _softmax(x, axis=-1):
    return torch.softmax(x, dim=axis)

def _gelu(x):
    return torch.nn.functional.gelu(x, approximate='tanh')

def _silu(x):
    return torch.nn.functional.silu(x)

def _sigmoid(x):
    return torch.sigmoid(x)

def _layernorm(x, axis=-1, eps=1e-05):
    m = x.mean(dim=axis, keepdim=True)
    v = x.var(dim=axis, keepdim=True, unbiased=False)
    return (x - m) / torch.sqrt(v + eps)

def _scatter_add(tgt, idx, src, axis=0):
    return tgt.clone().index_add_(axis, idx, src)

def _segment_sum(src, seg, n):
    out = torch.zeros((n,) + src.shape[1:], dtype=src.dtype)
    return out.index_add_(0, seg, src)

def _pad(x, pw):
    flat = tuple((v for pair in reversed(pw) for v in pair))
    return torch.nn.functional.pad(x, flat)
kernel_name = 'concat_heads__compressed_kv_cla__memory_aug_recurrent_mem_tr__prompt'

def setup_inputs():

    _w = lambda a: (lambda t: t.to(torch.bfloat16) if t.is_floating_point() else t)(torch.as_tensor(a))

    def _A_setup():
        B, H, Sq, Sk, D, M = (1, 32, 2048, 2048, 128, 576)
        Dc = 4 * D
        return {'x': _w((lambda *s: torch.randn(*s, dtype=torch.bfloat16) * 1.6)(B, Sq, M)), 'c_kv': _w((lambda *s: torch.randn(*s, dtype=torch.bfloat16) * 0.2)(B, Sk, Dc)), 'w_q': _w((lambda *s: torch.randn(*s, dtype=torch.bfloat16) * 3.2)(M, H, D) * M ** (-0.5)), 'w_uk': _w((lambda *s: torch.randn(*s, dtype=torch.bfloat16) * 3.2)(Dc, H, D) * Dc ** (-0.5)), 'w_uv': _w((lambda *s: torch.randn(*s, dtype=torch.bfloat16) * 0.2)(Dc, H, D) * Dc ** (-0.5)), 'w_o': _w((lambda *s: torch.randn(*s, dtype=torch.bfloat16) * 0.2)(H, D, M) * (H * D) ** (-0.5))}
    _A_in = _A_setup()

    def _B_setup():
        B, S, Dm = (1, 2048, 576)
        H, Dh = (32, 128)
        M, seg = (8, 32)
        seg = min(seg, S)
        S = S // seg * seg
        return {'x': _w((lambda *s: torch.randn(*s, dtype=torch.bfloat16) * 0.05)(B, S, Dm)), 'mem0': _w((lambda *s: torch.randn(*s, dtype=torch.bfloat16) * 0.4)(B, M, Dm)), 'Wq': _w((lambda *s: torch.randn(*s, dtype=torch.bfloat16) * 6.4)(Dm, H, Dh) * Dm ** (-0.5)), 'Wk': _w((lambda *s: torch.randn(*s, dtype=torch.bfloat16) * 6.4)(Dm, H, Dh) * Dm ** (-0.5)), 'Wv': _w((lambda *s: torch.randn(*s, dtype=torch.bfloat16) * 0.4)(Dm, H, Dh) * Dm ** (-0.5)), 'Wo': _w((lambda *s: torch.randn(*s, dtype=torch.bfloat16) * 0.4)(H, Dh, Dm) * (H * Dh) ** (-0.5)), 'seg_len': seg}
    _B_in = _B_setup()
    return {'A_x': _A_in['x'], 'A_c_kv': _A_in['c_kv'], 'A_w_q': _A_in['w_q'], 'A_w_uk': _A_in['w_uk'], 'A_w_uv': _A_in['w_uv'], 'A_w_o': _A_in['w_o'], 'B_x': _B_in['x'], 'B_mem0': _B_in['mem0'], 'B_Wq': _B_in['Wq'], 'B_Wk': _B_in['Wk'], 'B_Wv': _B_in['Wv'], 'B_Wo': _B_in['Wo'], 'B_seg_len': _B_in['seg_len']}

def reference(A_x, A_c_kv, A_w_q, A_w_uk, A_w_uv, A_w_o, B_x, B_mem0, B_Wq, B_Wk, B_Wv, B_Wo, B_seg_len):

    def _A_ref(x, c_kv, w_q, w_uk, w_uv, w_o):
        B, Sq, M = (x.shape[0], x.shape[1], x.shape[2])
        Sk = c_kv.shape[1]
        H, D = (w_q.shape[1], w_q.shape[2])
        q = torch.einsum('bqm,mhd->bhqd', x, w_q)
        k = torch.einsum('bkc,chd->bhkd', c_kv, w_uk)
        v = torch.einsum('bkc,chd->bhkd', c_kv, w_uv)
        scores = torch.einsum('bhqd,bhkd->bhqk', q, k) * D ** (-0.5)
        off = Sk - Sq
        qi = torch.arange(Sq)[:, None]
        kj = torch.arange(Sk)[None, :]
        cmask = kj <= qi + off
        scores = torch.where(cmask[None, None], scores, -1000000000.0)
        p = _softmax(scores, axis=-1)
        ctx = torch.einsum('bhqk,bhkd->bhqd', p, v)
        return torch.einsum('bhqd,hdm->bqm', ctx, w_o)

    def _B_ref(x, mem0, Wq, Wk, Wv, Wo, seg_len):
        B, S, Dm = x.shape
        H, Dh = (Wq.shape[1], Wq.shape[2])
        M = mem0.shape[1]
        scale = Dh ** (-0.5)
        n_seg = S // seg_len
        L = M + seg_len
        idx = torch.arange(L)
        mask = (idx[:, None] < M) | (idx[:, None] >= idx[None, :])
        mem = mem0
        outs = []
        for s in range(n_seg):
            xs = x[:, s * seg_len:(s + 1) * seg_len, :].clone()
            h = torch.concatenate([mem, xs], axis=1)
            q = torch.einsum('btd,dhe->bhte', h, Wq)
            k = torch.einsum('btd,dhe->bhte', h, Wk)
            v = torch.einsum('btd,dhe->bhte', h, Wv)
            scores = torch.einsum('bhqe,bhke->bhqk', q, k) * scale
            scores = torch.where(mask[None, None], scores, -1000000000.0)
            p = _softmax(scores, axis=-1)
            o = torch.einsum('bhqk,bhke->bhqe', p, v)
            o = torch.einsum('bhte,hed->btd', o, Wo)
            mem = o[:, :M, :].clone()
            outs.append(o[:, M:, :])
        return torch.concatenate(outs, axis=1)
    a = _A_ref(A_x, A_c_kv, A_w_q, A_w_uk, A_w_uv, A_w_o)
    b = _B_ref(B_x, B_mem0, B_Wq, B_Wk, B_Wv, B_Wo, B_seg_len)
    return torch.concatenate([a, b], axis=-1)
```

```cpp
#include <cuda_runtime.h>
#include <cuda_bf16.h>
#include <cuda.h>
#include <stdint.h>

typedef __nv_bfloat16 bf16;
#define DEVI __device__ __forceinline__
#define WAIT_FAIL break

constexpr int SEQ = 2048, HD = 4096, DM = 576, NSEG = 64;

#define RING 2
__device__ __align__(1024) bf16 g_qA[SEQ * HD], g_kA[SEQ * HD], g_vA[SEQ * HD];
__device__ __align__(1024) bf16 g_ctxA[SEQ * HD], g_ctxB[SEQ * HD];
__device__ __align__(1024) uint4 g_Y[RING * 72 * 256];
__device__ unsigned g_ctr[8];
__device__ unsigned g_flag[256];
#define TL_START(i)
#define TL_END(i)

DEVI uint32_t s2u(const void* p) { return (uint32_t)__cvta_generic_to_shared(p); }
DEVI void mbar_init(uint32_t b, uint32_t c) { asm volatile("mbarrier.init.shared::cta.b64 [%0],%1;" ::"r"(b), "r"(c)); }
DEVI void mbar_expect(uint32_t b, uint32_t n) { asm volatile("mbarrier.arrive.expect_tx.shared::cta.b64 _,[%0],%1;" ::"r"(b), "r"(n) : "memory"); }
DEVI void mbar_arrive(uint32_t b) { asm volatile("mbarrier.arrive.shared::cta.b64 _,[%0];" ::"r"(b) : "memory"); }
DEVI void mbar_wait(uint32_t b, uint32_t ph) {
  uint32_t ok; int it = 0;
  do {
    asm volatile("{.reg .pred p; mbarrier.try_wait.parity.shared::cta.b64 p,[%1],%2; selp.u32 %0,1,0,p;}" : "=r"(ok) : "r"(b), "r"(ph) : "memory");
    if (!ok && ++it > (1 << 22)) WAIT_FAIL;
  } while (!ok);
}
DEVI void tma_load(uint32_t dst, const CUtensorMap* tm, int c0, int c1, uint32_t bar) {
  asm volatile("cp.async.bulk.tensor.2d.shared::cluster.global.mbarrier::complete_tx::bytes [%0],[%1,{%3,%4}],[%2];" ::"r"(dst), "l"(tm), "r"(bar), "r"(c0), "r"(c1) : "memory");
}
DEVI void tma_store(const CUtensorMap* tm, uint32_t src, int c0, int c1) {
  asm volatile("cp.async.bulk.tensor.2d.global.shared::cta.bulk_group [%0,{%2,%3}],[%1];" ::"l"(tm), "r"(src), "r"(c0), "r"(c1) : "memory");
}
DEVI void bulk_commit() { asm volatile("cp.async.bulk.commit_group;" ::: "memory"); }
template <int N> DEVI void bulk_wait_read() { asm volatile("cp.async.bulk.wait_group.read %0;" ::"n"(N) : "memory"); }
template <int N> DEVI void bulk_wait() { asm volatile("cp.async.bulk.wait_group %0;" ::"n"(N) : "memory"); }
DEVI void fence_async() { asm volatile("fence.proxy.async.shared::cta;" ::: "memory"); }
DEVI void bar_sync(int id, int n) { asm volatile("bar.sync %0,%1;" ::"r"(id), "r"(n) : "memory"); }
DEVI void bar_arrive(int id, int n) { asm volatile("bar.arrive %0,%1;" ::"r"(id), "r"(n) : "memory"); }
template <int R> DEVI void reg_inc() { asm volatile("setmaxnreg.inc.sync.aligned.u32 %0;" ::"n"(R)); }
template <int R> DEVI void reg_dec() { asm volatile("setmaxnreg.dec.sync.aligned.u32 %0;" ::"n"(R)); }
DEVI void wg_fence() { asm volatile("wgmma.fence.sync.aligned;" ::: "memory"); }
DEVI void wg_commit() { asm volatile("wgmma.commit_group.sync.aligned;" ::: "memory"); }
template <int N> DEVI void wg_wait() { asm volatile("wgmma.wait_group.sync.aligned %0;" ::"n"(N) : "memory"); }
DEVI uint64_t desc_k(uint32_t a) { return (uint64_t)((a >> 4) & 0x3fff) | (1ull << 16) | (64ull << 32) | (1ull << 62); }
DEVI uint64_t desc_mn(uint32_t a, uint32_t lbo) { return (uint64_t)((a >> 4) & 0x3fff) | ((uint64_t)(lbo >> 4) << 16) | (64ull << 32) | (1ull << 62); }
DEVI uint32_t pack2(float lo, float hi) { uint32_t r; asm("cvt.rn.bf16x2.f32 %0,%1,%2;" : "=r"(r) : "f"(hi), "f"(lo)); return r; }
DEVI float ex2(float x) { float y; asm("ex2.approx.ftz.f32 %0,%1;" : "=f"(y) : "f"(x)); return y; }
DEVI void stsm4(uint32_t a, uint32_t r0, uint32_t r1, uint32_t r2, uint32_t r3) {
  asm volatile("stmatrix.sync.aligned.m8n8.x4.shared.b16 [%0],{%1,%2,%3,%4};" ::"r"(a), "r"(r0), "r"(r1), "r"(r2), "r"(r3) : "memory");
}
DEVI void ldsm4(uint32_t* r, uint32_t a) {
  asm volatile("ldmatrix.sync.aligned.m8n8.x4.shared.b16 {%0,%1,%2,%3},[%4];" : "=r"(r[0]), "=r"(r[1]), "=r"(r[2]), "=r"(r[3]) : "r"(a) : "memory");
}
DEVI void ldsm4t(uint32_t* r, uint32_t a) {
  asm volatile("ldmatrix.sync.aligned.m8n8.x4.trans.shared.b16 {%0,%1,%2,%3},[%4];" : "=r"(r[0]), "=r"(r[1]), "=r"(r[2]), "=r"(r[3]) : "r"(a) : "memory");
}
DEVI void mma16(float* d, uint32_t a0, uint32_t a1, uint32_t a2, uint32_t a3, uint32_t b0, uint32_t b1) {
  asm volatile("mma.sync.aligned.m16n8k16.row.col.f32.bf16.bf16.f32 {%0,%1,%2,%3},{%4,%5,%6,%7},{%8,%9},{%0,%1,%2,%3};"
               : "+f"(d[0]), "+f"(d[1]), "+f"(d[2]), "+f"(d[3]) : "r"(a0), "r"(a1), "r"(a2), "r"(a3), "r"(b0), "r"(b1));
}
DEVI void cp16(uint32_t dst, const void* src) { asm volatile("cp.async.cg.shared.global [%0],[%1],16;" ::"r"(dst), "l"(src) : "memory"); }
DEVI void cp_commit() { asm volatile("cp.async.commit_group;" ::: "memory"); }
template <int N> DEVI void cp_wait() { asm volatile("cp.async.wait_group %0;" ::"n"(N) : "memory"); }

#define F8(a, o) "+f"(a[o]), "+f"(a[o + 1]), "+f"(a[o + 2]), "+f"(a[o + 3]), "+f"(a[o + 4]), "+f"(a[o + 5]), "+f"(a[o + 6]), "+f"(a[o + 7])
#define F32(a, o) F8(a, o), F8(a, o + 8), F8(a, o + 16), F8(a, o + 24)
template<int TB> DEVI void wg_ss128(float* d, uint64_t da, uint64_t db, int acc){
 asm volatile("{.reg .pred p; setp.ne.b32 p,%66,0;\n wgmma.mma_async.sync.aligned.m64n128k16.f32.bf16.bf16 {%0,%1,%2,%3,%4,%5,%6,%7,%8,%9,%10,%11,%12,%13,%14,%15,%16,%17,%18,%19,%20,%21,%22,%23,%24,%25,%26,%27,%28,%29,%30,%31,%32,%33,%34,%35,%36,%37,%38,%39,%40,%41,%42,%43,%44,%45,%46,%47,%48,%49,%50,%51,%52,%53,%54,%55,%56,%57,%58,%59,%60,%61,%62,%63},%64,%65,p,1,1,0,%67;}"
 : F32(d,0),F32(d,32) : "l"(da),"l"(db),"r"(acc),"n"(TB));}
template<int TB> DEVI void wg_ss192(float* d, uint64_t da, uint64_t db, int acc){
 asm volatile("{.reg .pred p; setp.ne.b32 p,%98,0;\n wgmma.mma_async.sync.aligned.m64n192k16.f32.bf16.bf16 {%0,%1,%2,%3,%4,%5,%6,%7,%8,%9,%10,%11,%12,%13,%14,%15,%16,%17,%18,%19,%20,%21,%22,%23,%24,%25,%26,%27,%28,%29,%30,%31,%32,%33,%34,%35,%36,%37,%38,%39,%40,%41,%42,%43,%44,%45,%46,%47,%48,%49,%50,%51,%52,%53,%54,%55,%56,%57,%58,%59,%60,%61,%62,%63,%64,%65,%66,%67,%68,%69,%70,%71,%72,%73,%74,%75,%76,%77,%78,%79,%80,%81,%82,%83,%84,%85,%86,%87,%88,%89,%90,%91,%92,%93,%94,%95},%96,%97,p,1,1,0,%99;}"
 : F32(d,0),F32(d,32),F32(d,64) : "l"(da),"l"(db),"r"(acc),"n"(TB));}
template<int TB> DEVI void wg_ss256(float* d, uint64_t da, uint64_t db, int acc){
 asm volatile("{.reg .pred p; setp.ne.b32 p,%130,0;\n wgmma.mma_async.sync.aligned.m64n256k16.f32.bf16.bf16 {%0,%1,%2,%3,%4,%5,%6,%7,%8,%9,%10,%11,%12,%13,%14,%15,%16,%17,%18,%19,%20,%21,%22,%23,%24,%25,%26,%27,%28,%29,%30,%31,%32,%33,%34,%35,%36,%37,%38,%39,%40,%41,%42,%43,%44,%45,%46,%47,%48,%49,%50,%51,%52,%53,%54,%55,%56,%57,%58,%59,%60,%61,%62,%63,%64,%65,%66,%67,%68,%69,%70,%71,%72,%73,%74,%75,%76,%77,%78,%79,%80,%81,%82,%83,%84,%85,%86,%87,%88,%89,%90,%91,%92,%93,%94,%95,%96,%97,%98,%99,%100,%101,%102,%103,%104,%105,%106,%107,%108,%109,%110,%111,%112,%113,%114,%115,%116,%117,%118,%119,%120,%121,%122,%123,%124,%125,%126,%127},%128,%129,p,1,1,0,%131;}"
 : F32(d,0),F32(d,32),F32(d,64),F32(d,96) : "l"(da),"l"(db),"r"(acc),"n"(TB));}
DEVI void wg_rs128t(float* d, uint32_t a0,uint32_t a1,uint32_t a2,uint32_t a3, uint64_t db){
 asm volatile("wgmma.mma_async.sync.aligned.m64n128k16.f32.bf16.bf16 {%0,%1,%2,%3,%4,%5,%6,%7,%8,%9,%10,%11,%12,%13,%14,%15,%16,%17,%18,%19,%20,%21,%22,%23,%24,%25,%26,%27,%28,%29,%30,%31,%32,%33,%34,%35,%36,%37,%38,%39,%40,%41,%42,%43,%44,%45,%46,%47,%48,%49,%50,%51,%52,%53,%54,%55,%56,%57,%58,%59,%60,%61,%62,%63},{%64,%65,%66,%67},%68,1,1,1,1;"
 : F32(d,0),F32(d,32) : "r"(a0),"r"(a1),"r"(a2),"r"(a3),"l"(db));}
struct GemmProb { CUtensorMap a, b, c; };
struct GemmParams { GemmProb p[6]; int ksteps[6]; int tile_end[6]; int ntiles; int nsig; int id; };
template <int BN>
DEVI void tile_decode(const GemmParams& P, int t, int& pi, int& m0, int& n0) {
  if (t < P.nsig) { const int m = t / 48, r = t - m * 48; pi = r >> 4; m0 = m * 128; n0 = (r & 15) * BN; return; }
  pi = 0; while (t >= P.tile_end[pi]) pi++;
  const int lt = t - (pi ? P.tile_end[pi - 1] : 0);
  m0 = (lt & 15) * 128; n0 = (lt >> 4) * BN;
}
__global__ void clear_kernel() {
  for (int i = blockIdx.x * 256 + threadIdx.x; i < RING * 72 * 256; i += gridDim.x * 256) g_Y[i] = make_uint4(0, 0, 0, 0);
  if (blockIdx.x == 0) { g_flag[threadIdx.x] = 0; if (threadIdx.x < 8) g_ctr[threadIdx.x] = 0; }
}
DEVI void tile_signal(int f) {
  bulk_wait<0>();
  asm volatile("fence.proxy.async.global;" ::: "memory");
  asm volatile("red.release.gpu.global.add.u32 [%0], 1;" ::"l"(g_flag + f) : "memory");
}

template <int BN, int STAGES, int NBUF, bool DYN>
__global__ void __launch_bounds__(384, 1) gemm_kernel(const __grid_constant__ GemmParams P) {
  constexpr int NB = BN / 64, STAGE_BYTES = 16384 + NB * 8192;
  extern __shared__ __align__(1024) uint8_t smem_raw[];
  __shared__ __align__(8) uint64_t bars[2 * STAGES];
  __shared__ int info[STAGES];
  const uint32_t base = (s2u(smem_raw) + 1023) & ~1023u;
  const uint32_t stg = base + STAGES * STAGE_BYTES;
  const uint32_t full = s2u(bars), empty = full + 8 * STAGES;
  const int tid = threadIdx.x, wg = tid >> 7;
  TL_START(P.id)
  if (tid == 0) {
    for (int i = 0; i < STAGES; i++) { mbar_init(full + 8 * i, 1); mbar_init(empty + 8 * i, DYN ? 2 : 4); }
    asm volatile("fence.mbarrier_init.release.cluster;" ::: "memory");
  }
  const uint32_t rk = blockIdx.x & 1;
  auto release = [&](int st) {
    mbar_arrive(empty + 8 * st);
    if (!DYN) asm volatile("{.reg .b32 r; mapa.shared::cluster.u32 r,%0,%1; mbarrier.arrive.shared::cluster.b64 _,[r];}" ::"r"(empty + 8 * st), "r"(rk ^ 1) : "memory");
  };
  if (DYN) __syncthreads();
  else asm volatile("barrier.cluster.arrive.aligned; barrier.cluster.wait.aligned;" ::: "memory");
  if (wg == 2) {
    reg_dec<40>();
    if (tid == 256) {
      int s = 0, ph = 1;
      int t = DYN ? (int)atomicAdd(&g_ctr[0], 1) : blockIdx.x;
      while (t < P.ntiles) {
        int pi, m0, n0; tile_decode<BN>(P, t, pi, m0, n0);
        const int nk = P.ksteps[pi];
        int tn = DYN ? (int)atomicAdd(&g_ctr[0], 1) : P.ntiles;
        for (int k = 0; k < nk; k++) {
          mbar_wait(empty + 8 * s, ph);
          if (k == 0) info[s] = t;
          mbar_expect(full + 8 * s, STAGE_BYTES);
          const uint32_t sa = base + s * STAGE_BYTES;
          tma_load(sa, &P.p[pi].a, k * 64, m0, full + 8 * s);
#pragma unroll
          for (int j = 0; j < NB; j++) {
            if (DYN) tma_load(sa + 16384 + j * 8192, &P.p[pi].b, n0 + j * 64, k * 64, full + 8 * s);
            else asm volatile("cp.async.bulk.tensor.2d.shared::cluster.global.mbarrier::complete_tx::bytes.multicast::cluster [%0],[%1,{%3,%4}],[%2],%5;"
                              ::"r"(sa + 16384 + j * 8192 + rk * 4096), "l"(&P.p[pi].b), "r"(full + 8 * s), "r"(n0 + j * 64), "r"(k * 64 + (int)rk * 32), "h"((uint16_t)3) : "memory");
          }
          if (++s == STAGES) { s = 0; ph ^= 1; }
        }
        t = tn;
      }
      mbar_wait(empty + 8 * s, ph);
      info[s] = -1;
      mbar_arrive(full + 8 * s);
      if (!DYN) for (int i = 1; i < STAGES; i++) { if (++s == STAGES) { s = 0; ph ^= 1; } mbar_wait(empty + 8 * s, ph); }
    }
  } else {
    reg_inc<232>();
    float acc[BN / 2];
    int s = 0, ph = 0, cbuf = 0, pend = -1;
    const int lane = tid & 31, warp = (tid >> 5) & 3;
    const uint32_t srow = warp * 16 + (lane & 7) + ((lane >> 3) & 1) * 8;
    while (true) {
      mbar_wait(full + 8 * s, ph);
      const int t = info[s];
      if (t < 0) break;
      int pi, m0, n0; tile_decode<BN>(P, t, pi, m0, n0);
      const int nk = P.ksteps[pi];
      int prev = 0;
      for (int k = 0; k < nk; k++) {
        if (k) mbar_wait(full + 8 * s, ph);
        const uint32_t sa = base + s * STAGE_BYTES;
        const uint64_t da = desc_k(sa + wg * 8192), db = desc_mn(sa + 16384, 8192);
        wg_fence();
#pragma unroll
        for (int kk = 0; kk < 4; kk++) {
          if constexpr (BN == 256) wg_ss256<1>(acc, da + kk * 2, db + kk * 128, k | kk);
          else wg_ss192<1>(acc, da + kk * 2, db + kk * 128, k | kk);
        }
        wg_commit();
        if (k) { wg_wait<1>(); if ((tid & 127) == 0) release(prev); }
        if (DYN && k == 2 && pend >= 0) { if ((tid & 127) == 0) tile_signal(pend); pend = -1; }
        prev = s;
        if (++s == STAGES) { s = 0; ph ^= 1; }
      }
      wg_wait<0>();
      if ((tid & 127) == 0) release(prev);
#pragma unroll
      for (int c = 0; c < NB; c++) {
        const uint32_t sb = stg + (wg * NBUF + cbuf) * 8192;
        if ((tid & 127) == 0) bulk_wait_read<NBUF - 1>();
        bar_sync(1 + wg, 128);
#pragma unroll
        for (int i = 0; i < 4; i++) {
          const float* a = acc + c * 32 + i * 8;
          stsm4(sb + srow * 128 + (((i * 2 + (lane >> 4)) ^ (srow & 7)) << 4), pack2(a[0], a[1]), pack2(a[2], a[3]), pack2(a[4], a[5]), pack2(a[6], a[7]));
        }
        fence_async();
        bar_sync(1 + wg, 128);
        if ((tid & 127) == 0) { tma_store(&P.p[pi].c, sb, n0 + c * 64, m0 + wg * 64); bulk_commit(); }
        if (++cbuf == NBUF) cbuf = 0;
      }
      if (DYN && t < P.nsig) pend = (m0 >> 3) + n0 / BN;
    }
    if ((tid & 127) == 0) { if (DYN && pend >= 0) tile_signal(pend); bulk_wait<0>(); }
    TL_END(P.id)
  }
}
#define FG 16
struct FaParams { CUtensorMap q, k, v, o; };

template <bool MASK>
DEVI void fa_softmax(float* S, float& m0, float& m1, float& l0, float& l1, float& f0, float& f1, int row, int colb) {
  constexpr float C = 0.08838834764831845f * 1.4426950408889634f;
  if (MASK) {
#pragma unroll
    for (int j = 0; j < 16; j++) {
      const int c = j * 8 + colb;
      if (c > row) S[4 * j] = -INFINITY;
      if (c + 1 > row) S[4 * j + 1] = -INFINITY;
      if (c > row + 8) S[4 * j + 2] = -INFINITY;
      if (c + 1 > row + 8) S[4 * j + 3] = -INFINITY;
    }
  }
  float a = m0, b = m1;
#pragma unroll
  for (int j = 0; j < 16; j++) { a = fmaxf(a, fmaxf(S[4 * j], S[4 * j + 1])); b = fmaxf(b, fmaxf(S[4 * j + 2], S[4 * j + 3])); }
  a = fmaxf(a, __shfl_xor_sync(~0u, a, 1)); b = fmaxf(b, __shfl_xor_sync(~0u, b, 1));
  a = fmaxf(a, __shfl_xor_sync(~0u, a, 2)); b = fmaxf(b, __shfl_xor_sync(~0u, b, 2));
  const float ac = a * C, bc = b * C;
  f0 = ex2(fmaf(m0, C, -ac)); f1 = ex2(fmaf(m1, C, -bc));
  m0 = a; m1 = b;
  float s0 = 0.f, s1 = 0.f;
#pragma unroll
  for (int j = 0; j < 16; j++) {
    S[4 * j] = ex2(fmaf(S[4 * j], C, -ac)); S[4 * j + 1] = ex2(fmaf(S[4 * j + 1], C, -ac));
    S[4 * j + 2] = ex2(fmaf(S[4 * j + 2], C, -bc)); S[4 * j + 3] = ex2(fmaf(S[4 * j + 3], C, -bc));
    s0 += S[4 * j] + S[4 * j + 1]; s1 += S[4 * j + 2] + S[4 * j + 3];
  }
  l0 = fmaf(l0, f0, s0); l1 = fmaf(l1, f1, s1);
}

__global__ void __launch_bounds__(384, 1) fa_kernel(const __grid_constant__ FaParams P) {
  extern __shared__ __align__(1024) uint8_t smem_raw[];
  __shared__ __align__(8) uint64_t bars[10];
  __shared__ int info;
  const uint32_t base = (s2u(smem_raw) + 1023) & ~1023u;
  const uint32_t sQ = base, sK = base + 32768, sV = base + 3 * 32768, sO = base + 5 * 32768;
  const uint32_t qf = s2u(bars), qe = qf + 8, kf = qf + 16, ke = qf + 32, vf = qf + 48, ve = qf + 64;
  const int tid = threadIdx.x, wg = tid >> 7;
  TL_START(3)
  if (tid == 0) {
    mbar_init(qf, 1); mbar_init(qe, 2);
    for (int i = 0; i < 2; i++) { mbar_init(kf + 8 * i, 1); mbar_init(ke + 8 * i, 2); mbar_init(vf + 8 * i, 1); mbar_init(ve + 8 * i, 2); }
    asm volatile("fence.mbarrier_init.release.cluster;" ::: "memory");
  }
  __syncthreads();
  if (wg == 2) {
    reg_dec<40>();
    if (tid == 256) {
      int it = 0, qph = 1;
      int w = atomicAdd(&g_ctr[1], 1);
      while (w < 512) {
        const int qt = 15 - (w % (16 * FG)) / FG, hc = (w / (16 * FG) * FG + w % FG) * 128;
        const int wn = atomicAdd(&g_ctr[1], 1);
        for (int j = qt; j >= 0; j--, it++) {
          const int s = it & 1, ph = ((it >> 1) & 1) ^ 1;
          mbar_wait(ke + 8 * s, ph);
          mbar_expect(kf + 8 * s, 32768);
          tma_load(sK + s * 32768, &P.k, hc, j * 128, kf + 8 * s);
          tma_load(sK + s * 32768 + 16384, &P.k, hc + 64, j * 128, kf + 8 * s);
          if (j == qt) {
            mbar_wait(qe, qph); qph ^= 1;
            info = w;
            mbar_expect(qf, 32768);
            tma_load(sQ, &P.q, hc, qt * 128, qf);
            tma_load(sQ + 16384, &P.q, hc + 64, qt * 128, qf);
          }
          mbar_wait(ve + 8 * s, ph);
          mbar_expect(vf + 8 * s, 32768);
          tma_load(sV + s * 32768, &P.v, hc, j * 128, vf + 8 * s);
          tma_load(sV + s * 32768 + 16384, &P.v, hc + 64, j * 128, vf + 8 * s);
        }
        w = wn;
      }
      mbar_wait(qe, qph);
      info = -1;
      mbar_arrive(qf);
    }
  } else {
    reg_inc<232>();
    const int lane = tid & 31, warp = (tid >> 5) & 3;
    const bool el = (tid & 127) == 0;
    const uint32_t srow = warp * 16 + (lane & 7) + ((lane >> 3) & 1) * 8;
    const uint64_t dq = desc_k(sQ + wg * 8192);
    float O[64], S[64];
    uint32_t Pr[32];
    int it = 0, qph = 0;
    if (wg == 1) bar_arrive(3, 256);
    auto issue_qk = [&](int s) {
      const uint64_t dk = desc_k(sK + s * 32768);
      wg_fence();
#pragma unroll
      for (int kk = 0; kk < 8; kk++) wg_ss128<0>(S, dq + (kk & 3) * 2 + (kk >> 2) * 1024, dk + (kk & 3) * 2 + (kk >> 2) * 1024, kk);
      wg_commit();
    };
    auto issue_pv = [&](int s) {
      const uint64_t dv = desc_mn(sV + s * 32768, 16384);
      wg_fence();
#pragma unroll
      for (int kk = 0; kk < 8; kk++) wg_rs128t(O, Pr[4 * kk], Pr[4 * kk + 1], Pr[4 * kk + 2], Pr[4 * kk + 3], dv + kk * 128);
      wg_commit();
    };
    auto cvt_p = [&]() {
#pragma unroll
      for (int i = 0; i < 32; i++) Pr[i] = pack2(S[2 * i], S[2 * i + 1]);
    };
    while (true) {
      mbar_wait(qf, qph); qph ^= 1;
      const int w = info;
      if (w < 0) break;
      const int qt = 15 - (w % (16 * FG)) / FG, hc = (w / (16 * FG) * FG + w % FG) * 128;
      float m0 = -INFINITY, m1 = -INFINITY, l0 = 0.f, l1 = 0.f, f0, f1;
      mbar_wait(kf + 8 * (it & 1), (it >> 1) & 1);
      bar_sync(3 + wg, 256);
      issue_qk(it & 1);
      bar_arrive(4 - wg, 256);
#pragma unroll
      for (int i = 0; i < 64; i++) O[i] = 0.f;
      wg_wait<0>();
      if (el) { mbar_arrive(ke + 8 * (it & 1)); if (qt == 0) mbar_arrive(qe); }
      fa_softmax<true>(S, m0, m1, l0, l1, f0, f1, wg * 64 + warp * 16 + (lane >> 2), (lane & 3) * 2);
      cvt_p();
      for (int j = qt - 1; j >= 0; j--) {
        const int sp = it & 1, php = (it >> 1) & 1;
        it++;
        const int s = it & 1, ph = (it >> 1) & 1;
        mbar_wait(kf + 8 * s, ph);
        bar_sync(3 + wg, 256);
        issue_qk(s);
        mbar_wait(vf + 8 * sp, php);
        issue_pv(sp);
        bar_arrive(4 - wg, 256);
        wg_wait<1>();
        if (el) { mbar_arrive(ke + 8 * s); if (j == 0) mbar_arrive(qe); }
        fa_softmax<false>(S, m0, m1, l0, l1, f0, f1, 0, 0);
        wg_wait<0>();
        if (el) mbar_arrive(ve + 8 * sp);
#pragma unroll
        for (int i = 0; i < 16; i++) { O[4 * i] *= f0; O[4 * i + 1] *= f0; O[4 * i + 2] *= f1; O[4 * i + 3] *= f1; }
        cvt_p();
      }
      mbar_wait(vf + 8 * (it & 1), (it >> 1) & 1);
      issue_pv(it & 1);
      l0 += __shfl_xor_sync(~0u, l0, 1); l1 += __shfl_xor_sync(~0u, l1, 1);
      l0 += __shfl_xor_sync(~0u, l0, 2); l1 += __shfl_xor_sync(~0u, l1, 2);
      const float r0 = 1.f / l0, r1 = 1.f / l1;
      if (el) bulk_wait_read<0>();
      wg_wait<0>();
      if (el) mbar_arrive(ve + 8 * (it & 1));
      it++;
      bar_sync(1 + wg, 128);
      const uint32_t sb = sO + wg * 16384;
#pragma unroll
      for (int i = 0; i < 8; i++) {
        const float* a = O + i * 8;
        stsm4(sb + (i >> 2) * 8192 + srow * 128 + ((((i & 3) * 2 + (lane >> 4)) ^ (srow & 7)) << 4), pack2(a[0] * r0, a[1] * r0),
              pack2(a[2] * r1, a[3] * r1), pack2(a[4] * r0, a[5] * r0), pack2(a[6] * r1, a[7] * r1));
      }
      fence_async();
      bar_sync(1 + wg, 128);
      if (el) {
        tma_store(&P.o, sb, hc, qt * 128 + wg * 64);
        tma_store(&P.o, sb + 8192, hc + 64, qt * 128 + wg * 64);
        bulk_commit();
      }
    }
    if (wg == 0) bar_sync(3, 256);
    if (el) bulk_wait<0>();
    TL_END(3)
  }
}
#define PS 20
#define PT(i)
#define GT(i)
#define YD 150
#define YS 120
#define NPF 4
#define NRES 6
#define VB 8
#define RP 208
#define PD 4
#define VA 1
#define VC 36
#define VG 2
#define VW 1
#define YE 0
#define SL 0
#define XI 1
#define NPE 4
#define NUP 2
#define VI 3
#define T0 0
#define T1 16
#define T2 24
#define KA 24
constexpr int R_WV = 0, R_WO = 73728, R_H = 147456, R_OX = R_H + 46080, R_Q = R_OX + 4096, R_K = R_Q + 5120, R_SX = R_K + 5120, R_P = R_SX + 3200, R_U = R_P + 3200,
              R_BAR = R_U + 4096, R_PROF = R_BAR + 128, R_END = R_PROF + 3072 + 1024;
constexpr int B_W0 = R_BAR, B_W1 = R_BAR + 8, B_XA = R_BAR + 16, B_XB = R_BAR + 24, B_XF = R_BAR + 32, B_Z0 = R_BAR + 40, B_Z1 = R_BAR + 48, B_Z2 = R_BAR + 56,
              B_SM = R_BAR + 64, B_SX = R_BAR + 72, B_U = R_BAR + 80, B_V = R_BAR + 88;
enum { N_P1 = 1, N_PM, N_PX, N_SUM, N_O, N_Y, N_INIT, N_WO, N_V, N_S };
constexpr int YSLOT = 9 * 16 * 1024;
struct RecParams { CUtensorMap wq, wk, wv, wo, x, ctx; const bf16 *mem0, *wo_raw; };

DEVI uint64_t mkdesc(uint32_t a, uint32_t lbo, uint32_t sbo, int sw) { return (uint64_t)((a >> 4) & 0x3fff) | ((uint64_t)(lbo >> 4) << 16) | ((uint64_t)(sbo >> 4) << 32) | ((uint64_t)sw << 62); }
DEVI void wg_rs32(float* d, const uint32_t* a, uint64_t db, int acc) {
  asm volatile("{.reg .pred p; setp.ne.b32 p,%21,0;\n wgmma.mma_async.sync.aligned.m64n32k16.f32.bf16.bf16 {%0,%1,%2,%3,%4,%5,%6,%7,%8,%9,%10,%11,%12,%13,%14,%15},{%16,%17,%18,%19},%20,p,1,1,0;}"
               : F8(d, 0), F8(d, 8) : "r"(a[0]), "r"(a[1]), "r"(a[2]), "r"(a[3]), "l"(db), "r"(acc));
}
DEVI void wg_rs40(float* d, const uint32_t* a, uint64_t db, int acc) {
  asm volatile("{.reg .pred p; setp.ne.b32 p,%25,0;\n wgmma.mma_async.sync.aligned.m64n40k16.f32.bf16.bf16 {%0,%1,%2,%3,%4,%5,%6,%7,%8,%9,%10,%11,%12,%13,%14,%15,%16,%17,%18,%19},{%20,%21,%22,%23},%24,p,1,1,0;}"
               : F8(d, 0), F8(d, 8), "+f"(d[16]), "+f"(d[17]), "+f"(d[18]), "+f"(d[19]) : "r"(a[0]), "r"(a[1]), "r"(a[2]), "r"(a[3]), "l"(db), "r"(acc));
}
template <int TB> DEVI void wg_ss40(float* d, uint64_t da, uint64_t db, int acc) {
  asm volatile("{.reg .pred p; setp.ne.b32 p,%22,0;\n wgmma.mma_async.sync.aligned.m64n40k16.f32.bf16.bf16 {%0,%1,%2,%3,%4,%5,%6,%7,%8,%9,%10,%11,%12,%13,%14,%15,%16,%17,%18,%19},%20,%21,p,1,1,1,%23;}"
               : F8(d, 0), F8(d, 8), "+f"(d[16]), "+f"(d[17]), "+f"(d[18]), "+f"(d[19]) : "l"(da), "l"(db), "r"(acc), "n"(TB));
}
DEVI void mma8(float* d, uint32_t a0, uint32_t a1, uint32_t b0) {
  asm volatile("mma.sync.aligned.m16n8k8.row.col.f32.bf16.bf16.f32 {%0,%1,%2,%3},{%4,%5},{%6},{%0,%1,%2,%3};" : "+f"(d[0]), "+f"(d[1]), "+f"(d[2]), "+f"(d[3]) : "r"(a0), "r"(a1), "r"(b0));
}
DEVI void stsm4t(uint32_t a, uint32_t r0, uint32_t r1, uint32_t r2, uint32_t r3) {
  asm volatile("stmatrix.sync.aligned.m8n8.x4.trans.shared.b16 [%0],{%1,%2,%3,%4};" ::"r"(a), "r"(r0), "r"(r1), "r"(r2), "r"(r3) : "memory");
}
DEVI uint32_t movm(uint32_t a) { uint32_t d; asm volatile("movmatrix.sync.aligned.m8n8.trans.b16 %0,%1;" : "=r"(d) : "r"(a)); return d; }
DEVI uint32_t mapa(uint32_t a, uint32_t r) { uint32_t o; asm("mapa.shared::cluster.u32 %0,%1,%2;" : "=r"(o) : "r"(a), "r"(r)); return o; }
DEVI void sts1(uint32_t a, uint32_t v) { asm volatile("st.shared.b32 [%0],%1;" ::"r"(a), "r"(v) : "memory"); }
DEVI void sts4(uint32_t a, uint32_t x, uint32_t y, uint32_t z, uint32_t w) { asm volatile("st.shared.v4.b32 [%0],{%1,%2,%3,%4};" ::"r"(a), "r"(x), "r"(y), "r"(z), "r"(w) : "memory"); }
DEVI uint32_t lds1(uint32_t a) { uint32_t v; asm volatile("ld.shared.b32 %0,[%1];" : "=r"(v) : "r"(a) : "memory"); return v; }
DEVI void lds4(uint32_t* r, uint32_t a) { asm volatile("ld.shared.v4.b32 {%0,%1,%2,%3},[%4];" : "=r"(r[0]), "=r"(r[1]), "=r"(r[2]), "=r"(r[3]) : "r"(a) : "memory"); }
DEVI void lds4f(float* r, uint32_t a) { asm volatile("ld.shared.v4.f32 {%0,%1,%2,%3},[%4];" : "=f"(r[0]), "=f"(r[1]), "=f"(r[2]), "=f"(r[3]) : "r"(a) : "memory"); }
DEVI void sta1(uint32_t d, uint32_t a, uint32_t bar) { asm volatile("st.async.weak.shared::cluster.mbarrier::complete_tx::bytes.b32 [%0],%1,[%2];" ::"r"(d), "r"(a), "r"(bar) : "memory"); }
DEVI void sta2(uint32_t d, uint32_t a, uint32_t b, uint32_t bar) { asm volatile("st.async.weak.shared::cluster.mbarrier::complete_tx::bytes.v2.b32 [%0],{%1,%2},[%3];" ::"r"(d), "r"(a), "r"(b), "r"(bar) : "memory"); }
DEVI void sta4f(uint32_t d, float a, float b, float c, float e, uint32_t bar) {
  asm volatile("st.async.weak.shared::cluster.mbarrier::complete_tx::bytes.v4.f32 [%0],{%1,%2,%3,%4},[%5];" ::"r"(d), "f"(a), "f"(b), "f"(c), "f"(e), "r"(bar) : "memory");
}
DEVI bool mbar_try(uint32_t b, uint32_t ph) {
  uint32_t ok;
  asm volatile("{.reg .pred p; mbarrier.try_wait.parity.shared::cta.b64 p,[%1],%2; selp.u32 %0,1,0,p;}" : "=r"(ok) : "r"(b), "r"(ph) : "memory");
  return ok;
}
DEVI void mwait(uint32_t b, uint32_t ph) { if (__builtin_expect(!mbar_try(b, ph), 0)) mbar_wait(b, ph); }
DEVI uint32_t clk32() { uint64_t c; asm volatile("mov.u64 %0,%%clock64;" : "=l"(c)::"memory"); return (uint32_t)c; }
DEVI int opq(int x) { asm volatile("" : "+r"(x)); return x; }
DEVI int pin(int x) { return __shfl_sync(~0u, x, threadIdx.x & 31); }
DEVI uint32_t zero_after(float x) { uint32_t t; asm volatile("{.reg .u32 t; popc.b32 t,%1; shr.u32 %0,t,6;}" : "=r"(t) : "r"(__float_as_uint(x))); return t; }
DEVI float blo(uint32_t u) { return __uint_as_float(u << 16); }
DEVI float bhi(uint32_t u) { return __uint_as_float(u & 0xffff0000u); }
DEVI void sta4(uint32_t d, uint32_t a, uint32_t b, uint32_t c, uint32_t e, uint32_t bar) {
  asm volatile("st.async.weak.shared::cluster.mbarrier::complete_tx::bytes.v4.b32 [%0],{%1,%2,%3,%4},[%5];" ::"r"(d), "r"(a), "r"(b), "r"(c), "r"(e), "r"(bar) : "memory");
}
DEVI void x_load(const RecParams& P, uint32_t sb, int c, int seg) {
  asm volatile("cp.async.bulk.tensor.2d.shared::cluster.global.mbarrier::complete_tx::bytes.multicast::cluster [%0],[%1,{%3,%4}],[%2],%5;"
               ::"r"(sb + R_H + c * 5120 + 1024), "l"(&P.x), "r"(sb + (c < 6 ? B_XA : B_XB)), "r"(c * 64), "r"(seg * 32), "h"((uint16_t)0xffff) : "memory");
  if (seg + 2 < NSEG) asm volatile("cp.async.bulk.prefetch.tensor.2d.L2.global [%0,{%1,%2}];" ::"l"(&P.x), "r"(c * 64), "r"(seg * 32 + 64) : "memory");
}
DEVI uint32_t hadd2(uint32_t a, uint32_t b) { uint32_t r; asm("add.rn.bf16x2 %0,%1,%2;" : "=r"(r) : "r"(a), "r"(b)); return r; }
DEVI uint32_t hmax2(uint32_t a, uint32_t b) { uint32_t r; asm("max.bf16x2 %0,%1,%2;" : "=r"(r) : "r"(a), "r"(b)); return r; }
DEVI float rcp(float x) { float y; asm("rcp.approx.ftz.f32 %0,%1;" : "=f"(y) : "f"(x)); return y; }
constexpr float SCL = 0.08838834764831845f * 1.4426950408889634f;

DEVI void y_store(const float* a, uint32_t off, int s) {
  const uint32_t x = movm(pack2(a[0], a[1])), y = movm(pack2(a[2], a[3]));
  const uint32_t tag = ((s >> 1) & 1) ^ 1;
  asm volatile("st.relaxed.gpu.global.b64 [%0],%1;" ::"l"((uint8_t*)g_Y + (s & 1) * YSLOT + off), "l"((uint64_t)((x & ~1u) | tag) | ((uint64_t)y << 32)) : "memory");
}
DEVI void y_load(uint32_t* w, const uint8_t* p) {
#pragma unroll
  for (int i = 0; i < 4; i++) asm volatile("{.reg .b64 t; ld.relaxed.gpu.global.b64 t,[%2]; mov.b64 {%0,%1},t;}" : "=r"(w[2 * i]), "=r"(w[2 * i + 1]) : "l"(p + i * 256) : "memory");
}
DEVI bool y_missing(const uint32_t* w, uint32_t tag) {
  uint32_t r;
  asm volatile("{.reg .b32 a,b; .reg .pred p; lop3.b32 a,%1,%2,%5,0x7e; lop3.b32 b,%3,%4,%5,0x7e; lop3.b32 a,a,b,1,0xa8; setp.ne.u32 p,a,0; vote.sync.any.pred p,p,0xffffffff; selp.u32 %0,1,0,p;}"
               : "=r"(r) : "r"(w[0]), "r"(w[2]), "r"(w[4]), "r"(w[6]), "r"(tag));
  return r;
}
DEVI void y_reload(uint32_t* w, const uint8_t* p, uint32_t tag) {
#pragma unroll
  for (int i = 0; i < 4; i++)
    asm volatile("{.reg .b64 t; .reg .b32 a; .reg .pred q; lop3.b32 a,%0,%3,1,0x28; setp.ne.u32 q,a,0; mov.b64 t,{%0,%1}; @q ld.relaxed.gpu.global.b64 t,[%2]; mov.b64 {%0,%1},t;}"
                 : "+r"(w[2 * i]), "+r"(w[2 * i + 1]) : "l"(p + i * 256), "r"(tag) : "memory");
}
DEVI void y_sum(uint32_t* r, const uint32_t* w, uint32_t sel) {
  float d0[4] = {0, 0, 0, 0}, d1[4] = {0, 0, 0, 0};
  mma16(d0, w[0], w[1], w[2], w[3], sel, sel); mma16(d1, w[4], w[5], w[6], w[7], sel, sel);
  r[0] = pack2(d0[0] + d1[0], d0[1] + d1[1]); r[1] = pack2(d0[2] + d1[2], d0[3] + d1[3]);
}
DEVI void y_send(const uint32_t* r, uint32_t sb, uint32_t dst, uint32_t bar, int lane) {
#pragma unroll
  for (int i = 0; i < 4; i++) { const uint32_t rs = mapa(sb, (lane & 3) * 4 + i); sta2(rs + dst, r[0], r[1], rs + bar); }
}
template <int NR, int NP, int NE, int UP> DEVI void wo_tile(const uint32_t (*A0)[4], uint32_t sb, int chunk, int cta, int lane, uint32_t yo, int s) {
  uint32_t u[8][4], A[16][4];
  const int tid = threadIdx.x;
  const uint32_t wa = sb + R_WO + chunk * 8192 + lane * 16, ua = sb + R_U + lane * 16;
  float a[4] = {0, 0, 0, 0}, b[4] = {0, 0, 0, 0};
  auto fetch = [&](int i) { if (i < 16 - NR) lds4(A[i], wa + i * 512); };
  auto uload = [&](int i) { if (i < 8) ldsm4t(u[i], ua + i * 512); };
#pragma unroll
  for (int i = 0; i < NE; i++) fetch(i);
  mwait(sb + B_V, s & 1);
  PT(6)
  uload(0); uload(1);
#pragma unroll
  for (int i = NE; i < NP; i++) fetch(i);
#pragma unroll
  for (int i = 0; i < 16; i++) {
    if (i == 4) {
      mwait(sb + B_U, s & 1);
      PT(7)
#pragma unroll
      for (int k = 2; k < 2 + UP; k++) uload(k);
    }
    const uint32_t* f = i >= 16 - NR ? A0[i >= 16 - NR ? i - 16 + NR : 0] : A[i];
    mma16(i & 1 ? b : a, f[0], f[1], f[2], f[3], u[i >> 1][(i & 1) * 2], u[i >> 1][(i & 1) * 2 + 1]);
    fetch(i + NP);
    if (i >= 4 && (i & 1)) uload((i >> 1) + UP);
  }
#pragma unroll
  for (int i = 0; i < 4; i++) a[i] += b[i];
  y_store(a, yo, s);
}
template <bool X> DEVI void softmax8(const uint32_t* h, uint32_t a4, uint32_t a1) {
  uint32_t y[5];
  lds4(y, a4 + R_SX); y[4] = lds1(a1 + R_SX);
#pragma unroll
  for (int j = 0; j < 5; j++) y[j] = hadd2(h[j], y[j]);
  const uint32_t m2 = hmax2(hmax2(hmax2(y[0], y[1]), hmax2(y[2], y[3])), y[4]);
  const float mc = fmaxf(blo(m2), bhi(m2)) * SCL;
  const float m1 = __shfl_xor_sync(~0u, mc, 1), m3 = __shfl_xor_sync(~0u, mc, 2), m4 = __shfl_xor_sync(~0u, mc, 3);
  float e[10];
#pragma unroll
  for (int j = 0; j < 5; j++) { e[2 * j] = ex2(fmaf(blo(y[j]), SCL, -mc)); e[2 * j + 1] = ex2(fmaf(bhi(y[j]), SCL, -mc)); }
  const float c = ex2(mc - fmaxf(fmaxf(mc, m1), fmaxf(m3, m4)));
  const float l = c * ((((e[0] + e[1]) + (e[2] + e[3])) + ((e[4] + e[5]) + (e[6] + e[7]))) + (e[8] + e[9]));
  const float r = c * rcp((l + __shfl_xor_sync(~0u, l, 1)) + (__shfl_xor_sync(~0u, l, 2) + __shfl_xor_sync(~0u, l, 3)));
#pragma unroll
  for (int j = 0; j < 5; j++) y[j] = pack2(e[2 * j] * r, e[2 * j + 1] * r);
  if (!X) sts4(a4 + R_P, y[0], y[1], y[2], y[3]);
  else stsm4(a4 + R_P, y[0], y[1], y[2], y[3]);
  sts1(a1 + R_P, y[4]);
  if (X) fence_async();
}

DEVI void rec_proj(const RecParams& P, const uint32_t sb, const int cta) {
  uint32_t W[36][4], A0[NRES ? NRES : 1][4];
  const int tid = pin(threadIdx.x);
  const uint32_t yo = pin(((threadIdx.x >> 2) * 2 + ((cta >> 1) & 1)) * 1024 + (cta >> 4) * 256 + (cta & 1) * 128 + ((cta >> 2) & 3) * 32 + (threadIdx.x & 3) * 8);
  const int warp = __shfl_sync(~0u, threadIdx.x >> 5, 0), role = warp >> 2;
  const uint32_t qk = sb + R_Q + warp * 1280;
  {
    const int lane = threadIdx.x & 31, w4 = (threadIdx.x >> 5) & 3;
    const uint32_t a = sb + role * R_WO + ((lane & 7) + (lane >> 4) * 8) * 128 + (((w4 * 2 + ((lane >> 3) & 1)) ^ (lane & 7)) << 4);
    mbar_wait(sb + B_W0, 0);
#pragma unroll
    for (int k = 0; k < 36; k++) ldsm4t(W[k], a + k * 2048);
    bar_arrive(N_INIT, 384);
    bar_sync(N_WO, 384);
#pragma unroll
    for (int i = 0; i < NRES; i++) lds4(A0[i], sb + R_WO + (threadIdx.x >> 5) * 8192 + lane * 16 + (16 - NRES + i) * 512);
  }
  for (int s = -1; s < NSEG; s++) {
    if (s >= 0) {
      PT(0)
      {
        const int lane = opq(tid) & 31;
        const uint32_t hb = sb + R_H + (lane & 7) * 128 + (((lane >> 3) ^ (lane & 7)) << 4);
        float a[4] = {0, 0, 0, 0}, b[4] = {0, 0, 0, 0};
        mwait(sb + B_Z0, (s - 1) & 1);
        PT(1) if (role) { GT(0) }
        uint32_t f[18][4];
#pragma unroll
        for (int c = -PD; c < 18; c++) {
          if (c + PD == 8) mwait(sb + B_Z1, (s - 1) & 1);
          if (c + PD < 18) ldsm4(f[c + PD], (hb ^ (((c + PD) & 1) * 64)) + ((c + PD) >> 1) * 5120);
          if (c >= 0) {
            mma16(a, W[2 * c][0], W[2 * c][1], W[2 * c][2], W[2 * c][3], f[c][0], f[c][1]);
            mma16(b, W[2 * c + 1][0], W[2 * c + 1][1], W[2 * c + 1][2], W[2 * c + 1][3], f[c][2], f[c][3]);
          }
        }
        sts1(qk + 512 + lane * 4, pack2(a[0] + b[0], a[1] + b[1]));
        sts1(qk + 1152 + lane * 4, pack2(a[2] + b[2], a[3] + b[3]));
        fence_async();
      }
      PT(2)
      const int lane = opq(tid) & 31;
      if (role) {
        bar_arrive(N_P1, 256);
        if (tid == 128) {
          mbar_expect(sb + B_SM, 640); mbar_expect(sb + B_SX, 2560); mbar_expect(sb + B_U, 3072);
          if (s < NSEG - 1) {
            mbar_expect(sb + B_Z0, 4096); mbar_expect(sb + B_Z1, 5120);
            mbar_expect(sb + B_XA, 24576); mbar_expect(sb + B_XB, 12288);
          }
        }
        const uint32_t o4 = sb + (warp - 4) * 640 + lane * 16, o1 = sb + (warp - 4) * 640 + 512 + lane * 4;
        uint32_t h[5];
        bar_sync(N_PX, 192);
        lds4(h, o4 + R_P); h[4] = lds1(o1 + R_P);
        mwait(sb + B_SX, s & 1);
        PT(4)
        softmax8<true>(h, o4, o1);
        PT(5)
      } else {
        float S[20];
        const uint64_t da = mkdesc(sb + R_Q, 640, 128, 0), db = mkdesc(sb + R_K, 640, 128, 0);
        const uint32_t rs = mapa(sb, (cta & 15) ^ 1);
        const uint32_t o4 = warp * 1280 + lane * 16, o1 = warp * 1280 + 512 + lane * 4;
        bar_sync(N_P1, 256);
        wg_fence();
#pragma unroll
        for (int k = 0; k < 4; k++) wg_ss40<1>(S, da + k * 80, db + k * 80, k);
        wg_commit();
        bar_arrive(N_S, 256);
        wg_wait<0>();
        PT(3)
        uint32_t h[2][5];
        if (warp == 2) {
#pragma unroll
          for (int j = 0; j < 5; j++) h[0][j] = pack2(S[4 * j], S[4 * j + 1]);
          sta4(rs + R_SX + o4, h[0][0], h[0][1], h[0][2], h[0][3], rs + B_SM); sta1(rs + R_SX + o1, h[0][4], rs + B_SM);
          mwait(sb + B_SM, s & 1);
          PT(4)
          softmax8<false>(h[0], sb + o4, sb + o1);
          bar_arrive(N_PM, 160);
        } else if (warp < 2) {
          const int row = warp * 16 + (lane >> 2) - (lane & 3) * 2;
#pragma unroll
          for (int g = 0; g < 2; g++) {
#pragma unroll
            for (int j = 0; j < 5; j++) h[g][j] = pack2(j < 4 && j * 8 > row + g * 8 ? -INFINITY : S[4 * j + 2 * g], j < 4 && j * 8 + 1 > row + g * 8 ? -INFINITY : S[4 * j + 2 * g + 1]);
            sts4(sb + R_P + o4 + g * 640, h[g][0], h[g][1], h[g][2], h[g][3]); sts1(sb + R_P + o1 + g * 640, h[g][4]);
            sta4(rs + R_SX + o4 + g * 640, h[g][0], h[g][1], h[g][2], h[g][3], rs + B_SX); sta1(rs + R_SX + o1 + g * 640, h[g][4], rs + B_SX);
          }
          bar_arrive(N_PX, 192);
        } else if (XI && tid == 96 && (cta & 15) < 6 && s < NSEG - 1) { mbar_wait(sb + B_XF, s & 1); x_load(P, sb, cta & 15, s + 1); }
        __syncwarp();
        PT(5)
      }
      {
        wo_tile<NRES, NPF, NPE, NUP>(A0, sb, warp, cta, lane, yo, s);
        if (role) { GT(1) }
        if (s == NSEG - 1) { bar_arrive(N_WO, 384); break; }
        PT(8)
        bar_sync(N_WO, 384);
      }
    }
    {
      float acc[16];
      const uint64_t db = mkdesc(sb + R_H + 1024, 16, 1024, 1);
      mwait(sb + B_XA, (s + 1) & 1);
      PT(9) if (role) { GT(2) }
      wg_fence();
#pragma unroll
      for (int k = 0; k < (KA < 24 ? KA : 24); k++) wg_rs32(acc, W[k], db + (k >> 2) * 320 + (k & 3) * 2, k);
      wg_commit();
      mwait(sb + B_XB, (s + 1) & 1);
      wg_fence();
#pragma unroll
      for (int k = 24; k < KA; k++) wg_rs32(acc, W[k], db + (k >> 2) * 320 + (k & 3) * 2, 1);
      wg_commit();
      wg_wait<0>();
      PT(10)
      if (s >= 0) bar_sync(N_SUM, 384);
      wg_fence();
#pragma unroll
      for (int k = KA; k < 36; k++) wg_rs32(acc, W[k], db + (k >> 2) * 320 + (k & 3) * 2, 1);
      wg_commit();
      const uint32_t o = qk + (opq(tid) & 31) * 16;
      wg_wait<0>();
      PT(11)
      stsm4(o, pack2(acc[0], acc[1]), pack2(acc[4], acc[5]), pack2(acc[8], acc[9]), pack2(acc[12], acc[13]));
      stsm4(o + 640, pack2(acc[2], acc[3]), pack2(acc[6], acc[7]), pack2(acc[10], acc[11]), pack2(acc[14], acc[15]));
    }
  }
}

DEVI void rec_aux(const RecParams& P, const uint32_t sb, const int cta) {
  const int tid = pin(threadIdx.x);
  bar_sync(N_INIT, 384);
  if (tid == 256) {
    mbar_expect(sb + B_W1, 2 * 73728);
    for (int i = 0; i < 3; i++) tma_load(sb + R_WV + i * 24576, &P.wv, cta * 64, i * 192, sb + B_W1);
    for (int i = 0; i < 36; i++) tma_load(sb + R_WO + i * 2048, &P.wo, (i >> 2) * 64 + (cta & 3) * 16, (cta ^ (i & 3)) * 64, sb + B_W1);
  }
  mbar_wait(sb + B_W1, 0);
  {
    const int lane = threadIdx.x & 31, g = lane >> 2;
    for (int i = (threadIdx.x >> 5) & 3; i < 144; i += 4) {
      uint32_t r[4];
      const uint32_t a = sb + R_WO + i * 512;
      ldsm4t(r, a + ((lane & 7) + (lane >> 4) * 8) * 32 + ((lane >> 3) & 1) * 16);
      __syncwarp();
#pragma unroll
      for (int m = 0; m < 4; m++) sts1(a + ((((m & 1) * 2 + (g >> 2)) * 2 + (g & 1)) * 4 + (lane & 3)) * 16 + ((m >> 1) * 2 + ((g >> 1) & 1)) * 4, r[m]);
    }
    bar_arrive(N_WO, 384);
  }
  const int rk = cta & 15, w4 = __shfl_sync(~0u, (threadIdx.x >> 5) & 3, 0);
  const uint32_t yg = pin((((threadIdx.x >> 5) & 3) * 16 + rk) * 1024 + ((threadIdx.x >> 4) & 1) * 128 + (threadIdx.x & 3) * 32 + ((threadIdx.x >> 2) & 3) * 8);
  uint32_t F[VB][4];
  auto v_prefetch = [&]() {
    const int lane = opq(tid) & 31;
    const uint32_t wv = sb + R_WV + ((lane & 7) + (lane >> 4) * 8) * 128 + (((w4 * 2 + ((lane >> 3) & 1)) ^ (lane & 7)) << 4);
#pragma unroll
    for (int k = 0; k < VB; k++) ldsm4t(F[k], wv + (VA + k * VI) * 2048);
  };
  v_prefetch();
  for (int s = 0; s < NSEG; s++) {
    const bool last = s == NSEG - 1;
    uint32_t va[12], p[5];
    int lane = opq(tid) & 31;
    {
      float acc[20];
      const uint64_t da = mkdesc(sb + R_WV, 0, 1024, 1), db = mkdesc(sb + R_H, 16, 1024, 1);
      PT(0)
      bar_sync(N_S, 256);
      asm volatile("fence.proxy.async::generic.acquire.sync_restrict::shared::cluster.cluster;" ::: "memory");
#pragma unroll
      for (int k = 0; k < 36; k++) {
        wg_fence();
        if (k >= VA && k < VA + VB * VI && (k - VA) % VI == 0) wg_rs40(acc, F[(k - VA) / VI], db + (k >> 2) * 320 + (k & 3) * 2, k);
        else wg_ss40<0>(acc, da + k * 128, db + (k >> 2) * 320 + (k & 3) * 2, k);
        wg_commit();
        if (k >= T0 && k < T1) wg_wait<VW>();
        else if (k >= T1 && k < T2) wg_wait<VW + 1>();
        if (k == 27) { wg_wait<4>(); asm volatile("{.reg .pred p; .reg .b32 a; setp.lt.u32 p,%1,%2; @p mapa.shared::cluster.u32 a,%0,%1; @p mbarrier.arrive.shared::cluster.b64 _,[a];}" ::"r"(sb + B_XF), "r"(tid - 256), "r"(last ? 0 : 6) : "memory"); }
      }
      PT(13)
      bar_sync(N_PM, 160);
      lds4(p, sb + R_P + 2560 + lane * 16); p[4] = lds1(sb + R_P + 3072 + lane * 4);
      wg_wait<0>();
      PT(1)
#pragma unroll
      for (int i = 0; i < 10; i++) va[i < 2 ? i + 8 : i - 2] = pack2(acc[2 * i], acc[2 * i + 1]);
      va[10] = va[11] = 0;
    }
    lane = opq(tid) & 31;
    {
      const uint32_t uo = R_U + w4 * 256 + lane * 4;
      float a[4] = {0, 0, 0, 0}, b[4] = {0, 0, 0, 0}, c[4] = {0, 0, 0, 0};
      mma16(a, va[0], va[1], va[2], va[3], p[0], p[1]); mma16(b, va[4], va[5], va[6], va[7], p[2], p[3]); mma8(c, va[8], va[9], p[4]);
      const uint32_t u0 = pack2(a[0] + b[0] + c[0], a[1] + b[1] + c[1]), u1 = pack2(a[2] + b[2] + c[2], a[3] + b[3] + c[3]);
      sts1(sb + uo, u0); sts1(sb + uo + 128, u1);
      __syncwarp();
      if (lane == 0) mbar_arrive(sb + B_V);
#pragma unroll
      for (int q = 1; q < 4; q++) { const uint32_t rs = mapa(sb, rk ^ q); sta1(rs + uo + q * 1024, u0, rs + B_U); sta1(rs + uo + q * 1024 + 128, u1, rs + B_U); }
      asm volatile("{.reg .pred p; .reg .b32 a; setp.lt.u32 p,%1,%3; @p mapa.shared::cluster.u32 a,%0,%2; @p mbarrier.arrive.shared::cluster.b64 _,[a];}" ::"r"(sb + B_XF), "r"(tid - 262), "r"(tid - 256), "r"(last ? 0 : 3) : "memory");
      PT(4)
      if (w4 == 3) {
        wo_tile<0, 8, 8, 2>(nullptr, sb, 8, cta, lane, ((64 + (lane >> 2)) * 2 + ((cta >> 1) & 1)) * 1024 + (cta >> 4) * 256 + (cta & 1) * 128 + ((cta >> 2) & 3) * 32 + (lane & 3) * 8, s);
      } else if (tid == 288 && rk < 9 && (!XI || rk >= 6) && !last) { mbar_wait(sb + B_XF, s & 1); x_load(P, sb, rk, s + 1); }
      PT(2)
    }
    lane = opq(tid) & 31;
    const uint8_t* y = (const uint8_t*)g_Y + (s & 1) * YSLOT + yg;
    uint32_t w0[8], w1[8], w2[8], ox[8];
    {
      float o[16];
      const uint64_t dp = mkdesc(sb + R_P, 128, 640, 0);
      bar_sync(N_WO, 384);
      wg_fence();
      wg_rs32(o, va, dp, 0); wg_rs32(o, va + 4, dp + 16, 1); wg_rs32(o, va + 8, mkdesc(sb + R_P + 512, 0, 640, 0), 1);
      wg_commit();
      const uint32_t tu = clk32();
      wg_wait<0>();
      PT(3)
#pragma unroll
      for (int i = 0; i < 8; i++) ox[i] = pack2(o[2 * i], o[2 * i + 1]);
      while (clk32() - tu < (uint32_t)YD) {}
      y_load(w0, y); y_load(w1, y + 4 * 16384);
      if (w4 == 0) y_load(w2, y + 8 * 16384);
      else {
#pragma unroll
        for (int i = 0; i < 8; i++) w2[i] = ((s >> 1) & 1) ^ 1;
      }
      PT(5)
    }
    if (!last) {
      const uint32_t dst = R_H + w4 * 5120 + (rk >> 1) * 128 + ((((rk & 1) * 4 + (lane >> 3)) ^ (rk >> 1)) << 4) + (lane & 4) * 2;
      const uint32_t tag = ((s >> 1) & 1) ^ 1, sel = (lane & 4) ? 0x3f800000u : 0x3f80u;
      uint32_t r0[2], r1[2], r2[2];
#pragma unroll 1
      for (int it = 0; (y_missing(w0, tag) | y_missing(w1, tag) | y_missing(w2, tag)) && it < (1 << 20); it++) {
        y_reload(w0, y, tag); y_reload(w1, y + 4 * 16384, tag); y_reload(w2, y + 8 * 16384, tag);
      }
      PT(7) GT(3)
      y_sum(r0, w0, sel); y_sum(r1, w1, sel); y_sum(r2, w2, sel);
      if (SL == 0) bar_arrive(N_SUM + zero_after(__uint_as_float(r2[0])), 384);
      y_send(r0, sb, dst, B_Z0, lane);
      if (SL == 1) bar_arrive(N_SUM, 384);
      y_send(r1, sb, dst + 4 * 5120, B_Z1, lane);
      if (w4 == 0) y_send(r2, sb, dst + 8 * 5120, B_Z1, lane);
      if (SL == 2) bar_arrive(N_SUM, 384);
      PT(9) GT(4)
    }
#pragma unroll
    for (int h = 0; h < 2; h++) stsm4t(sb + R_OX + lane * 128 + (((w4 * 2 + h) ^ (lane & 7)) << 4), ox[h], ox[2 + h], ox[4 + h], ox[6 + h]);
    v_prefetch();
    fence_async();
    bar_sync(N_O, 128);
    if (tid == 288) { tma_store(&P.ctx, sb + R_OX, cta * 64, s * 32); bulk_commit(); bulk_wait_read<0>(); }
    __syncwarp();
    PT(11)
  }
  if (tid == 288) bulk_wait<0>();
}

__global__ void __launch_bounds__(384, 1) rec_kernel(const __grid_constant__ RecParams P) {
  extern __shared__ __align__(1024) uint8_t smem_raw[];
  const uint32_t sb = (s2u(smem_raw) + 1023) & ~1023u;
  const int tid = threadIdx.x, cta = blockIdx.x;
  TL_START(1)
  if (tid == 0) {
    for (int i = 0; i < 12; i++) mbar_init(sb + R_BAR + 8 * i, 8 * i == B_XF - R_BAR ? 16 : 8 * i == B_V - R_BAR ? 4 : 1);
    asm volatile("fence.mbarrier_init.release.cluster;" ::: "memory");
    mbar_expect(sb + B_W0, 2 * 73728);
    for (int i = 0; i < 3; i++) { tma_load(sb + R_WV + i * 24576, &P.wq, cta * 64, i * 192, sb + B_W0); tma_load(sb + R_WO + i * 24576, &P.wk, cta * 64, i * 192, sb + B_W0); }
    mbar_expect(sb + B_XA, 24576); mbar_expect(sb + B_XB, 12288);
    for (int i = 0; i < 3; i++) asm volatile("cp.async.bulk.prefetch.tensor.2d.L2.global [%0,{%1,%2}];" ::"l"(&P.wv), "r"(cta * 64), "r"(i * 192) : "memory");
    asm volatile("cp.async.bulk.prefetch.L2.global [%0],%1;" ::"l"(P.wo_raw + cta * 64 * DM), "r"(64 * DM * 2) : "memory");
  }
  for (int i = tid; i < 576; i += 384) {
    const int t = i / 72, c = i - t * 72;
    const uint4 v = ((const uint4*)P.mem0)[i];
    sts4(sb + R_H + (c >> 3) * 5120 + t * 128 + (((c & 7) ^ t) << 4), v.x, v.y, v.z, v.w);
  }
  fence_async();
  asm volatile("barrier.cluster.arrive.aligned; barrier.cluster.wait.aligned;" ::: "memory");
  if (tid == 0 && (cta & 15) < 9) {
    x_load(P, sb, cta & 15, 0);
    asm volatile("cp.async.bulk.prefetch.tensor.2d.L2.global [%0,{%1,%2}];" ::"l"(&P.x), "r"((cta & 15) * 64), "r"(32) : "memory");
  }
  if (tid >= 256) { reg_dec<504 - 2 * RP>(); rec_aux(P, sb, cta); }
  else { reg_inc<RP>(); rec_proj(P, sb, cta); }
  TL_END(1)
  asm volatile("barrier.cluster.arrive.aligned; barrier.cluster.wait.aligned;" ::: "memory");
}
typedef CUresult (*EncFn)(CUtensorMap*, CUtensorMapDataType, cuuint32_t, void*, const cuuint64_t*, const cuuint64_t*, const cuuint32_t*, const cuuint32_t*,
                          CUtensorMapInterleave, CUtensorMapSwizzle, CUtensorMapL2promotion, CUtensorMapFloatOOBfill);
static EncFn g_enc;
static CUtensorMap mk(const void* p, uint64_t cols, uint64_t rows, uint64_t pitch_elems, uint32_t box_rows, uint32_t box_cols = 64) {
  CUtensorMap m;
  cuuint64_t dim[2] = {cols, rows}, str[1] = {pitch_elems * 2};
  cuuint32_t box[2] = {box_cols, box_rows}, es[2] = {1, 1};
  g_enc(&m, CU_TENSOR_MAP_DATA_TYPE_BFLOAT16, 2, (void*)p, dim, str, box, es, CU_TENSOR_MAP_INTERLEAVE_NONE, box_cols == 64 ? CU_TENSOR_MAP_SWIZZLE_128B : CU_TENSOR_MAP_SWIZZLE_NONE,
        CU_TENSOR_MAP_L2_PROMOTION_L2_256B, CU_TENSOR_MAP_FLOAT_OOB_FILL_NONE);
  return m;
}
template <class T> static void* sym(T& s) { void* p; cudaGetSymbolAddress(&p, s); return p; }

extern "C" void kernel_launch(void* const* d_in, const int* in_sizes, int n_in, void* d_out, int out_size) {
  static cudaStream_t s2;
  static cudaEvent_t e1, e2;
  static int nsm;
  constexpr int SM_P = 4 * 49152 + 4 * 8192 + 1024, SM_O = 4 * 40960 + 6 * 8192 + 1024, SM_F = 6 * 32768 + 1024;
  if (!g_enc) {
    cudaDriverEntryPointQueryResult qr;
    cudaGetDriverEntryPoint("cuTensorMapEncodeTiled", (void**)&g_enc, cudaEnableDefault, &qr);
    int lo, hi;
    cudaDeviceGetStreamPriorityRange(&lo, &hi);
    cudaStreamCreateWithPriority(&s2, cudaStreamNonBlocking, hi);
    cudaEventCreateWithFlags(&e1, cudaEventDisableTiming);
    cudaEventCreateWithFlags(&e2, cudaEventDisableTiming);
    cudaDeviceGetAttribute(&nsm, cudaDevAttrMultiProcessorCount, 0);
    cudaFuncSetAttribute(gemm_kernel<256, 4, 2, true>, cudaFuncAttributeMaxDynamicSharedMemorySize, SM_P);
    cudaFuncSetAttribute(gemm_kernel<192, 4, 3, false>, cudaFuncAttributeMaxDynamicSharedMemorySize, SM_O);
    cudaFuncSetAttribute(fa_kernel, cudaFuncAttributeMaxDynamicSharedMemorySize, SM_F);
    cudaFuncSetAttribute(rec_kernel, cudaFuncAttributeMaxDynamicSharedMemorySize, R_END);
    cudaFuncSetAttribute(rec_kernel, cudaFuncAttributeNonPortableClusterSizeAllowed, 1);
  }
  const bf16 *Ax = (const bf16*)d_in[0], *Ac = (const bf16*)d_in[1], *Awq = (const bf16*)d_in[2], *Awk = (const bf16*)d_in[3], *Awv = (const bf16*)d_in[4],
             *Awo = (const bf16*)d_in[5], *Bx = (const bf16*)d_in[6], *Bm = (const bf16*)d_in[7], *Bwq = (const bf16*)d_in[8], *Bwk = (const bf16*)d_in[9],
             *Bwv = (const bf16*)d_in[10], *Bwo = (const bf16*)d_in[11];
  bf16* out = (bf16*)d_out;
  cudaStream_t s1 = cudaStreamPerThread;
  auto proj = [&](GemmParams& g, int i, const bf16* a, int K, const bf16* w, void* c) {
    g.p[i].a = mk(a, K, SEQ, K, 128); g.p[i].b = mk(w, HD, K, HD, 64); g.p[i].c = mk(c, HD, SEQ, HD, 64);
    g.ksteps[i] = K / 64; g.tile_end[i] = (i + 1) * 256; g.ntiles = (i + 1) * 256;
  };
  GemmParams g2 = {}, g3 = {};
  proj(g2, 0, Ac, 512, Awk, sym(g_kA)); proj(g2, 1, Ac, 512, Awv, sym(g_vA)); proj(g2, 2, Ax, DM, Awq, sym(g_qA));
  for (int i = 0; i < 2; i++) {
    g3.p[i].a = mk(i ? sym(g_ctxB) : sym(g_ctxA), HD, SEQ, HD, 128); g3.p[i].b = mk(i ? Bwo : Awo, DM, HD, DM, 32);
    g3.p[i].c = mk(out + i * DM, DM, SEQ, 2 * DM, 64); g3.ksteps[i] = 64; g3.tile_end[i] = (i + 1) * 48;
  }
  g3.ntiles = 96; g2.id = 2; g3.id = 5;
  FaParams f;
  f.q = mk(sym(g_qA), HD, SEQ, HD, 128); f.k = mk(sym(g_kA), HD, SEQ, HD, 128); f.v = mk(sym(g_vA), HD, SEQ, HD, 128); f.o = mk(sym(g_ctxA), HD, SEQ, HD, 64);

  clear_kernel<<<nsm, 256, 0, s1>>>();
  cudaEventRecord(e1, s1);
  cudaStreamWaitEvent(s2, e1, 0);
  RecParams r;
  r.wq = mk(Bwq, HD, DM, HD, 192); r.wk = mk(Bwk, HD, DM, HD, 192); r.wv = mk(Bwv, HD, DM, HD, 192); r.wo = mk(Bwo, DM, HD, DM, 64, 16); r.wo_raw = Bwo;
  r.x = mk(Bx, DM, SEQ, DM, 32); r.ctx = mk(sym(g_ctxB), HD, SEQ, HD, 32); r.mem0 = Bm;
  {
    cudaLaunchConfig_t c = {};
    cudaLaunchAttribute at; at.id = cudaLaunchAttributeClusterDimension; at.val.clusterDim.x = 16; at.val.clusterDim.y = at.val.clusterDim.z = 1;
    c.gridDim = 64; c.blockDim = 384; c.dynamicSmemBytes = R_END; c.stream = s2; c.attrs = &at; c.numAttrs = 1;
    cudaLaunchKernelEx(&c, rec_kernel, r);
  }
  cudaEventRecord(e2, s2);
  gemm_kernel<256, 4, 2, true><<<nsm - 64, 384, SM_P, s1>>>(g2);
  fa_kernel<<<nsm, 384, SM_F, s1>>>(f);
  cudaStreamWaitEvent(s1, e2, 0);
  cudaLaunchConfig_t c = {};
  cudaLaunchAttribute at; at.id = cudaLaunchAttributeClusterDimension; at.val.clusterDim.x = 2; at.val.clusterDim.y = at.val.clusterDim.z = 1;
  c.gridDim = 96; c.blockDim = 384; c.dynamicSmemBytes = SM_O; c.stream = s1; c.attrs = &at; c.numAttrs = 1;
  cudaLaunchKernelEx(&c, gemm_kernel<192, 4, 3, false>, g3);
}
```

```cpp
#include <cuda_runtime.h>
#include <cuda_bf16.h>
#include <cuda.h>
#include <stdint.h>

typedef __nv_bfloat16 bf16;
#define DEVI __device__ __forceinline__
#define WAIT_FAIL(code) break
#define WAIT_MAX (1 << 22)

constexpr int SEQ = 2048, HD = 4096, DM = 576, NSEG = 64;

__device__ __align__(1024) bf16 g_qA[SEQ * HD], g_kA[SEQ * HD], g_vA[SEQ * HD];
__device__ __align__(1024) bf16 g_ctxB[SEQ * HD];
__device__ __align__(1024) uint4 g_Y[2 * 9 * 16 * 64];
enum { S_QUEUE = 0, S_EXIT = 1, S_PROJ = 32, S_CTXA = 64, S_CTXB = 96 };
__device__ unsigned g_sync[128];
#define CT(k, i) {}
#define TL_START(i)
#define TL_END(i)

DEVI uint32_t s2u(const void* p) { return (uint32_t)__cvta_generic_to_shared(p); }
DEVI void mbar_init(uint32_t b, uint32_t c) { asm volatile("mbarrier.init.shared::cta.b64 [%0],%1;" ::"r"(b), "r"(c)); }
DEVI void mbar_expect(uint32_t b, uint32_t n) { asm volatile("mbarrier.arrive.expect_tx.shared::cta.b64 _,[%0],%1;" ::"r"(b), "r"(n) : "memory"); }
DEVI void mbar_arrive(uint32_t b) { asm volatile("mbarrier.arrive.shared::cta.b64 _,[%0];" ::"r"(b) : "memory"); }
DEVI void mbar_wait(uint32_t b, uint32_t ph) {
  uint32_t ok; int it = 0;
  do {
    asm volatile("{.reg .pred p; mbarrier.try_wait.parity.shared::cta.b64 p,[%1],%2; selp.u32 %0,1,0,p;}" : "=r"(ok) : "r"(b), "r"(ph) : "memory");
    if (!ok && ++it > WAIT_MAX) WAIT_FAIL(b & 0xffffff);
  } while (!ok);
}
DEVI bool mbar_try(uint32_t b, uint32_t ph) {
  uint32_t ok;
  asm volatile("{.reg .pred p; mbarrier.try_wait.parity.shared::cta.b64 p,[%1],%2; selp.u32 %0,1,0,p;}" : "=r"(ok) : "r"(b), "r"(ph) : "memory");
  return ok;
}
DEVI bool mbar_test(uint32_t b, uint32_t ph) {
  uint32_t ok;
  asm volatile("{.reg .pred p; mbarrier.test_wait.parity.shared::cta.b64 p,[%1],%2; selp.u32 %0,1,0,p;}" : "=r"(ok) : "r"(b), "r"(ph) : "memory");
  return ok;
}
DEVI void mwait(uint32_t b, uint32_t ph) { if (__builtin_expect(!mbar_try(b, ph), 0)) mbar_wait(b, ph); }
DEVI void tma_load(uint32_t dst, const CUtensorMap* tm, int c0, int c1, uint32_t bar) {
  asm volatile("cp.async.bulk.tensor.2d.shared::cluster.global.mbarrier::complete_tx::bytes [%0],[%1,{%3,%4}],[%2];" ::"r"(dst), "l"(tm), "r"(bar), "r"(c0), "r"(c1) : "memory");
}
DEVI void tma_store(const CUtensorMap* tm, uint32_t src, int c0, int c1) {
  asm volatile("cp.async.bulk.tensor.2d.global.shared::cta.bulk_group [%0,{%2,%3}],[%1];" ::"l"(tm), "r"(src), "r"(c0), "r"(c1) : "memory");
}
DEVI void bulk_commit() { asm volatile("cp.async.bulk.commit_group;" ::: "memory"); }
template <int N> DEVI void bulk_wait_read() { asm volatile("cp.async.bulk.wait_group.read %0;" ::"n"(N) : "memory"); }
template <int N> DEVI void bulk_wait() { asm volatile("cp.async.bulk.wait_group %0;" ::"n"(N) : "memory"); }
DEVI void fence_async() { asm volatile("fence.proxy.async.shared::cta;" ::: "memory"); }
DEVI void bar_sync(int id, int n) { asm volatile("bar.sync %0,%1;" ::"r"(id), "r"(n) : "memory"); }
DEVI void bar_arrive(int id, int n) { asm volatile("bar.arrive %0,%1;" ::"r"(id), "r"(n) : "memory"); }
template <int R> DEVI void reg_inc() { asm volatile("setmaxnreg.inc.sync.aligned.u32 %0;" ::"n"(R)); }
template <int R> DEVI void reg_dec() { asm volatile("setmaxnreg.dec.sync.aligned.u32 %0;" ::"n"(R)); }
DEVI void wg_fence() { asm volatile("wgmma.fence.sync.aligned;" ::: "memory"); }
DEVI void wg_commit() { asm volatile("wgmma.commit_group.sync.aligned;" ::: "memory"); }
template <int N> DEVI void wg_wait() { asm volatile("wgmma.wait_group.sync.aligned %0;" ::"n"(N) : "memory"); }
DEVI uint64_t desc_k(uint32_t a) { return (uint64_t)((a >> 4) & 0x3fff) | (1ull << 16) | (64ull << 32) | (1ull << 62); }
DEVI uint64_t desc_mn(uint32_t a, uint32_t lbo) { return (uint64_t)((a >> 4) & 0x3fff) | ((uint64_t)(lbo >> 4) << 16) | (64ull << 32) | (1ull << 62); }
DEVI uint32_t pack2(float lo, float hi) { uint32_t r; asm("cvt.rn.bf16x2.f32 %0,%1,%2;" : "=r"(r) : "f"(hi), "f"(lo)); return r; }
DEVI float ex2(float x) { float y; asm("ex2.approx.ftz.f32 %0,%1;" : "=f"(y) : "f"(x)); return y; }
DEVI void stsm4(uint32_t a, uint32_t r0, uint32_t r1, uint32_t r2, uint32_t r3) {
  asm volatile("stmatrix.sync.aligned.m8n8.x4.shared.b16 [%0],{%1,%2,%3,%4};" ::"r"(a), "r"(r0), "r"(r1), "r"(r2), "r"(r3) : "memory");
}
DEVI void ldsm4(uint32_t* r, uint32_t a) {
  asm volatile("ldmatrix.sync.aligned.m8n8.x4.shared.b16 {%0,%1,%2,%3},[%4];" : "=r"(r[0]), "=r"(r[1]), "=r"(r[2]), "=r"(r[3]) : "r"(a) : "memory");
}
DEVI void ldsm4t(uint32_t* r, uint32_t a) {
  asm volatile("ldmatrix.sync.aligned.m8n8.x4.trans.shared.b16 {%0,%1,%2,%3},[%4];" : "=r"(r[0]), "=r"(r[1]), "=r"(r[2]), "=r"(r[3]) : "r"(a) : "memory");
}
DEVI void mma16(float* d, uint32_t a0, uint32_t a1, uint32_t a2, uint32_t a3, uint32_t b0, uint32_t b1) {
  asm volatile("mma.sync.aligned.m16n8k16.row.col.f32.bf16.bf16.f32 {%0,%1,%2,%3},{%4,%5,%6,%7},{%8,%9},{%0,%1,%2,%3};"
               : "+f"(d[0]), "+f"(d[1]), "+f"(d[2]), "+f"(d[3]) : "r"(a0), "r"(a1), "r"(a2), "r"(a3), "r"(b0), "r"(b1));
}

DEVI void pdl_trigger() { asm volatile("griddepcontrol.launch_dependents;" ::: "memory"); }
DEVI void signal_after_bulk(int f) {
  asm volatile("fence.proxy.async.global;" ::: "memory");
  asm volatile("red.release.gpu.global.add.u32 [%0], 1;" ::"l"(g_sync + f) : "memory");
}
DEVI void flag_wait(int f, unsigned n, unsigned waiters) {
  for (int it = 0;; it++) {
    if (it > WAIT_MAX) WAIT_FAIL(f);
    unsigned v; asm volatile("ld.acquire.gpu.global.u32 %0, [%1];" : "=r"(v) : "l"(g_sync + f) : "memory");
    if (v >= n) break;
    __nanosleep(64);
  }
  if (waiters) asm volatile("red.relaxed.gpu.global.inc.u32 [%0], %1;" ::"l"(g_sync + f), "r"(n + waiters - 1) : "memory");
  asm volatile("fence.proxy.async.global;" ::: "memory");
}
DEVI uint32_t mapa(uint32_t a, uint32_t r) { uint32_t o; asm("mapa.shared::cluster.u32 %0,%1,%2;" : "=r"(o) : "r"(a), "r"(r)); return o; }
DEVI void tma_load_mc(uint32_t dst, const CUtensorMap* tm, int c0, int c1, uint32_t bar, uint16_t mask) {
  asm volatile("cp.async.bulk.tensor.2d.shared::cluster.global.mbarrier::complete_tx::bytes.multicast::cluster [%0],[%1,{%3,%4}],[%2],%5;" ::"r"(dst), "l"(tm), "r"(bar), "r"(c0), "r"(c1), "h"(mask) : "memory");
}
DEVI void arrive_pair(uint32_t b) { if ((threadIdx.x & 127) < 2) asm volatile("mbarrier.arrive.shared::cluster.b64 _,[%0];" ::"r"(mapa(b, threadIdx.x & 1)) : "memory"); }
DEVI void cluster_sync_relaxed() { asm volatile("barrier.cluster.arrive.relaxed.aligned; barrier.cluster.wait.aligned;" ::: "memory"); }
DEVI void cluster_sync() { asm volatile("barrier.cluster.arrive.aligned; barrier.cluster.wait.aligned;" ::: "memory"); }
DEVI void sts4(uint32_t a, uint32_t x, uint32_t y, uint32_t z, uint32_t w) { asm volatile("st.shared.v4.b32 [%0],{%1,%2,%3,%4};" ::"r"(a), "r"(x), "r"(y), "r"(z), "r"(w) : "memory"); }
DEVI void lds4(uint32_t* r, uint32_t a) { asm volatile("ld.shared.v4.b32 {%0,%1,%2,%3},[%4];" : "=r"(r[0]), "=r"(r[1]), "=r"(r[2]), "=r"(r[3]) : "r"(a) : "memory"); }
DEVI void sta4(uint32_t d, uint32_t a, uint32_t b, uint32_t c, uint32_t e, uint32_t bar) {
  asm volatile("st.async.weak.shared::cluster.mbarrier::complete_tx::bytes.v4.b32 [%0],{%1,%2,%3,%4},[%5];" ::"r"(d), "r"(a), "r"(b), "r"(c), "r"(e), "r"(bar) : "memory");
}
DEVI float blo(uint32_t u) { return __uint_as_float(u << 16); }
DEVI float bhi(uint32_t u) { return __uint_as_float(u & 0xffff0000u); }

#define F8(a, o) "+f"(a[o]), "+f"(a[o + 1]), "+f"(a[o + 2]), "+f"(a[o + 3]), "+f"(a[o + 4]), "+f"(a[o + 5]), "+f"(a[o + 6]), "+f"(a[o + 7])
#define F32(a, o) F8(a, o), F8(a, o + 8), F8(a, o + 16), F8(a, o + 24)
template<int TB> DEVI void wg_ss128(float* d, uint64_t da, uint64_t db, int acc){
 asm volatile("{.reg .pred p; setp.ne.b32 p,%66,0;\n wgmma.mma_async.sync.aligned.m64n128k16.f32.bf16.bf16 {%0,%1,%2,%3,%4,%5,%6,%7,%8,%9,%10,%11,%12,%13,%14,%15,%16,%17,%18,%19,%20,%21,%22,%23,%24,%25,%26,%27,%28,%29,%30,%31,%32,%33,%34,%35,%36,%37,%38,%39,%40,%41,%42,%43,%44,%45,%46,%47,%48,%49,%50,%51,%52,%53,%54,%55,%56,%57,%58,%59,%60,%61,%62,%63},%64,%65,p,1,1,0,%67;}"
 : F32(d,0),F32(d,32) : "l"(da),"l"(db),"r"(acc),"n"(TB));}
template<int TB> DEVI void wg_ss192(float* d, uint64_t da, uint64_t db, int acc){
 asm volatile("{.reg .pred p; setp.ne.b32 p,%98,0;\n wgmma.mma_async.sync.aligned.m64n192k16.f32.bf16.bf16 {%0,%1,%2,%3,%4,%5,%6,%7,%8,%9,%10,%11,%12,%13,%14,%15,%16,%17,%18,%19,%20,%21,%22,%23,%24,%25,%26,%27,%28,%29,%30,%31,%32,%33,%34,%35,%36,%37,%38,%39,%40,%41,%42,%43,%44,%45,%46,%47,%48,%49,%50,%51,%52,%53,%54,%55,%56,%57,%58,%59,%60,%61,%62,%63,%64,%65,%66,%67,%68,%69,%70,%71,%72,%73,%74,%75,%76,%77,%78,%79,%80,%81,%82,%83,%84,%85,%86,%87,%88,%89,%90,%91,%92,%93,%94,%95},%96,%97,p,1,1,0,%99;}"
 : F32(d,0),F32(d,32),F32(d,64) : "l"(da),"l"(db),"r"(acc),"n"(TB));}
template<int TB> DEVI void wg_rs128(float* d, const uint32_t* a, uint64_t db, int acc){
 asm volatile("{.reg .pred p; setp.ne.b32 p,%69,0;\n wgmma.mma_async.sync.aligned.m64n128k16.f32.bf16.bf16 {%0,%1,%2,%3,%4,%5,%6,%7,%8,%9,%10,%11,%12,%13,%14,%15,%16,%17,%18,%19,%20,%21,%22,%23,%24,%25,%26,%27,%28,%29,%30,%31,%32,%33,%34,%35,%36,%37,%38,%39,%40,%41,%42,%43,%44,%45,%46,%47,%48,%49,%50,%51,%52,%53,%54,%55,%56,%57,%58,%59,%60,%61,%62,%63},{%64,%65,%66,%67},%68,p,1,1,%70;}"
 : F32(d,0),F32(d,32) : "r"(a[0]),"r"(a[1]),"r"(a[2]),"r"(a[3]),"l"(db),"r"(acc),"n"(TB));}
struct ProjItem { uint8_t pa, m, c0[2], n[2]; };
struct ProjParams { CUtensorMap a[2], w[3], c[3]; ProjItem item[64]; int nitems; };
#define PWD 1
constexpr int PST = 12, SM_P = PST * 16384 + 32768 + 256;
DEVI void proj_decode(const ProjItem& I, int t, int& pw, int& n) {
  const int g = t >= I.n[0], c = g ? I.c0[1] + t - I.n[0] : I.c0[0] + t;
  pw = I.pa ? 2 : c >> 4; n = (c & 15) + g * 16;
}
__global__ void __launch_bounds__(384, 1) proj_kernel(const __grid_constant__ ProjParams P) {
  extern __shared__ __align__(1024) uint8_t smem_raw[];
  const uint32_t base = __shfl_sync(~0u, s2u(smem_raw), 0), stg = base + PST * 16384, full = stg + 32768, empty = full + 8 * PST, of = empty + 8 * PST, oe = of + 16;
  const int tid = threadIdx.x, wg = __shfl_sync(~0u, tid >> 7, 0);
  TL_START(2)
  pdl_trigger();
  if (tid == 0) {
    for (int i = 0; i < PST; i++) { mbar_init(full + 8 * i, 1); mbar_init(empty + 8 * i, 4); }
    for (int i = 0; i < 2; i++) { mbar_init(of + 8 * i, 4); mbar_init(oe + 8 * i, 1); }
    asm volatile("fence.mbarrier_init.release.cluster;" ::: "memory");
  }
  cluster_sync_relaxed();
  if (wg == 2) {
    reg_dec<24>();
    const int r = blockIdx.x & 1;
    if (tid == 256) {
      int s = 0, ph = 1;
      for (int it = blockIdx.x >> 1; it < P.nitems; it += gridDim.x >> 1) {
        const ProjItem& I = P.item[it];
        const int nk = 8 + I.pa;
        for (int t = -1; t < I.n[0] + I.n[1]; t++) {
          int pw, n; proj_decode(I, t, pw, n);
          for (int k = 0; k < nk; k++) {
            mbar_wait(empty + 8 * s, ph);
            mbar_expect(full + 8 * s, 16384);
            if (t < 0) tma_load(base + s * 16384, &P.a[I.pa], k * 64, (I.m * 2 + r) * 128, full + 8 * s);
            else tma_load_mc(base + s * 16384 + r * 8192, &P.w[pw], n * 128 + r * 64, k * 64, full + 8 * s, 3);
            if (++s == PST) { s = 0; ph ^= 1; }
          }
        }
      }
      for (int i = 0; i < PST; i++) { mbar_wait(empty + 8 * s, ph); if (++s == PST) { s = 0; ph ^= 1; } }
    } else if (tid == 288 || tid == 320) {
      const int g = tid == 320;
      int c = 0;
      for (int it = blockIdx.x >> 1; it < P.nitems; it += gridDim.x >> 1) {
        const ProjItem& I = P.item[it];
        for (int t = 0; t < I.n[0] + I.n[1]; t++, c++) {
          int pw, n; proj_decode(I, t, pw, n);
          mbar_wait(of + 8 * g, c & 1);
          tma_store(&P.c[pw], stg + g * 16384, n * 128, (I.m * 2 + r) * 128 + g * 64);
          tma_store(&P.c[pw], stg + g * 16384 + 8192, n * 128 + 64, (I.m * 2 + r) * 128 + g * 64);
          bulk_commit();
          bulk_wait_read<0>();
          mbar_arrive(oe + 8 * g);
          if (t == 3 && !g) CT(0, 1)
          if (t == I.n[0] - 1) { bulk_wait<0>(); signal_after_bulk(S_PROJ + I.pa * (I.m + 1) * 2); }
        }
        bulk_wait<0>(); signal_after_bulk(S_PROJ + I.pa * (I.m + 1) * 2 + 1);
      }
      if (!g) CT(0, 2)
    }
  } else {
    reg_inc<240>();
    uint32_t A[36][4];
    float acc[64];
    uint32_t s = 0, ph = 0, c = 1;
    const uint32_t row = ((tid >> 5) & 3) * 16 + (tid & 15);
    const uint32_t roff = row * 128 + ((((tid >> 4) & 1) ^ (row & 7)) << 4);
    const uint32_t rel = mapa(empty, tid & 1);
    auto release = [&](uint32_t st) { asm volatile("{.reg .pred p; setp.lt.u32 p,%1,2; @p mbarrier.arrive.shared::cluster.b64 _,[%0];}" ::"r"(rel + 8 * st), "r"(tid & 127) : "memory"); };
    for (int it = blockIdx.x >> 1; it < P.nitems; it += gridDim.x >> 1) {
      const int pa = P.item[it].pa, nt = P.item[it].n[0] + P.item[it].n[1];
#pragma unroll
      for (int k = 0; k < 9; k++) {
        if (k < 8 || pa) {
          mbar_wait(full + 8 * s, ph);
#pragma unroll
          for (int kk = 0; kk < 4; kk++) ldsm4(A[4 * k + kk], base + s * 16384 + wg * 8192 + (roff ^ (kk * 32)));
          bar_sync(1 + wg, 128);
          release(s);
          if (++s == PST) { s = 0; ph ^= 1; }
        }
      }
      if (tid == 0) CT(0, 0)
      if (wg) bar_sync(3, 256);
      bool ok = false;
      for (int t = 0; t < nt; t++, c ^= 1) {
        uint32_t p1 = 0, p2 = 0;
#pragma unroll
        for (int k = 0; k < 9; k++) {
          if (k < 8 || pa) {
            if (!ok) mbar_wait(full + 8 * s, ph);
            const uint64_t db = desc_mn(base + s * 16384, 8192);
            wg_fence();
#pragma unroll
            for (int kk = 0; kk < 4; kk++) wg_rs128<1>(acc, A[4 * k + kk], db + kk * 128, k | kk);
            wg_commit();
            const uint32_t cur = s;
            if (++s == PST) { s = 0; ph ^= 1; }
            ok = mbar_test(full + 8 * s, ph);
            if (PWD == 1) { if (k) { wg_wait<1>(); release(p1); } }
            else if (k > 1) { wg_wait<2>(); release(p2); }
            if (k == 4 && t == 0 && !wg) bar_arrive(3, 256);
            p2 = p1; p1 = cur;
          }
        }
        mwait(oe + 8 * wg, c);
        if (PWD == 2) { wg_wait<1>(); release(p2); }
        wg_wait<0>();
        release(p1);
#pragma unroll
        for (int i = 0; i < 8; i++) {
          const float* a = acc + i * 8;
          stsm4(stg + wg * 16384 + (i >> 2) * 8192 + (roff ^ ((i & 3) * 32)), pack2(a[0], a[1]), pack2(a[2], a[3]), pack2(a[4], a[5]), pack2(a[6], a[7]));
        }
        fence_async();
        __syncwarp();
        if ((tid & 31) == 0) mbar_arrive(of + 8 * wg);
      }
    }
  }
}

struct OutMaps { CUtensorMap a, b, bh; };
constexpr int OSB = 40960;
template <int NST, bool MC> DEVI void out_produce(const OutMaps& M, uint32_t base, uint32_t full, int m, int n, int k0, int nk, int flag) {
  const uint32_t empty = full + 8 * NST;
  auto load_b = [&](int s, int k) {
    const int r = blockIdx.x & 1;
    for (int j = 0; j < 3; j++) {
      if (MC) tma_load_mc(base + s * OSB + 16384 + j * 8192 + r * 4096, &M.bh, n * 192 + j * 64, k * 64 + r * 32, full + 8 * s, 3);
      else tma_load(base + s * OSB + 16384 + j * 8192, &M.b, n * 192 + j * 64, k * 64, full + 8 * s);
    }
  };
  for (int k = 0; k < NST; k++) {
    mbar_expect(full + 8 * k, OSB);
    load_b(k, k0 + k);
  }
  flag_wait(flag, 64, 192 / nk);
  for (int k = 0; k < NST; k++) tma_load(base + k * OSB, &M.a, (k0 + k) * 64, m * 128, full + 8 * k);
  int s = 0, ph = 0;
  for (int k = NST; k < nk; k++) {
    mbar_wait(empty + 8 * s, ph);
    mbar_expect(full + 8 * s, OSB);
    tma_load(base + s * OSB, &M.a, (k0 + k) * 64, m * 128, full + 8 * s);
    load_b(s, k0 + k);
    if (++s == NST) { s = 0; ph ^= 1; }
  }
  if (MC) for (int i = 1; i < NST; i++) { mbar_wait(empty + 8 * s, ph); if (++s == NST) { s = 0; ph ^= 1; } }
}
template <int NST, bool MC> DEVI void out_consume(float* acc, uint32_t base, uint32_t full, int nk) {
  const uint32_t empty = full + 8 * NST;
  const int wg = threadIdx.x >> 7;
  int s = 0, ph = 0, prev = 0;
  for (int k = 0; k < nk; k++) {
    mbar_wait(full + 8 * s, ph);
    const uint64_t da = desc_k(base + s * OSB + wg * 8192), db = desc_mn(base + s * OSB + 16384, 8192);
    wg_fence();
#pragma unroll
    for (int kk = 0; kk < 4; kk++) wg_ss192<1>(acc, da + kk * 2, db + kk * 128, k | kk);
    wg_commit();
    if (k) { wg_wait<1>(); if (MC) arrive_pair(empty + 8 * prev); else if ((threadIdx.x & 127) == 0) mbar_arrive(empty + 8 * prev); }
    prev = s;
    if (++s == NST) { s = 0; ph ^= 1; }
  }
  wg_wait<0>();
}
struct OutParams { OutMaps p[2]; CUtensorMap c[2]; int m0, nb, id; };
#define OST 4
constexpr int SM_O = 5 * OSB + 256;
template <bool MC> __global__ void __launch_bounds__(384, 1) out_kernel(const __grid_constant__ OutParams P) {
  extern __shared__ __align__(1024) uint8_t smem_raw[];
  const uint32_t base = s2u(smem_raw), full = base + OST * OSB;
  const int tid = threadIdx.x, wg = tid >> 7;
  const int pb = (int)blockIdx.x < P.nb, t = pb ? blockIdx.x : 47 - (blockIdx.x - P.nb);
  const int m = (pb ? P.m0 : 0) + (MC ? t / 6 * 2 + (t & 1) : t / 3), n = MC ? (t >> 1) % 3 : t % 3;
  TL_START(P.id)
  pdl_trigger();
  if (tid == 0) {
    for (int i = 0; i < OST; i++) { mbar_init(full + 8 * i, 1); mbar_init(full + 8 * (OST + i), MC ? 4 : 2); }
    asm volatile("fence.mbarrier_init.release.cluster;" ::: "memory");
  }
  if (MC) cluster_sync_relaxed(); else __syncthreads();
  if (wg == 2) {
    if (tid == 256) out_produce<OST, MC>(P.p[pb], base, full, m, n, 0, 64, (pb ? S_CTXB : S_CTXA) + m);
  } else {
    float acc[96];
    out_consume<OST, MC>(acc, base, full, 64);
    bar_sync(3, 256);
    const uint32_t row = ((tid >> 5) & 3) * 16 + (tid & 15);
    const uint32_t roff = row * 128 + ((((tid >> 4) & 1) ^ (row & 7)) << 4);
#pragma unroll
    for (int i = 0; i < 12; i++) {
      const float* a = acc + i * 8;
      stsm4(base + wg * 24576 + (i >> 2) * 8192 + (roff ^ ((i & 3) * 32)), pack2(a[0], a[1]), pack2(a[2], a[3]), pack2(a[4], a[5]), pack2(a[6], a[7]));
    }
    fence_async();
    bar_sync(1 + wg, 128);
    if ((tid & 127) == 0) {
      for (int c = 0; c < 3; c++) tma_store(&P.c[pb], base + wg * 24576 + c * 8192, n * 192 + c * 64, m * 128 + wg * 64);
      bulk_commit();
      bulk_wait<0>();
    }
    TL_END(P.id)
  }
}
struct FaParams { CUtensorMap q, k, v, o; unsigned nctas; uint8_t nproj[12]; uint16_t order[512]; };
constexpr int SM_F = 7 * 32768 + 256;
constexpr float FA_C = 0.08838834764831845f * 1.4426950408889634f;
DEVI int fa_qt(int w) { return w >> 5; }
DEVI int fa_hc(int w) { return (w & 31) * 128; }

DEVI void fa_exp(const float* S, uint32_t* Pn, float mc0, float mc1, float& s0, float& s1) {
  float a0 = 0.f, a1 = 0.f, b0 = 0.f, b1 = 0.f;
#pragma unroll
  for (int j = 0; j < 16; j++) {
    const float e0 = ex2(fmaf(S[4 * j], FA_C, -mc0)), e1 = ex2(fmaf(S[4 * j + 1], FA_C, -mc0));
    const float e2 = ex2(fmaf(S[4 * j + 2], FA_C, -mc1)), e3 = ex2(fmaf(S[4 * j + 3], FA_C, -mc1));
    a0 += e0; a1 += e1; b0 += e2; b1 += e3;
    Pn[2 * j] = pack2(e0, e1); Pn[2 * j + 1] = pack2(e2, e3);
  }
  s0 = a0 + a1; s1 = b0 + b1;
}

struct FaState { float mc0, mc1, l0, l1; int w, j, qi; uint32_t dq; bool first; };
enum { F_Q = 0, F_K = 2 * 32768, F_V = 4 * 32768, F_O = 6 * 32768, F_QF = 7 * 32768, F_QE = F_QF + 16, F_KF = F_QF + 32, F_KE = F_QF + 48, F_VF = F_QF + 64, F_VE = F_QF + 80,
       F_OF = F_QF + 96, F_OE = F_QF + 112, F_INFO = F_QF + 128 };

template <int SC> DEVI bool fa_step(FaState& T, float* O, float* S, const uint32_t* Pc, uint32_t* Pn, uint32_t base, int tid, int wg, uint32_t ph) {
  const bool el = (tid & 127) == 0, fin = T.j == 0;
  int wn = T.w, jn = T.j - 1;
  const bool okk = mbar_try(base + F_KF + 8 * (SC ^ 1), ph), okv = mbar_try(base + F_VF + 8 * SC, ph ^ SC);
  if (fin) {
    T.qi++; T.dq ^= 2048;
    mbar_wait(base + F_QF + 8 * (T.qi & 1), (T.qi >> 1) & 1);
    asm volatile("ld.shared.b32 %0,[%1];" : "=r"(wn) : "r"(base + F_INFO + (T.qi & 1) * 4) : "memory");
    wn = __shfl_sync(~0u, wn, 0);
    jn = fa_qt(wn);
  }
  if (!(okk && okv)) { mbar_wait(base + F_KF + 8 * (SC ^ 1), ph); mbar_wait(base + F_VF + 8 * SC, ph ^ SC); }
  const bool last = wn < 0;
  {
    const uint64_t dq = desc_k(0) | T.dq, dk = desc_k(base + F_K + (SC ^ 1) * 32768), dv = desc_mn(base + F_V + SC * 32768, 16384);
    bar_sync(3 + wg, 256);
    wg_fence();
#pragma unroll
    for (int kk = 0; kk < 8; kk++) wg_ss128<0>(S, dq + (kk & 3) * 2 + (kk >> 2) * 1024, dk + (kk & 3) * 2 + (kk >> 2) * 1024, kk);
    wg_commit();
#pragma unroll
    for (int kk = 0; kk < 8; kk++) wg_rs128<1>(O, Pc + 4 * kk, dv + kk * 128, kk || !T.first);
    wg_commit();
    bar_arrive(4 - wg, 256);
  }
  wg_wait<1>();
  asm volatile("{.reg .pred p,q; setp.ne.u32 p,%0,0; setp.eq.and.u32 q,%1,0,p; @p mbarrier.arrive.shared::cta.b64 _,[%2]; @q mbarrier.arrive.shared::cta.b64 _,[%3];}"
               ::"r"((uint32_t)el), "r"(jn), "r"(base + F_KE + 8 * (SC ^ 1)), "r"(base + F_QE + 8 * (T.qi & 1)) : "memory");
  const float lp0 = T.l0, lp1 = T.l1;
  float s0 = 0.f, s1 = 0.f, f0 = 1.f, f1 = 1.f;
  bool exact = fin;
  if (!fin) {
    fa_exp(S, Pn, T.mc0, T.mc1, s0, s1);
    exact = __any_sync(~0u, !(fmaxf(s0, s1) <= 1073741824.f));
  }
  if (exact && !last) {
    float a = -INFINITY, b = -INFINITY;
    if (fin) {
      const int row = (tid >> 5) * 16 + ((tid & 31) >> 2) - (tid & 3) * 2;
#pragma unroll
      for (int j = 0; j < 16; j++) {
        if (j * 8 > row) S[4 * j] = -INFINITY;
        if (j * 8 + 1 > row) S[4 * j + 1] = -INFINITY;
        if (j * 8 > row + 8) S[4 * j + 2] = -INFINITY;
        if (j * 8 + 1 > row + 8) S[4 * j + 3] = -INFINITY;
      }
      T.mc0 = T.mc1 = -INFINITY;
    }
#pragma unroll
    for (int j = 0; j < 16; j++) { a = fmaxf(a, fmaxf(S[4 * j], S[4 * j + 1])); b = fmaxf(b, fmaxf(S[4 * j + 2], S[4 * j + 3])); }
    a = fmaxf(a, __shfl_xor_sync(~0u, a, 1)); b = fmaxf(b, __shfl_xor_sync(~0u, b, 1));
    a = fmaxf(a, __shfl_xor_sync(~0u, a, 2)); b = fmaxf(b, __shfl_xor_sync(~0u, b, 2));
    a = fmaxf(a * FA_C, T.mc0); b = fmaxf(b * FA_C, T.mc1);
    f0 = ex2(T.mc0 - a); f1 = ex2(T.mc1 - b);
    T.mc0 = a; T.mc1 = b;
    T.l0 = fin ? 0.f : T.l0 * f0; T.l1 = fin ? 0.f : T.l1 * f1;
    fa_exp(S, Pn, a, b, s0, s1);
  }
  T.l0 += s0; T.l1 += s1;
  wg_wait<0>();
  if (el) mbar_arrive(base + F_VE + 8 * SC);
  if (exact) {
    if (fin) {
      f0 = lp0 + __shfl_xor_sync(~0u, lp0, 1); f1 = lp1 + __shfl_xor_sync(~0u, lp1, 1);
      f0 += __shfl_xor_sync(~0u, f0, 2); f1 += __shfl_xor_sync(~0u, f1, 2);
      f0 = 1.f / f0; f1 = 1.f / f1;
    }
#pragma unroll
    for (int i = 0; i < 16; i++) { O[4 * i] *= f0; O[4 * i + 1] *= f0; O[4 * i + 2] *= f1; O[4 * i + 3] *= f1; }
    if (fin && (T.qi || last)) {
      const uint32_t row = ((tid >> 5) & 3) * 16 + (tid & 15);
      const uint32_t o = base + F_O + wg * 16384 + row * 128 + ((((tid >> 4) & 1) ^ (row & 7)) << 4);
      if (T.qi) mbar_wait(base + F_OE + 8 * wg, T.qi & 1);
#pragma unroll
      for (int i = 0; i < 8; i++) {
        const float* a = O + i * 8;
        stsm4((o ^ ((i & 3) * 32)) + (i >> 2) * 8192, pack2(a[0], a[1]), pack2(a[2], a[3]), pack2(a[4], a[5]), pack2(a[6], a[7]));
      }
      if (el) asm volatile("st.shared.b32 [%0],%1;" ::"r"(base + F_INFO + 8 + wg * 4), "r"(!T.qi ? -1 : T.w | (last ? 1024 : 0)) : "memory");
      fence_async();
      __syncwarp();
      if ((tid & 31) == 0) mbar_arrive(base + F_OF + 8 * wg);
    }
  }
  T.w = wn; T.j = jn; T.first = fin;
  return last;
}

__global__ void __launch_bounds__(384, 1) fa_kernel(const __grid_constant__ FaParams P) {
  extern __shared__ __align__(1024) uint8_t smem_raw[];
  const uint32_t base = s2u(smem_raw);
  const uint32_t sQ = base, sK = base + 2 * 32768, sV = base + 4 * 32768, sO = base + 6 * 32768, bars = base + 7 * 32768;
  const uint32_t qf = bars, qe = bars + 16, kf = bars + 32, ke = bars + 48, vf = bars + 64, ve = bars + 80, of = bars + 96, oe = bars + 112;
  volatile int* info = (volatile int*)(smem_raw + 7 * 32768 + 128);
  const int tid = threadIdx.x, wg = tid >> 7;
  pdl_trigger();
  if (tid == 0) {
    for (int i = 0; i < 16; i++) mbar_init(bars + 8 * i, i >= 14 ? 1 : i >= 12 ? 4 : (i & 2) ? 2 : 1);
    asm volatile("fence.mbarrier_init.release.cluster;" ::: "memory");
  }
  __syncthreads();
  if (wg == 2) {
    reg_dec<24>();
    if (tid == 256) {
      int it = 0, qi = 0;
      uint32_t seen = 0;
      int w = atomicInc(&g_sync[S_QUEUE], 511 + P.nctas), vc = 0, vr = -1;
      auto load_v = [&]() {
        if (vr < 0) return;
        const int s = (it - 1) & 1;
        mbar_wait(ve + 8 * s, (((it - 1) >> 1) & 1) ^ 1 ^ s);
        mbar_expect(vf + 8 * s, 32768);
        tma_load(sV + s * 32768, &P.v, vc, vr, vf + 8 * s);
        tma_load(sV + s * 32768 + 16384, &P.v, vc + 64, vr, vf + 8 * s);
      };
      while (true) {
        const uint32_t q = qi & 1;
        mbar_wait(qe + 8 * q, ((qi >> 1) & 1) ^ 1);
        if (w >= 512) { info[q] = -1; mbar_arrive(qf + 8 * q); mbar_wait(ke + 8 * (it & 1), ((it >> 1) & 1) ^ 1); mbar_arrive(kf + 8 * (it & 1)); load_v(); break; }
        w = P.order[w];
        const int qt = fa_qt(w), hc = fa_hc(w), fk = (w >> 4) & 1, fq = (qt | 1) + 1 + fk;
        if (~seen & ((1u << fk) | (1u << fq))) {
          load_v(); vr = -1;
          flag_wait(S_PROJ + fk, P.nproj[0], 0); flag_wait(S_PROJ + fq, P.nproj[fq >> 1], 0);
          seen |= (1u << fk) | (1u << fq);
        }
        info[q] = w;
        mbar_expect(qf + 8 * q, 32768);
        tma_load(sQ + q * 32768, &P.q, hc, qt * 128, qf + 8 * q);
        tma_load(sQ + q * 32768 + 16384, &P.q, hc + 64, qt * 128, qf + 8 * q);
        qi++;
        for (int j = qt; j >= 0; j--, it++) {
          const int s = it & 1;
          mbar_wait(ke + 8 * s, ((it >> 1) & 1) ^ 1);
          mbar_expect(kf + 8 * s, 32768);
          tma_load(sK + s * 32768, &P.k, hc, j * 128, kf + 8 * s);
          tma_load(sK + s * 32768 + 16384, &P.k, hc + 64, j * 128, kf + 8 * s);
          if (j == 0) w = atomicInc(&g_sync[S_QUEUE], 511 + P.nctas);
          load_v();
          vc = hc; vr = j * 128;
        }
      }
      if (atomicInc(&g_sync[S_EXIT], P.nctas - 1) == P.nctas - 1)
        for (int i = 0; i < 18; i++) g_sync[S_PROJ + i] = 0;
    } else if (tid == 288 || tid == 320) {
      const int g = tid == 320;
        for (int n = 0;; n++) {
          mbar_wait(of + 8 * g, n & 1);
          const int v = info[2 + g], w = v & 1023, qt = fa_qt(w), hc = fa_hc(w);
          if (v < 0) break;
          tma_store(&P.o, sO + g * 16384, hc, qt * 128 + g * 64);
          tma_store(&P.o, sO + g * 16384 + 8192, hc + 64, qt * 128 + g * 64);
          bulk_commit();
          bulk_wait_read<0>();
          mbar_arrive(oe + 8 * g);
          bulk_wait<0>();
          signal_after_bulk(S_CTXA + qt);
          if (v & 1024) break;
        }
    }
  } else {
    reg_inc<240>();
    float O[64], S[64];
    uint32_t PA[32], PB[32];
#pragma unroll
    for (int i = 0; i < 32; i++) PA[i] = 0;
#pragma unroll
    for (int i = 0; i < 64; i++) O[i] = 0.f;
    const uint32_t ub = __shfl_sync(~0u, base, 0);
    const int uw = __shfl_sync(~0u, wg, 0);
    FaState T = {0.f, 0.f, 1.f, 1.f, 0, 0, -1, ((ub + 32768 + uw * 8192) >> 4) & 0x3fff, true};
    if (wg == 1) bar_arrive(3, 256);
    for (uint32_t ph = 0;; ph ^= 1) {
      if (fa_step<1>(T, O, S, PA, PB, ub, tid, uw, ph)) break;
      if (fa_step<0>(T, O, S, PB, PA, ub, tid, uw, ph)) break;
    }
    if (wg == 0) bar_sync(3, 256);
  }
}
#define PS 20
#define PT(i)
#define GT(i)
#define YD 150
#define NPF 4
#define NRES 6
#define VB 8
#define RP 208
#define PD 4
#define VA 1
#define VC 36
#define VG 2
#define VW 1
#define YE 0
#define SL 1
#define XI 0
#define NPE 4
#define NUP 2
#define VI 3
#define T0 0
#define T1 16
#define T2 24
#define LATE 1
#define KA 24
constexpr int R_WV = 0, R_WO = 73728, R_H = 147456, R_OX = R_H + 46080, R_Q = R_OX + 4096, R_K = R_Q + 5120, R_SX = R_K + 5120, R_P = R_SX + 3200, R_U = R_P + 3200,
              R_BAR = R_H + 73728, R_PROF = R_BAR + 256, R_END = R_PROF + 3072;
constexpr int B_W0 = R_BAR, B_W1 = R_BAR + 8, B_XA = R_BAR + 16, B_XB = R_BAR + 24, B_XF = R_BAR + 32, B_Z0 = R_BAR + 40, B_Z1 = R_BAR + 48, B_R = R_BAR + 56,
              B_SM = R_BAR + 64, B_SX = R_BAR + 72, B_U = R_BAR + 80, B_V = R_BAR + 88, B_O = R_BAR + 96, B_W2 = R_BAR + 160, B_W3 = R_BAR + 168;
static_assert(R_U + 4096 <= R_BAR, "");
enum { N_P1 = 1, N_PM, N_PX, N_SUM, N_O, N_INIT, N_INIT1, N_INIT2, N_WO, N_S };
constexpr int YSLOT = 9 * 16 * 1024;
struct RecParams { CUtensorMap wq, wk, wv, wo, x, ctx; OutMaps o; const bf16 *mem0, *x_raw; bf16* out; };
constexpr int TAIL0 = 11;
constexpr int R_RED = 4 * OSB;

DEVI uint64_t mkdesc(uint32_t a, uint32_t lbo, uint32_t sbo, int sw) { return (uint64_t)((a >> 4) & 0x3fff) | ((uint64_t)(lbo >> 4) << 16) | ((uint64_t)(sbo >> 4) << 32) | ((uint64_t)sw << 62); }
DEVI void wg_rs32(float* d, const uint32_t* a, uint64_t db, int acc) {
  asm volatile("{.reg .pred p; setp.ne.b32 p,%21,0;\n wgmma.mma_async.sync.aligned.m64n32k16.f32.bf16.bf16 {%0,%1,%2,%3,%4,%5,%6,%7,%8,%9,%10,%11,%12,%13,%14,%15},{%16,%17,%18,%19},%20,p,1,1,0;}"
               : F8(d, 0), F8(d, 8) : "r"(a[0]), "r"(a[1]), "r"(a[2]), "r"(a[3]), "l"(db), "r"(acc));
}
DEVI void wg_rs40(float* d, const uint32_t* a, uint64_t db, int acc) {
  asm volatile("{.reg .pred p; setp.ne.b32 p,%25,0;\n wgmma.mma_async.sync.aligned.m64n40k16.f32.bf16.bf16 {%0,%1,%2,%3,%4,%5,%6,%7,%8,%9,%10,%11,%12,%13,%14,%15,%16,%17,%18,%19},{%20,%21,%22,%23},%24,p,1,1,0;}"
               : F8(d, 0), F8(d, 8), "+f"(d[16]), "+f"(d[17]), "+f"(d[18]), "+f"(d[19]) : "r"(a[0]), "r"(a[1]), "r"(a[2]), "r"(a[3]), "l"(db), "r"(acc));
}
template <int TB> DEVI void wg_ss40(float* d, uint64_t da, uint64_t db, int acc) {
  asm volatile("{.reg .pred p; setp.ne.b32 p,%22,0;\n wgmma.mma_async.sync.aligned.m64n40k16.f32.bf16.bf16 {%0,%1,%2,%3,%4,%5,%6,%7,%8,%9,%10,%11,%12,%13,%14,%15,%16,%17,%18,%19},%20,%21,p,1,1,1,%23;}"
               : F8(d, 0), F8(d, 8), "+f"(d[16]), "+f"(d[17]), "+f"(d[18]), "+f"(d[19]) : "l"(da), "l"(db), "r"(acc), "n"(TB));
}
DEVI void mma8(float* d, uint32_t a0, uint32_t a1, uint32_t b0) {
  asm volatile("mma.sync.aligned.m16n8k8.row.col.f32.bf16.bf16.f32 {%0,%1,%2,%3},{%4,%5},{%6},{%0,%1,%2,%3};" : "+f"(d[0]), "+f"(d[1]), "+f"(d[2]), "+f"(d[3]) : "r"(a0), "r"(a1), "r"(b0));
}
DEVI void stsm4t(uint32_t a, uint32_t r0, uint32_t r1, uint32_t r2, uint32_t r3) {
  asm volatile("stmatrix.sync.aligned.m8n8.x4.trans.shared.b16 [%0],{%1,%2,%3,%4};" ::"r"(a), "r"(r0), "r"(r1), "r"(r2), "r"(r3) : "memory");
}
DEVI uint32_t movm(uint32_t a) { uint32_t d; asm volatile("movmatrix.sync.aligned.m8n8.trans.b16 %0,%1;" : "=r"(d) : "r"(a)); return d; }
DEVI void sts1(uint32_t a, uint32_t v) { asm volatile("st.shared.b32 [%0],%1;" ::"r"(a), "r"(v) : "memory"); }
DEVI uint32_t lds1(uint32_t a) { uint32_t v; asm volatile("ld.shared.b32 %0,[%1];" : "=r"(v) : "r"(a) : "memory"); return v; }
DEVI void sta1(uint32_t d, uint32_t a, uint32_t bar) { asm volatile("st.async.weak.shared::cluster.mbarrier::complete_tx::bytes.b32 [%0],%1,[%2];" ::"r"(d), "r"(a), "r"(bar) : "memory"); }
DEVI void sta2(uint32_t d, uint32_t a, uint32_t b, uint32_t bar) { asm volatile("st.async.weak.shared::cluster.mbarrier::complete_tx::bytes.v2.b32 [%0],{%1,%2},[%3];" ::"r"(d), "r"(a), "r"(b), "r"(bar) : "memory"); }
DEVI uint32_t clk32() { uint64_t c; asm volatile("mov.u64 %0,%%clock64;" : "=l"(c)::"memory"); return (uint32_t)c; }
DEVI int opq(int x) { asm volatile("" : "+r"(x)); return x; }
DEVI int pin(int x) { return __shfl_sync(~0u, x, threadIdx.x & 31); }
DEVI uint32_t zero_after(float x) { uint32_t t; asm volatile("{.reg .u32 t; popc.b32 t,%1; shr.u32 %0,t,6;}" : "=r"(t) : "r"(__float_as_uint(x))); return t; }
DEVI void x_load(const RecParams& P, uint32_t sb, int c, int seg) {
  asm volatile("cp.async.bulk.tensor.2d.shared::cluster.global.mbarrier::complete_tx::bytes.multicast::cluster [%0],[%1,{%3,%4}],[%2],%5;"
               ::"r"(sb + R_H + c * 5120 + 1024), "l"(&P.x), "r"(sb + (c < 6 ? B_XA : B_XB)), "r"(c * 64), "r"(seg * 32), "h"((uint16_t)0xffff) : "memory");
  if (seg + 2 < NSEG) asm volatile("cp.async.bulk.prefetch.tensor.2d.L2.global [%0,{%1,%2}];" ::"l"(&P.x), "r"(c * 64), "r"(seg * 32 + 64) : "memory");
}
DEVI uint32_t hadd2(uint32_t a, uint32_t b) { uint32_t r; asm("add.rn.bf16x2 %0,%1,%2;" : "=r"(r) : "r"(a), "r"(b)); return r; }
DEVI uint32_t hmax2(uint32_t a, uint32_t b) { uint32_t r; asm("max.bf16x2 %0,%1,%2;" : "=r"(r) : "r"(a), "r"(b)); return r; }
DEVI float rcp(float x) { float y; asm("rcp.approx.ftz.f32 %0,%1;" : "=f"(y) : "f"(x)); return y; }
constexpr float SCL = 0.08838834764831845f * 1.4426950408889634f;

DEVI void y_store(const float* a, uint32_t off, int s) {
  const uint32_t x = movm(pack2(a[0], a[1])), y = movm(pack2(a[2], a[3]));
  const uint32_t tag = ((s >> 1) & 1) ^ 1;
  asm volatile("st.relaxed.gpu.global.b64 [%0],%1;" ::"l"((uint8_t*)g_Y + (s & 1) * YSLOT + off), "l"((uint64_t)((x & ~1u) | tag) | ((uint64_t)y << 32)) : "memory");
}
DEVI void y_load(uint32_t* w, const uint8_t* p) {
#pragma unroll
  for (int i = 0; i < 4; i++) asm volatile("{.reg .b64 t; ld.relaxed.gpu.global.b64 t,[%2]; mov.b64 {%0,%1},t;}" : "=r"(w[2 * i]), "=r"(w[2 * i + 1]) : "l"(p + i * 256) : "memory");
}
DEVI bool y_missing(const uint32_t* w, uint32_t tag) {
  uint32_t r;
  asm volatile("{.reg .b32 a,b; .reg .pred p; lop3.b32 a,%1,%2,%5,0x7e; lop3.b32 b,%3,%4,%5,0x7e; lop3.b32 a,a,b,1,0xa8; setp.ne.u32 p,a,0; vote.sync.any.pred p,p,0xffffffff; selp.u32 %0,1,0,p;}"
               : "=r"(r) : "r"(w[0]), "r"(w[2]), "r"(w[4]), "r"(w[6]), "r"(tag));
  return r;
}
DEVI void y_reload(uint32_t* w, const uint8_t* p, uint32_t tag) {
#pragma unroll
  for (int i = 0; i < 4; i++)
    asm volatile("{.reg .b64 t; .reg .b32 a; .reg .pred q; lop3.b32 a,%0,%3,1,0x28; setp.ne.u32 q,a,0; mov.b64 t,{%0,%1}; @q ld.relaxed.gpu.global.b64 t,[%2]; mov.b64 {%0,%1},t;}"
                 : "+r"(w[2 * i]), "+r"(w[2 * i + 1]) : "l"(p + i * 256), "r"(tag) : "memory");
}
DEVI void y_sum(uint32_t* r, const uint32_t* w, uint32_t sel) {
  float d0[4] = {0, 0, 0, 0}, d1[4] = {0, 0, 0, 0};
  mma16(d0, w[0], w[1], w[2], w[3], sel, sel); mma16(d1, w[4], w[5], w[6], w[7], sel, sel);
  r[0] = pack2(d0[0] + d1[0], d0[1] + d1[1]); r[1] = pack2(d0[2] + d1[2], d0[3] + d1[3]);
}
DEVI void y_send(const uint32_t* r, uint32_t sb, uint32_t dst, uint32_t bar, int lane) {
#pragma unroll
  for (int i = 0; i < 4; i++) { const uint32_t rs = mapa(sb, (lane & 3) * 4 + i); sta2(rs + dst, r[0], r[1], rs + bar); }
}
DEVI void wo_convert(uint32_t sb, int lane) {
  const int g = lane >> 2;
  TL_END(11)
  mbar_wait(sb + B_W3, 0);
  TL_END(9)
#pragma unroll 1
  for (uint32_t a = sb + R_WO + ((threadIdx.x >> 5) & 3) * 2048, i = 0; i < 9; i++, a += 8192) {
    uint32_t r[4][4];
#pragma unroll
    for (int k = 0; k < 4; k++) ldsm4t(r[k], a + k * 512 + ((lane & 7) + (lane >> 4) * 8) * 32 + ((lane >> 3) & 1) * 16);
    __syncwarp();
#pragma unroll
    for (int k = 0; k < 4; k++)
#pragma unroll
      for (int m = 0; m < 4; m++) sts1(a + k * 512 + ((((m & 1) * 2 + (g >> 2)) * 2 + (g & 1)) * 4 + (lane & 3)) * 16 + ((m >> 1) * 2 + ((g >> 1) & 1)) * 4, r[k][m]);
  }
  __syncwarp();
}
template <int NR, int NP, int NE, int UP> DEVI void wo_tile(const uint32_t (*A0)[4], uint32_t sb, int chunk, int cta, int lane, uint32_t yo, int s) {
  uint32_t u[8][4], A[16][4];
  const uint32_t wa = sb + R_WO + chunk * 8192 + lane * 16, ua = sb + R_U + lane * 16;
  float a[4] = {0, 0, 0, 0}, b[4] = {0, 0, 0, 0};
  auto fetch = [&](int i) { if (i < 16 - NR) lds4(A[i], wa + i * 512); };
  auto uload = [&](int i) { if (i < 8) ldsm4t(u[i], ua + i * 512); };
#pragma unroll
  for (int i = 0; i < NE; i++) fetch(i);
  mwait(sb + B_V, s & 1);
  PT(6)
  uload(0); uload(1);
#pragma unroll
  for (int i = NE; i < NP; i++) fetch(i);
#pragma unroll
  for (int i = 0; i < 16; i++) {
    if (i == 4) {
      mwait(sb + B_U, s & 1);
      PT(7)
#pragma unroll
      for (int k = 2; k < 2 + UP; k++) uload(k);
    }
    const uint32_t* f = i >= 16 - NR ? A0[i >= 16 - NR ? i - 16 + NR : 0] : A[i];
    mma16(i & 1 ? b : a, f[0], f[1], f[2], f[3], u[i >> 1][(i & 1) * 2], u[i >> 1][(i & 1) * 2 + 1]);
    fetch(i + NP);
    if (i >= 4 && (i & 1)) uload((i >> 1) + UP);
  }
#pragma unroll
  for (int i = 0; i < 4; i++) a[i] += b[i];
  y_store(a, yo, s);
}
template <bool X> DEVI void softmax8(const uint32_t* h, uint32_t a4, uint32_t a1) {
  uint32_t y[5];
  lds4(y, a4 + R_SX); y[4] = lds1(a1 + R_SX);
#pragma unroll
  for (int j = 0; j < 5; j++) y[j] = hadd2(h[j], y[j]);
  const uint32_t m2 = hmax2(hmax2(hmax2(y[0], y[1]), hmax2(y[2], y[3])), y[4]);
  const float mc = fmaxf(blo(m2), bhi(m2)) * SCL;
  const float m1 = __shfl_xor_sync(~0u, mc, 1), m3 = __shfl_xor_sync(~0u, mc, 2), m4 = __shfl_xor_sync(~0u, mc, 3);
  float e[10];
#pragma unroll
  for (int j = 0; j < 5; j++) { e[2 * j] = ex2(fmaf(blo(y[j]), SCL, -mc)); e[2 * j + 1] = ex2(fmaf(bhi(y[j]), SCL, -mc)); }
  const float c = ex2(mc - fmaxf(fmaxf(mc, m1), fmaxf(m3, m4)));
  const float l = c * ((((e[0] + e[1]) + (e[2] + e[3])) + ((e[4] + e[5]) + (e[6] + e[7]))) + (e[8] + e[9]));
  const float r = c * rcp((l + __shfl_xor_sync(~0u, l, 1)) + (__shfl_xor_sync(~0u, l, 2) + __shfl_xor_sync(~0u, l, 3)));
#pragma unroll
  for (int j = 0; j < 5; j++) y[j] = pack2(e[2 * j] * r, e[2 * j + 1] * r);
  if (!X) sts4(a4 + R_P, y[0], y[1], y[2], y[3]);
  else stsm4(a4 + R_P, y[0], y[1], y[2], y[3]);
  sts1(a1 + R_P, y[4]);
  if (X) fence_async();
}

DEVI void rec_proj(const RecParams& P, const uint32_t sb, const int cta) {
  uint32_t W[36][4], A0[NRES ? NRES : 1][4];
  const int tid = pin(threadIdx.x);
  const uint32_t yo = pin(((threadIdx.x >> 2) * 2 + ((cta >> 1) & 1)) * 1024 + (cta >> 4) * 256 + (cta & 1) * 128 + ((cta >> 2) & 3) * 32 + (threadIdx.x & 3) * 8);
  const int warp = __shfl_sync(~0u, threadIdx.x >> 5, 0), role = warp >> 2;
  const uint32_t qk = sb + R_Q + warp * 1280;
  {
    const int lane = threadIdx.x & 31, w4 = (threadIdx.x >> 5) & 3;
    const uint32_t a = sb + role * R_H + ((lane & 7) + (lane >> 4) * 8) * 128 + (((w4 * 2 + ((lane >> 3) & 1)) ^ (lane & 7)) << 4);
    mbar_wait(sb + B_W0 + role * 8, 0);
    TL_END(8)
#pragma unroll
    for (int k = 0; k < 36; k++) ldsm4t(W[k], a + k * 2048);
    if (LATE == 1) pdl_trigger();
    bar_arrive(N_INIT + role, 256);
    cluster_sync_relaxed();
    if (tid == 0 && (cta & 15) < 9) x_load(P, sb, cta & 15, 0);
#pragma unroll
    for (int i = 0; i < NRES; i++) A0[i][0] = A0[i][1] = A0[i][2] = A0[i][3] = 0;
  }
  for (int s = -1; s < NSEG; s++) {
    if (s >= 0) {
      PT(0)
      {
        const int lane = opq(tid) & 31;
        const uint32_t hb = sb + R_H + (lane & 7) * 128 + (((lane >> 3) ^ (lane & 7)) << 4);
        float a[4] = {0, 0, 0, 0}, b[4] = {0, 0, 0, 0};
        mwait(sb + B_Z0, (s - 1) & 1);
        PT(1) if (role) { GT(0) }
        uint32_t f[18][4];
#pragma unroll
        for (int c = -PD; c < 18; c++) {
          if (c + PD == 8) mwait(sb + B_Z1, (s - 1) & 1);
          if (c + PD < 18) ldsm4(f[c + PD], (hb ^ (((c + PD) & 1) * 64)) + ((c + PD) >> 1) * 5120);
          if (c >= 0) {
            mma16(a, W[2 * c][0], W[2 * c][1], W[2 * c][2], W[2 * c][3], f[c][0], f[c][1]);
            mma16(b, W[2 * c + 1][0], W[2 * c + 1][1], W[2 * c + 1][2], W[2 * c + 1][3], f[c][2], f[c][3]);
          }
        }
        sts1(qk + 512 + lane * 4, pack2(a[0] + b[0], a[1] + b[1]));
        sts1(qk + 1152 + lane * 4, pack2(a[2] + b[2], a[3] + b[3]));
        fence_async();
      }
      PT(2)
      const int lane = opq(tid) & 31;
      if (role) {
        bar_arrive(N_P1, 256);
        if (tid == 128) {
          mbar_expect(sb + B_SM, 640); mbar_expect(sb + B_SX, 2560); mbar_expect(sb + B_U, 3072);
          if (s < NSEG - 1) {
            mbar_expect(sb + B_Z0, 4096); mbar_expect(sb + B_Z1, 5120);
            mbar_expect(sb + B_XA, 24576); mbar_expect(sb + B_XB, 12288);
          }
        }
        const uint32_t o4 = sb + (warp - 4) * 640 + lane * 16, o1 = sb + (warp - 4) * 640 + 512 + lane * 4;
        uint32_t h[5];
        bar_sync(N_PX, 192);
        lds4(h, o4 + R_P); h[4] = lds1(o1 + R_P);
        mwait(sb + B_SX, s & 1);
        PT(4)
        softmax8<true>(h, o4, o1);
        PT(5)
      } else {
        float S[20];
        const uint64_t da = mkdesc(sb + R_Q, 640, 128, 0), db = mkdesc(sb + R_K, 640, 128, 0);
        const uint32_t rs = mapa(sb, (cta & 15) ^ 1);
        const uint32_t o4 = warp * 1280 + lane * 16, o1 = warp * 1280 + 512 + lane * 4;
        bar_sync(N_P1, 256);
        wg_fence();
#pragma unroll
        for (int k = 0; k < 4; k++) wg_ss40<1>(S, da + k * 80, db + k * 80, k);
        wg_commit();
        bar_arrive(N_S, 256);
        wg_wait<0>();
        PT(3)
        uint32_t h[2][5];
        if (warp == 2) {
#pragma unroll
          for (int j = 0; j < 5; j++) h[0][j] = pack2(S[4 * j], S[4 * j + 1]);
          sta4(rs + R_SX + o4, h[0][0], h[0][1], h[0][2], h[0][3], rs + B_SM); sta1(rs + R_SX + o1, h[0][4], rs + B_SM);
          mwait(sb + B_SM, s & 1);
          PT(4)
          softmax8<false>(h[0], sb + o4, sb + o1);
          bar_arrive(N_PM, 160);
        } else if (warp < 2) {
          const int row = warp * 16 + (lane >> 2) - (lane & 3) * 2;
#pragma unroll
          for (int g = 0; g < 2; g++) {
#pragma unroll
            for (int j = 0; j < 5; j++) h[g][j] = pack2(j < 4 && j * 8 > row + g * 8 ? -INFINITY : S[4 * j + 2 * g], j < 4 && j * 8 + 1 > row + g * 8 ? -INFINITY : S[4 * j + 2 * g + 1]);
            sts4(sb + R_P + o4 + g * 640, h[g][0], h[g][1], h[g][2], h[g][3]); sts1(sb + R_P + o1 + g * 640, h[g][4]);
            sta4(rs + R_SX + o4 + g * 640, h[g][0], h[g][1], h[g][2], h[g][3], rs + B_SX); sta1(rs + R_SX + o1 + g * 640, h[g][4], rs + B_SX);
          }
          bar_arrive(N_PX, 192);
        } else {
          if (s) bar_sync(N_O, 160);
          if (tid == 96) {
            if (s) {
              bulk_wait<0>();
              tma_store(&P.ctx, sb + R_OX, cta * 64, s * 32 - 32); bulk_commit();
              if ((s & 3) == 1 && s > 1) signal_after_bulk(S_CTXB + (s >> 2) - 1);
              bulk_wait_read<0>();
            }
            if (XI && (cta & 15) < 6 && s < NSEG - 1) { mbar_wait(sb + B_XF, s & 1); x_load(P, sb, cta & 15, s + 1); }
          }
        }
        __syncwarp();
        PT(5)
      }
      {
        if (s == 0) {
          bar_sync(N_INIT2, 384);
#pragma unroll
          for (int i = 0; i < NRES; i++) lds4(A0[i], sb + R_WO + warp * 8192 + lane * 16 + (16 - NRES + i) * 512);
        }
        wo_tile<NRES, NPF, NPE, NUP>(A0, sb, warp, cta, lane, yo, s);
        if (role) { GT(1) }
        if (s == NSEG - 1) { bar_arrive(N_WO, 384); break; }
        PT(8)
        bar_sync(N_WO, 384);
      }
    }
    {
      float acc[16];
      const uint64_t db = mkdesc(sb + R_H + 1024, 16, 1024, 1);
      mwait(sb + B_XA, (s + 1) & 1);
      PT(9) if (role) { GT(2) }
      wg_fence();
#pragma unroll
      for (int k = 0; k < (KA < 24 ? KA : 24); k++) wg_rs32(acc, W[k], db + (k >> 2) * 320 + (k & 3) * 2, k);
      wg_commit();
      mwait(sb + B_XB, (s + 1) & 1);
      wg_fence();
#pragma unroll
      for (int k = 24; k < KA; k++) wg_rs32(acc, W[k], db + (k >> 2) * 320 + (k & 3) * 2, 1);
      wg_commit();
      wg_wait<0>();
      PT(10)
      if (KA < 36 || s < 0) bar_sync(N_SUM, 384);
      wg_fence();
#pragma unroll
      for (int k = KA; k < 36; k++) wg_rs32(acc, W[k], db + (k >> 2) * 320 + (k & 3) * 2, 1);
      wg_commit();
      const uint32_t o = qk + (opq(tid) & 31) * 16;
      wg_wait<0>();
      PT(11)
      stsm4(o, pack2(acc[0], acc[1]), pack2(acc[4], acc[5]), pack2(acc[8], acc[9]), pack2(acc[12], acc[13]));
      stsm4(o + 640, pack2(acc[2], acc[3]), pack2(acc[6], acc[7]), pack2(acc[10], acc[11]), pack2(acc[14], acc[15]));
    }
  }
  TL_END(6)
  if (warp == 3) {
    bar_sync(N_O, 160);
    if (tid == 96) { tma_store(&P.ctx, sb + R_OX, cta * 64, SEQ - 32); bulk_commit(); bulk_wait<0>(); signal_after_bulk(S_CTXB + 15); }
    __syncwarp();
  }
  asm volatile("barrier.cluster.arrive.aligned;" ::: "memory");
  float acc[96];
  if (cta < 60) out_consume<4, false>(acc, sb, sb + B_O, 16);
  asm volatile("barrier.cluster.wait.aligned;" ::: "memory");
  if (cta < 60) {
    const uint32_t o = R_RED + (cta & 3) * 12288 + tid * 16;
#pragma unroll
    for (int q = 0; q < 4; q++) {
      const uint32_t rs = mapa(sb, (cta & 12) + q);
#pragma unroll
      for (int i = 0; i < 3; i++) {
        const float* a = acc + q * 24 + i * 8;
        const uint32_t x = pack2(a[0], a[1]), y = pack2(a[2], a[3]), z = pack2(a[4], a[5]), w = pack2(a[6], a[7]);
        if (q == (cta & 3)) sts4(sb + o + i * 4096, x, y, z, w); else sta4(rs + o + i * 4096, x, y, z, w, rs + B_R);
      }
    }
    mbar_wait(sb + B_R, 0);
    const int t = cta >> 2;
    bf16* out = P.out + (size_t)((TAIL0 + t / 3) * 128 + warp * 16 + ((tid & 31) >> 2)) * (2 * DM) + DM + (t % 3) * 192 + (cta & 3) * 48 + (tid & 3) * 2;
#pragma unroll
    for (int i = 0; i < 3; i++) {
      uint32_t v[4][4];
#pragma unroll
      for (int q = 0; q < 4; q++) lds4(v[q], sb + R_RED + q * 12288 + i * 4096 + tid * 16);
#pragma unroll
      for (int j = 0; j < 4; j++)
        *(uint32_t*)(out + (j & 1) * 8 * 2 * DM + i * 16 + (j >> 1) * 8) =
            pack2((blo(v[0][j]) + blo(v[1][j])) + (blo(v[2][j]) + blo(v[3][j])), (bhi(v[0][j]) + bhi(v[1][j])) + (bhi(v[2][j]) + bhi(v[3][j])));
    }
  }
}

DEVI void rec_aux(const RecParams& P, const uint32_t sb, const int cta) {
  const int tid = pin(threadIdx.x);
  {
    uint4 v[5];
#pragma unroll
    for (int j = 0; j < 5; j++) if (j * 128 + tid - 256 < 576) v[j] = ((const uint4*)P.mem0)[j * 128 + tid - 256];
    bar_sync(N_INIT, 256);
    if (tid == 256) {
      mbar_expect(sb + B_W2, 73728);
      for (int i = 0; i < 3; i++) tma_load(sb + R_WV + i * 24576, &P.wv, cta * 64, i * 192, sb + B_W2);
    }
    bar_sync(N_INIT1, 256);
#pragma unroll
    for (int j = 0; j < 5; j++) {
      const int i = j * 128 + tid - 256, t = i / 72, c = i - t * 72;
      if (i < 576) sts4(sb + R_H + (c >> 3) * 5120 + t * 128 + (((c & 7) ^ t) << 4), v[j].x, v[j].y, v[j].z, v[j].w);
    }
    fence_async();
    bar_arrive(N_SUM, 384);
    cluster_sync_relaxed();
    TL_END(12)
    wo_convert(sb, threadIdx.x & 31);
    bar_sync(N_O, 128);
    bar_arrive(N_INIT2, 384);
    TL_END(10)
  }
  const int rk = cta & 15, w4 = __shfl_sync(~0u, (threadIdx.x >> 5) & 3, 0);
  const uint32_t yg = pin((((threadIdx.x >> 5) & 3) * 16 + rk) * 1024 + ((threadIdx.x >> 4) & 1) * 128 + (threadIdx.x & 3) * 32 + ((threadIdx.x >> 2) & 3) * 8);
  uint32_t F[VB][4];
  auto v_prefetch = [&]() {
    const int lane = opq(tid) & 31;
    const uint32_t wv = sb + R_WV + ((lane & 7) + (lane >> 4) * 8) * 128 + (((w4 * 2 + ((lane >> 3) & 1)) ^ (lane & 7)) << 4);
#pragma unroll
    for (int k = 0; k < VB; k++) ldsm4t(F[k], wv + (VA + k * VI) * 2048);
  };
  mbar_wait(sb + B_W2, 0);
  TL_END(7)
  if (LATE == 2) pdl_trigger();
  v_prefetch();
  for (int s = 0; s < NSEG; s++) {
    const bool last = s == NSEG - 1;
    uint32_t va[12], p[5];
    int lane = opq(tid) & 31;
    {
      float acc[20];
      const uint64_t da = mkdesc(sb + R_WV, 0, 1024, 1), db = mkdesc(sb + R_H, 16, 1024, 1);
      PT(0)
      bar_sync(N_S, 256);
      asm volatile("fence.proxy.async::generic.acquire.sync_restrict::shared::cluster.cluster;" ::: "memory");
#pragma unroll
      for (int k = 0; k < 36; k++) {
        wg_fence();
        if (k >= VA && k < VA + VB * VI && (k - VA) % VI == 0) wg_rs40(acc, F[(k - VA) / VI], db + (k >> 2) * 320 + (k & 3) * 2, k);
        else wg_ss40<0>(acc, da + k * 128, db + (k >> 2) * 320 + (k & 3) * 2, k);
        wg_commit();
        if (k >= T0 && k < T1) wg_wait<VW>();
        else if (k >= T1 && k < T2) wg_wait<VW + 1>();
        if (k == 27) { wg_wait<4>(); asm volatile("{.reg .pred p; .reg .b32 a; setp.lt.u32 p,%1,%2; @p mapa.shared::cluster.u32 a,%0,%1; @p mbarrier.arrive.shared::cluster.b64 _,[a];}" ::"r"(sb + B_XF), "r"(tid - 256), "r"(last ? 0 : 6) : "memory"); }
      }
      PT(13)
      bar_sync(N_PM, 160);
      lds4(p, sb + R_P + 2560 + lane * 16); p[4] = lds1(sb + R_P + 3072 + lane * 4);
      wg_wait<0>();
      PT(1)
#pragma unroll
      for (int i = 0; i < 10; i++) va[i < 2 ? i + 8 : i - 2] = pack2(acc[2 * i], acc[2 * i + 1]);
      va[10] = va[11] = 0;
    }
    lane = opq(tid) & 31;
    {
      const uint32_t uo = R_U + w4 * 256 + lane * 4;
      float a[4] = {0, 0, 0, 0}, b[4] = {0, 0, 0, 0}, c[4] = {0, 0, 0, 0};
      mma16(a, va[0], va[1], va[2], va[3], p[0], p[1]); mma16(b, va[4], va[5], va[6], va[7], p[2], p[3]); mma8(c, va[8], va[9], p[4]);
      const uint32_t u0 = pack2(a[0] + b[0] + c[0], a[1] + b[1] + c[1]), u1 = pack2(a[2] + b[2] + c[2], a[3] + b[3] + c[3]);
      sts1(sb + uo, u0); sts1(sb + uo + 128, u1);
      __syncwarp();
      if (lane == 0) mbar_arrive(sb + B_V);
#pragma unroll
      for (int q = 1; q < 4; q++) { const uint32_t rs = mapa(sb, rk ^ q); sta1(rs + uo + q * 1024, u0, rs + B_U); sta1(rs + uo + q * 1024 + 128, u1, rs + B_U); }
      asm volatile("{.reg .pred p; .reg .b32 a; setp.lt.u32 p,%1,%3; @p mapa.shared::cluster.u32 a,%0,%2; @p mbarrier.arrive.shared::cluster.b64 _,[a];}" ::"r"(sb + B_XF), "r"(tid - 262), "r"(tid - 256), "r"(last ? 0 : 3) : "memory");
      PT(4)
      if (w4 == 3) {
        wo_tile<0, 8, 8, 2>(nullptr, sb, 8, cta, lane, ((64 + (lane >> 2)) * 2 + ((cta >> 1) & 1)) * 1024 + (cta >> 4) * 256 + (cta & 1) * 128 + ((cta >> 2) & 3) * 32 + (lane & 3) * 8, s);
      } else if (tid == 288 && rk < 9 && (!XI || rk >= 6) && !last) { mbar_wait(sb + B_XF, s & 1); x_load(P, sb, rk, s + 1); }
      PT(2)
    }
    lane = opq(tid) & 31;
    const uint8_t* y = (const uint8_t*)g_Y + (s & 1) * YSLOT + yg;
    uint32_t w0[8], w1[8], w2[8], ox[8];
    {
      float o[16];
      const uint64_t dp = mkdesc(sb + R_P, 128, 640, 0);
      bar_sync(N_WO, 384);
      wg_fence();
      wg_rs32(o, va, dp, 0); wg_rs32(o, va + 4, dp + 16, 1); wg_rs32(o, va + 8, mkdesc(sb + R_P + 512, 0, 640, 0), 1);
      wg_commit();
      const uint32_t tu = clk32();
      wg_wait<0>();
      PT(3)
#pragma unroll
      for (int i = 0; i < 8; i++) ox[i] = pack2(o[2 * i], o[2 * i + 1]);
      while (clk32() - tu < (uint32_t)YD) {}
      y_load(w0, y); y_load(w1, y + 4 * 16384);
      if (w4 == 0) y_load(w2, y + 8 * 16384);
      else {
#pragma unroll
        for (int i = 0; i < 8; i++) w2[i] = ((s >> 1) & 1) ^ 1;
      }
      PT(5)
    }
    if (!last) {
      const uint32_t dst = R_H + w4 * 5120 + (rk >> 1) * 128 + ((((rk & 1) * 4 + (lane >> 3)) ^ (rk >> 1)) << 4) + (lane & 4) * 2;
      const uint32_t tag = ((s >> 1) & 1) ^ 1, sel = (lane & 4) ? 0x3f800000u : 0x3f80u;
      uint32_t r0[2], r1[2], r2[2];
#pragma unroll 1
      for (int it = 0; (y_missing(w0, tag) | y_missing(w1, tag) | y_missing(w2, tag)) && it < (1 << 20); it++) {
        y_reload(w0, y, tag); y_reload(w1, y + 4 * 16384, tag); y_reload(w2, y + 8 * 16384, tag);
      }
      PT(7) GT(3)
      y_sum(r0, w0, sel); y_sum(r1, w1, sel); y_sum(r2, w2, sel);
      if (KA < 36 && SL == 0) bar_arrive(N_SUM + zero_after(__uint_as_float(r2[0])), 384);
      y_send(r0, sb, dst, B_Z0, lane);
      if (KA < 36 && SL == 1) bar_arrive(N_SUM, 384);
      y_send(r1, sb, dst + 4 * 5120, B_Z1, lane);
      if (w4 == 0) y_send(r2, sb, dst + 8 * 5120, B_Z1, lane);
      if (SL == 2) bar_arrive(N_SUM, 384);
      PT(9) GT(4)
    }
#pragma unroll
    for (int h = 0; h < 2; h++) stsm4t(sb + R_OX + lane * 128 + (((w4 * 2 + h) ^ (lane & 7)) << 4), ox[h], ox[2 + h], ox[4 + h], ox[6 + h]);
    if (last) break;
    v_prefetch();
    fence_async();
    bar_arrive(N_O, 160);
    PT(11)
  }
  fence_async();
  bar_arrive(N_O, 160);
  asm volatile("barrier.cluster.arrive.aligned;" ::: "memory");
  if (tid == 256 && cta < 60) {
    const int t = cta >> 2, m = TAIL0 + t / 3;
    mbar_expect(sb + B_R, 36864);
    out_produce<4, false>(P.o, sb, sb + B_O, m, t % 3, (cta & 3) * 16, 16, S_CTXB + m);
  }
  __syncwarp();
  asm volatile("barrier.cluster.wait.aligned;" ::: "memory");
}

__global__ void __launch_bounds__(384, 1) rec_kernel(const __grid_constant__ RecParams P) {
  extern __shared__ __align__(1024) uint8_t smem_raw[];
  const uint32_t sb = s2u(smem_raw);
  const int tid = threadIdx.x, cta = blockIdx.x;
  TL_START(1)
  if (!LATE) pdl_trigger();
  if (tid == 0) {
    for (int i = 0; i < 22; i++) mbar_init(sb + R_BAR + 8 * i, 8 * i == B_XF - R_BAR ? 16 : 8 * i == B_V - R_BAR ? 4 : i >= 16 && i < 20 ? 2 : 1);
    asm volatile("fence.mbarrier_init.release.cluster;" ::: "memory");
    asm volatile("cp.async.bulk.prefetch.L2.global [%0],%1;" ::"l"(P.x_raw + cta * DM), "r"(DM * 2) : "memory");
    mbar_expect(sb + B_W0, 73728); mbar_expect(sb + B_W1, 73728); mbar_expect(sb + B_W3, 73728);
    for (int i = 0; i < 3; i++) { tma_load(sb + R_WV + i * 24576, &P.wq, cta * 64, i * 192, sb + B_W0); tma_load(sb + R_H + i * 24576, &P.wk, cta * 64, i * 192, sb + B_W1); }
    mbar_expect(sb + B_XA, 24576); mbar_expect(sb + B_XB, 12288);
  }
  __syncthreads();
  if (tid == 288) {
    for (int i = 0; i < 36; i++) tma_load(sb + R_WO + i * 2048, &P.wo, (i >> 2) * 64 + (cta & 3) * 16, (cta ^ (i & 3)) * 64, sb + B_W3);
    for (int i = 0; i < 3; i++) asm volatile("cp.async.bulk.prefetch.tensor.2d.L2.global [%0,{%1,%2}];" ::"l"(&P.wv), "r"(cta * 64), "r"(i * 192) : "memory");
  }
  __syncwarp();
  if (tid >= 256) { reg_dec<504 - 2 * RP>(); rec_aux(P, sb, cta); }
  else { reg_inc<RP>(); rec_proj(P, sb, cta); }
  TL_END(1)
  asm volatile("barrier.cluster.arrive.aligned; barrier.cluster.wait.aligned;" ::: "memory");
}
typedef CUresult (*EncFn)(CUtensorMap*, CUtensorMapDataType, cuuint32_t, void*, const cuuint64_t*, const cuuint64_t*, const cuuint32_t*, const cuuint32_t*,
                          CUtensorMapInterleave, CUtensorMapSwizzle, CUtensorMapL2promotion, CUtensorMapFloatOOBfill);
static EncFn g_enc;
static CUtensorMap mk(const void* p, uint64_t cols, uint64_t rows, uint64_t pitch_elems, uint32_t box_rows, uint32_t box_cols = 64) {
  CUtensorMap m;
  cuuint64_t dim[2] = {cols, rows}, str[1] = {pitch_elems * 2};
  cuuint32_t box[2] = {box_cols, box_rows}, es[2] = {1, 1};
  g_enc(&m, CU_TENSOR_MAP_DATA_TYPE_BFLOAT16, 2, (void*)p, dim, str, box, es, CU_TENSOR_MAP_INTERLEAVE_NONE, box_cols == 64 ? CU_TENSOR_MAP_SWIZZLE_128B : CU_TENSOR_MAP_SWIZZLE_NONE,
        CU_TENSOR_MAP_L2_PROMOTION_L2_256B, CU_TENSOR_MAP_FLOAT_OOB_FILL_NONE);
  return m;
}
template <class T> static void* sym(T& s) { void* p; cudaGetSymbolAddress(&p, s); return p; }

#define FHC 22
#define FSL 4
#define NOE 5
#define OMC true
template <class K, class A> static void launch(K k, int grid, int smem, int cluster, bool pdl, const A& arg) {
  cudaLaunchConfig_t c = {};
  cudaLaunchAttribute at[2];
  int n = 0;
  if (cluster > 1) { at[n].id = cudaLaunchAttributeClusterDimension; at[n].val.clusterDim.x = cluster; at[n].val.clusterDim.y = at[n].val.clusterDim.z = 1; n++; }
  if (pdl) { at[n].id = cudaLaunchAttributeProgrammaticStreamSerialization; at[n].val.programmaticStreamSerializationAllowed = 1; n++; }
  c.gridDim = grid; c.blockDim = 384; c.dynamicSmemBytes = smem; c.stream = cudaStreamPerThread; c.attrs = at; c.numAttrs = n;
  cudaLaunchKernelEx(&c, k, arg);
}

extern "C" void kernel_launch(void* const* d_in, const int* in_sizes, int n_in, void* d_out, int out_size) {
  static int nb;
  if (!g_enc) {
    cudaDriverEntryPointQueryResult qr;
    cudaGetDriverEntryPoint("cuTensorMapEncodeTiled", (void**)&g_enc, cudaEnableDefault, &qr);
    cudaDeviceGetAttribute(&nb, cudaDevAttrMultiProcessorCount, 0);
    nb = nb - 64 < 16 ? 16 : nb - 64 > 128 ? 128 : (nb - 64) & ~1;
    cudaFuncSetAttribute(proj_kernel, cudaFuncAttributeMaxDynamicSharedMemorySize, SM_P);
    cudaFuncSetAttribute(out_kernel<false>, cudaFuncAttributeMaxDynamicSharedMemorySize, SM_O);
    cudaFuncSetAttribute(out_kernel<true>, cudaFuncAttributeMaxDynamicSharedMemorySize, SM_O);
    cudaFuncSetAttribute(fa_kernel, cudaFuncAttributeMaxDynamicSharedMemorySize, SM_F);
    cudaFuncSetAttribute(rec_kernel, cudaFuncAttributeMaxDynamicSharedMemorySize, R_END);
    cudaFuncSetAttribute(rec_kernel, cudaFuncAttributeNonPortableClusterSizeAllowed, 1);
  }
  const bf16 *Ax = (const bf16*)d_in[0], *Ac = (const bf16*)d_in[1], *Awq = (const bf16*)d_in[2], *Awk = (const bf16*)d_in[3], *Awv = (const bf16*)d_in[4],
             *Awo = (const bf16*)d_in[5], *Bx = (const bf16*)d_in[6], *Bm = (const bf16*)d_in[7], *Bwq = (const bf16*)d_in[8], *Bwk = (const bf16*)d_in[9],
             *Bwv = (const bf16*)d_in[10], *Bwo = (const bf16*)d_in[11];
  bf16* out = (bf16*)d_out;
  ProjParams p;
  p.a[0] = mk(Ac, 512, SEQ, 512, 128); p.a[1] = mk(Ax, DM, SEQ, DM, 128);
  p.w[0] = mk(Awk, HD, 512, HD, 64); p.w[1] = mk(Awv, HD, 512, HD, 64); p.w[2] = mk(Awq, HD, DM, HD, 64);
  p.c[0] = mk(sym(g_kA), HD, SEQ, HD, 64); p.c[1] = mk(sym(g_vA), HD, SEQ, HD, 64); p.c[2] = mk(sym(g_qA), HD, SEQ, HD, 64);
  {
    int parts[16];
    for (int i = 0; i < 16; i++) parts[i] = 1;
    for (int e = 0; e < nb / 2 - 16; e++) parts[e % 24 < 16 ? e % 8 : 15 - (e % 24 - 16)]++;
    p.nitems = 0;
    for (int i = 15; i >= 0; i--)
      for (int j = 0, nc = i < 8 ? 32 : 16, a = parts[i]; j < a; j++) {
        ProjItem& I = p.item[p.nitems++];
        I.pa = i >> 3; I.m = i & 7;
        I.c0[0] = j * nc / a; I.n[0] = (j + 1) * nc / a - I.c0[0];
        I.c0[1] = (j * nc + a - 1) / a; I.n[1] = ((j + 1) * nc + a - 1) / a - I.c0[1];
      }
  }
  OutParams o;
  for (int i = 0; i < 2; i++) {
    o.p[i].a = mk(i ? sym(g_ctxB) : sym(g_qA), HD, SEQ, HD, 128); o.p[i].b = mk(i ? Bwo : Awo, DM, HD, DM, 64); o.p[i].bh = mk(i ? Bwo : Awo, DM, HD, DM, 32);
    o.c[i] = mk(out + i * DM, DM, SEQ, 2 * DM, 64);
  }
  FaParams f;
  f.q = mk(sym(g_qA), HD, SEQ, HD, 128); f.k = mk(sym(g_kA), HD, SEQ, HD, 128); f.v = mk(sym(g_vA), HD, SEQ, HD, 128); f.o = mk(sym(g_qA), HD, SEQ, HD, 64);
  f.nctas = nb;
  for (int i = 0; i < 9; i++) f.nproj[i] = 0;
  for (int i = 0; i < p.nitems; i++) f.nproj[p.item[i].pa * (p.item[i].m + 1)] += 4;
  for (int key = -30, n = 0; n < 512; key++)
    for (int h = 0; h < 32; h++)
      for (int qt = 0; qt < 16; qt++)
        if ((h < FHC ? h : FHC) * FSL - qt * 2 == key) f.order[n++] = qt * 32 + h;
  RecParams r;
  r.wq = mk(Bwq, HD, DM, HD, 192); r.wk = mk(Bwk, HD, DM, HD, 192); r.wv = mk(Bwv, HD, DM, HD, 192); r.wo = mk(Bwo, DM, HD, DM, 64, 16);
  r.x_raw = Bx;
  r.x = mk(Bx, DM, SEQ, DM, 32); r.ctx = mk(sym(g_ctxB), HD, SEQ, HD, 32); r.mem0 = Bm; r.o = o.p[1]; r.out = out;

  launch(rec_kernel, 64, R_END, 16, false, r);
  launch(proj_kernel, nb, SM_P, 2, true, p);
  launch(fa_kernel, nb - NOE * 3, SM_F, 1, true, f);
  o.m0 = 0; o.nb = NOE * 3; o.id = 4;
  launch(out_kernel<false>, o.nb, SM_O, 1, true, o);
  launch(fa_kernel, NOE * 3, SM_F, 1, true, f);
  o.m0 = NOE; o.nb = (TAIL0 - NOE) * 3; o.id = 5;
  launch(out_kernel<OMC>, o.nb + 48, SM_O, OMC ? 2 : 1, true, o);
}
```

```cpp
#include <cuda_runtime.h>
#include <cuda_bf16.h>
#include <cuda.h>
#include <stdint.h>

typedef __nv_bfloat16 bf16;
#define DEVI __device__ __forceinline__
#define WAIT_FAIL(code) break
#define WAIT_MAX (1 << 22)

constexpr int SEQ = 2048, HD = 4096, DM = 576, NSEG = 64;

__device__ __align__(1024) bf16 g_qA[SEQ * HD], g_kA[SEQ * HD], g_vA[SEQ * HD];
__device__ __align__(1024) bf16 g_ctxB[SEQ * HD];
__device__ __align__(1024) uint4 g_Y[2 * 9 * 16 * 64];
enum { S_QUEUE = 0, S_EXIT = 1, S_PROJ = 32, S_CTXA = 64, S_CTXB = 96 };
__device__ unsigned g_sync[128];
#define CT(k, i) {}
#define TL_START(i)
#define TL_END(i)

DEVI uint32_t s2u(const void* p) { return (uint32_t)__cvta_generic_to_shared(p); }
DEVI void mbar_init(uint32_t b, uint32_t c) { asm volatile("mbarrier.init.shared::cta.b64 [%0],%1;" ::"r"(b), "r"(c)); }
DEVI void mbar_expect(uint32_t b, uint32_t n) { asm volatile("mbarrier.arrive.expect_tx.shared::cta.b64 _,[%0],%1;" ::"r"(b), "r"(n) : "memory"); }
DEVI void mbar_arrive(uint32_t b) { asm volatile("mbarrier.arrive.shared::cta.b64 _,[%0];" ::"r"(b) : "memory"); }
DEVI void mbar_wait(uint32_t b, uint32_t ph) {
  uint32_t ok; int it = 0;
  do {
    asm volatile("{.reg .pred p; mbarrier.try_wait.parity.shared::cta.b64 p,[%1],%2; selp.u32 %0,1,0,p;}" : "=r"(ok) : "r"(b), "r"(ph) : "memory");
    if (!ok && ++it > WAIT_MAX) WAIT_FAIL(b & 0xffffff);
  } while (!ok);
}
DEVI bool mbar_try(uint32_t b, uint32_t ph) {
  uint32_t ok;
  asm volatile("{.reg .pred p; mbarrier.try_wait.parity.shared::cta.b64 p,[%1],%2; selp.u32 %0,1,0,p;}" : "=r"(ok) : "r"(b), "r"(ph) : "memory");
  return ok;
}
DEVI bool mbar_test(uint32_t b, uint32_t ph) {
  uint32_t ok;
  asm volatile("{.reg .pred p; mbarrier.test_wait.parity.shared::cta.b64 p,[%1],%2; selp.u32 %0,1,0,p;}" : "=r"(ok) : "r"(b), "r"(ph) : "memory");
  return ok;
}
DEVI void mwait(uint32_t b, uint32_t ph) { if (__builtin_expect(!mbar_try(b, ph), 0)) mbar_wait(b, ph); }
DEVI void tma_load(uint32_t dst, const CUtensorMap* tm, int c0, int c1, uint32_t bar) {
  asm volatile("cp.async.bulk.tensor.2d.shared::cluster.global.mbarrier::complete_tx::bytes [%0],[%1,{%3,%4}],[%2];" ::"r"(dst), "l"(tm), "r"(bar), "r"(c0), "r"(c1) : "memory");
}
DEVI void tma_store(const CUtensorMap* tm, uint32_t src, int c0, int c1) {
  asm volatile("cp.async.bulk.tensor.2d.global.shared::cta.bulk_group [%0,{%2,%3}],[%1];" ::"l"(tm), "r"(src), "r"(c0), "r"(c1) : "memory");
}
DEVI void bulk_commit() { asm volatile("cp.async.bulk.commit_group;" ::: "memory"); }
template <int N> DEVI void bulk_wait_read() { asm volatile("cp.async.bulk.wait_group.read %0;" ::"n"(N) : "memory"); }
template <int N> DEVI void bulk_wait() { asm volatile("cp.async.bulk.wait_group %0;" ::"n"(N) : "memory"); }
DEVI void fence_async() { asm volatile("fence.proxy.async.shared::cta;" ::: "memory"); }
DEVI void bar_sync(int id, int n) { asm volatile("bar.sync %0,%1;" ::"r"(id), "r"(n) : "memory"); }
DEVI void bar_arrive(int id, int n) { asm volatile("bar.arrive %0,%1;" ::"r"(id), "r"(n) : "memory"); }
template <int R> DEVI void reg_inc() { asm volatile("setmaxnreg.inc.sync.aligned.u32 %0;" ::"n"(R)); }
template <int R> DEVI void reg_dec() { asm volatile("setmaxnreg.dec.sync.aligned.u32 %0;" ::"n"(R)); }
DEVI void wg_fence() { asm volatile("wgmma.fence.sync.aligned;" ::: "memory"); }
DEVI void wg_commit() { asm volatile("wgmma.commit_group.sync.aligned;" ::: "memory"); }
template <int N> DEVI void wg_wait() { asm volatile("wgmma.wait_group.sync.aligned %0;" ::"n"(N) : "memory"); }
DEVI uint64_t desc_k(uint32_t a) { return (uint64_t)((a >> 4) & 0x3fff) | (1ull << 16) | (64ull << 32) | (1ull << 62); }
DEVI uint64_t desc_mn(uint32_t a, uint32_t lbo) { return (uint64_t)((a >> 4) & 0x3fff) | ((uint64_t)(lbo >> 4) << 16) | (64ull << 32) | (1ull << 62); }
DEVI uint32_t pack2(float lo, float hi) { uint32_t r; asm("cvt.rn.bf16x2.f32 %0,%1,%2;" : "=r"(r) : "f"(hi), "f"(lo)); return r; }
DEVI float ex2(float x) { float y; asm("ex2.approx.ftz.f32 %0,%1;" : "=f"(y) : "f"(x)); return y; }
DEVI void stsm4(uint32_t a, uint32_t r0, uint32_t r1, uint32_t r2, uint32_t r3) {
  asm volatile("stmatrix.sync.aligned.m8n8.x4.shared.b16 [%0],{%1,%2,%3,%4};" ::"r"(a), "r"(r0), "r"(r1), "r"(r2), "r"(r3) : "memory");
}
DEVI void ldsm4(uint32_t* r, uint32_t a) {
  asm volatile("ldmatrix.sync.aligned.m8n8.x4.shared.b16 {%0,%1,%2,%3},[%4];" : "=r"(r[0]), "=r"(r[1]), "=r"(r[2]), "=r"(r[3]) : "r"(a) : "memory");
}
DEVI void ldsm4t(uint32_t* r, uint32_t a) {
  asm volatile("ldmatrix.sync.aligned.m8n8.x4.trans.shared.b16 {%0,%1,%2,%3},[%4];" : "=r"(r[0]), "=r"(r[1]), "=r"(r[2]), "=r"(r[3]) : "r"(a) : "memory");
}
DEVI void mma16(float* d, uint32_t a0, uint32_t a1, uint32_t a2, uint32_t a3, uint32_t b0, uint32_t b1) {
  asm volatile("mma.sync.aligned.m16n8k16.row.col.f32.bf16.bf16.f32 {%0,%1,%2,%3},{%4,%5,%6,%7},{%8,%9},{%0,%1,%2,%3};"
               : "+f"(d[0]), "+f"(d[1]), "+f"(d[2]), "+f"(d[3]) : "r"(a0), "r"(a1), "r"(a2), "r"(a3), "r"(b0), "r"(b1));
}

DEVI void pdl_trigger() { asm volatile("griddepcontrol.launch_dependents;" ::: "memory"); }
DEVI void signal_after_bulk(int f) {
  asm volatile("fence.proxy.async.global;" ::: "memory");
  asm volatile("red.release.gpu.global.add.u32 [%0], 1;" ::"l"(g_sync + f) : "memory");
}
DEVI void flag_wait(int f, unsigned n, unsigned waiters) {
  for (int it = 0;; it++) {
    if (it > WAIT_MAX) WAIT_FAIL(f);
    unsigned v; asm volatile("ld.acquire.gpu.global.u32 %0, [%1];" : "=r"(v) : "l"(g_sync + f) : "memory");
    if (v >= n) break;
    __nanosleep(64);
  }
  if (waiters) asm volatile("red.relaxed.gpu.global.inc.u32 [%0], %1;" ::"l"(g_sync + f), "r"(n + waiters - 1) : "memory");
  asm volatile("fence.proxy.async.global;" ::: "memory");
}
DEVI uint32_t mapa(uint32_t a, uint32_t r) { uint32_t o; asm("mapa.shared::cluster.u32 %0,%1,%2;" : "=r"(o) : "r"(a), "r"(r)); return o; }
DEVI void tma_load_mc(uint32_t dst, const CUtensorMap* tm, int c0, int c1, uint32_t bar, uint16_t mask) {
  asm volatile("cp.async.bulk.tensor.2d.shared::cluster.global.mbarrier::complete_tx::bytes.multicast::cluster [%0],[%1,{%3,%4}],[%2],%5;" ::"r"(dst), "l"(tm), "r"(bar), "r"(c0), "r"(c1), "h"(mask) : "memory");
}
DEVI void arrive_pair(uint32_t b) { if ((threadIdx.x & 127) < 2) asm volatile("mbarrier.arrive.shared::cluster.b64 _,[%0];" ::"r"(mapa(b, threadIdx.x & 1)) : "memory"); }
DEVI void cluster_sync_relaxed() { asm volatile("barrier.cluster.arrive.relaxed.aligned; barrier.cluster.wait.aligned;" ::: "memory"); }
DEVI void cluster_sync() { asm volatile("barrier.cluster.arrive.aligned; barrier.cluster.wait.aligned;" ::: "memory"); }
DEVI void sts4(uint32_t a, uint32_t x, uint32_t y, uint32_t z, uint32_t w) { asm volatile("st.shared.v4.b32 [%0],{%1,%2,%3,%4};" ::"r"(a), "r"(x), "r"(y), "r"(z), "r"(w) : "memory"); }
DEVI void lds4(uint32_t* r, uint32_t a) { asm volatile("ld.shared.v4.b32 {%0,%1,%2,%3},[%4];" : "=r"(r[0]), "=r"(r[1]), "=r"(r[2]), "=r"(r[3]) : "r"(a) : "memory"); }
DEVI void sta4(uint32_t d, uint32_t a, uint32_t b, uint32_t c, uint32_t e, uint32_t bar) {
  asm volatile("st.async.weak.shared::cluster.mbarrier::complete_tx::bytes.v4.b32 [%0],{%1,%2,%3,%4},[%5];" ::"r"(d), "r"(a), "r"(b), "r"(c), "r"(e), "r"(bar) : "memory");
}
DEVI float blo(uint32_t u) { return __uint_as_float(u << 16); }
DEVI float bhi(uint32_t u) { return __uint_as_float(u & 0xffff0000u); }

#define F8(a, o) "+f"(a[o]), "+f"(a[o + 1]), "+f"(a[o + 2]), "+f"(a[o + 3]), "+f"(a[o + 4]), "+f"(a[o + 5]), "+f"(a[o + 6]), "+f"(a[o + 7])
#define F32(a, o) F8(a, o), F8(a, o + 8), F8(a, o + 16), F8(a, o + 24)
template<int TB> DEVI void wg_ss128(float* d, uint64_t da, uint64_t db, int acc){
 asm volatile("{.reg .pred p; setp.ne.b32 p,%66,0;\n wgmma.mma_async.sync.aligned.m64n128k16.f32.bf16.bf16 {%0,%1,%2,%3,%4,%5,%6,%7,%8,%9,%10,%11,%12,%13,%14,%15,%16,%17,%18,%19,%20,%21,%22,%23,%24,%25,%26,%27,%28,%29,%30,%31,%32,%33,%34,%35,%36,%37,%38,%39,%40,%41,%42,%43,%44,%45,%46,%47,%48,%49,%50,%51,%52,%53,%54,%55,%56,%57,%58,%59,%60,%61,%62,%63},%64,%65,p,1,1,0,%67;}"
 : F32(d,0),F32(d,32) : "l"(da),"l"(db),"r"(acc),"n"(TB));}
template<int TB> DEVI void wg_ss192(float* d, uint64_t da, uint64_t db, int acc){
 asm volatile("{.reg .pred p; setp.ne.b32 p,%98,0;\n wgmma.mma_async.sync.aligned.m64n192k16.f32.bf16.bf16 {%0,%1,%2,%3,%4,%5,%6,%7,%8,%9,%10,%11,%12,%13,%14,%15,%16,%17,%18,%19,%20,%21,%22,%23,%24,%25,%26,%27,%28,%29,%30,%31,%32,%33,%34,%35,%36,%37,%38,%39,%40,%41,%42,%43,%44,%45,%46,%47,%48,%49,%50,%51,%52,%53,%54,%55,%56,%57,%58,%59,%60,%61,%62,%63,%64,%65,%66,%67,%68,%69,%70,%71,%72,%73,%74,%75,%76,%77,%78,%79,%80,%81,%82,%83,%84,%85,%86,%87,%88,%89,%90,%91,%92,%93,%94,%95},%96,%97,p,1,1,0,%99;}"
 : F32(d,0),F32(d,32),F32(d,64) : "l"(da),"l"(db),"r"(acc),"n"(TB));}
template<int TB> DEVI void wg_rs128(float* d, const uint32_t* a, uint64_t db, int acc){
 asm volatile("{.reg .pred p; setp.ne.b32 p,%69,0;\n wgmma.mma_async.sync.aligned.m64n128k16.f32.bf16.bf16 {%0,%1,%2,%3,%4,%5,%6,%7,%8,%9,%10,%11,%12,%13,%14,%15,%16,%17,%18,%19,%20,%21,%22,%23,%24,%25,%26,%27,%28,%29,%30,%31,%32,%33,%34,%35,%36,%37,%38,%39,%40,%41,%42,%43,%44,%45,%46,%47,%48,%49,%50,%51,%52,%53,%54,%55,%56,%57,%58,%59,%60,%61,%62,%63},{%64,%65,%66,%67},%68,p,1,1,%70;}"
 : F32(d,0),F32(d,32) : "r"(a[0]),"r"(a[1]),"r"(a[2]),"r"(a[3]),"l"(db),"r"(acc),"n"(TB));}
struct ProjItem { uint8_t pa, m, c0[2], n[2]; };
struct ProjParams { CUtensorMap a[2], w[3], c[3]; ProjItem item[64]; int nitems; };
#define PWD 1
constexpr int PST = 12, SM_P = PST * 16384 + 32768 + 256;
DEVI void proj_decode(const ProjItem& I, int t, int& pw, int& n) {
  const int g = t >= I.n[0], c = g ? I.c0[1] + t - I.n[0] : I.c0[0] + t;
  pw = I.pa ? 2 : c >> 4; n = (c & 15) + g * 16;
}
__global__ void __launch_bounds__(384, 1) proj_kernel(const __grid_constant__ ProjParams P) {
  extern __shared__ __align__(1024) uint8_t smem_raw[];
  const uint32_t base = __shfl_sync(~0u, s2u(smem_raw), 0), stg = base + PST * 16384, full = stg + 32768, empty = full + 8 * PST, of = empty + 8 * PST, oe = of + 16;
  const int tid = threadIdx.x, wg = __shfl_sync(~0u, tid >> 7, 0);
  TL_START(2)
  pdl_trigger();
  if (tid == 0) {
    for (int i = 0; i < PST; i++) { mbar_init(full + 8 * i, 1); mbar_init(empty + 8 * i, 4); }
    for (int i = 0; i < 2; i++) { mbar_init(of + 8 * i, 4); mbar_init(oe + 8 * i, 1); }
    asm volatile("fence.mbarrier_init.release.cluster;" ::: "memory");
  }
  cluster_sync_relaxed();
  if (wg == 2) {
    reg_dec<24>();
    const int r = blockIdx.x & 1;
    if (tid == 256) {
      int s = 0, ph = 1;
      for (int it = blockIdx.x >> 1; it < P.nitems; it += gridDim.x >> 1) {
        const ProjItem& I = P.item[it];
        const int nk = 8 + I.pa;
        for (int t = -1; t < I.n[0] + I.n[1]; t++) {
          int pw, n; proj_decode(I, t, pw, n);
          for (int k = 0; k < nk; k++) {
            mbar_wait(empty + 8 * s, ph);
            mbar_expect(full + 8 * s, 16384);
            if (t < 0) tma_load(base + s * 16384, &P.a[I.pa], k * 64, (I.m * 2 + r) * 128, full + 8 * s);
            else tma_load_mc(base + s * 16384 + r * 8192, &P.w[pw], n * 128 + r * 64, k * 64, full + 8 * s, 3);
            if (++s == PST) { s = 0; ph ^= 1; }
          }
        }
      }
      for (int i = 0; i < PST; i++) { mbar_wait(empty + 8 * s, ph); if (++s == PST) { s = 0; ph ^= 1; } }
    } else if (tid == 288 || tid == 320) {
      const int g = tid == 320;
      int c = 0;
      for (int it = blockIdx.x >> 1; it < P.nitems; it += gridDim.x >> 1) {
        const ProjItem& I = P.item[it];
        for (int t = 0; t < I.n[0] + I.n[1]; t++, c++) {
          int pw, n; proj_decode(I, t, pw, n);
          mbar_wait(of + 8 * g, c & 1);
          tma_store(&P.c[pw], stg + g * 16384, n * 128, (I.m * 2 + r) * 128 + g * 64);
          tma_store(&P.c[pw], stg + g * 16384 + 8192, n * 128 + 64, (I.m * 2 + r) * 128 + g * 64);
          bulk_commit();
          bulk_wait_read<0>();
          mbar_arrive(oe + 8 * g);
          if (t == 3 && !g) CT(0, 1)
          if (t == I.n[0] - 1) { bulk_wait<0>(); signal_after_bulk(S_PROJ + I.pa * (I.m + 1) * 2); }
        }
        bulk_wait<0>(); signal_after_bulk(S_PROJ + I.pa * (I.m + 1) * 2 + 1);
      }
      if (!g) CT(0, 2)
    }
  } else {
    reg_inc<240>();
    uint32_t A[36][4];
    float acc[64];
    uint32_t s = 0, ph = 0, c = 1;
    const uint32_t row = ((tid >> 5) & 3) * 16 + (tid & 15);
    const uint32_t roff = row * 128 + ((((tid >> 4) & 1) ^ (row & 7)) << 4);
    const uint32_t rel = mapa(empty, tid & 1);
    auto release = [&](uint32_t st) { asm volatile("{.reg .pred p; setp.lt.u32 p,%1,2; @p mbarrier.arrive.shared::cluster.b64 _,[%0];}" ::"r"(rel + 8 * st), "r"(tid & 127) : "memory"); };
    for (int it = blockIdx.x >> 1; it < P.nitems; it += gridDim.x >> 1) {
      const int pa = P.item[it].pa, nt = P.item[it].n[0] + P.item[it].n[1];
#pragma unroll
      for (int k = 0; k < 9; k++) {
        if (k < 8 || pa) {
          mbar_wait(full + 8 * s, ph);
#pragma unroll
          for (int kk = 0; kk < 4; kk++) ldsm4(A[4 * k + kk], base + s * 16384 + wg * 8192 + (roff ^ (kk * 32)));
          bar_sync(1 + wg, 128);
          release(s);
          if (++s == PST) { s = 0; ph ^= 1; }
        }
      }
      if (tid == 0) CT(0, 0)
      if (wg) bar_sync(3, 256);
      bool ok = false;
      for (int t = 0; t < nt; t++, c ^= 1) {
        uint32_t p1 = 0, p2 = 0;
#pragma unroll
        for (int k = 0; k < 9; k++) {
          if (k < 8 || pa) {
            if (!ok) mbar_wait(full + 8 * s, ph);
            const uint64_t db = desc_mn(base + s * 16384, 8192);
            wg_fence();
#pragma unroll
            for (int kk = 0; kk < 4; kk++) wg_rs128<1>(acc, A[4 * k + kk], db + kk * 128, k | kk);
            wg_commit();
            const uint32_t cur = s;
            if (++s == PST) { s = 0; ph ^= 1; }
            ok = mbar_test(full + 8 * s, ph);
            if (PWD == 1) { if (k) { wg_wait<1>(); release(p1); } }
            else if (k > 1) { wg_wait<2>(); release(p2); }
            if (k == 4 && t == 0 && !wg) bar_arrive(3, 256);
            p2 = p1; p1 = cur;
          }
        }
        mwait(oe + 8 * wg, c);
        if (PWD == 2) { wg_wait<1>(); release(p2); }
        wg_wait<0>();
        release(p1);
#pragma unroll
        for (int i = 0; i < 8; i++) {
          const float* a = acc + i * 8;
          stsm4(stg + wg * 16384 + (i >> 2) * 8192 + (roff ^ ((i & 3) * 32)), pack2(a[0], a[1]), pack2(a[2], a[3]), pack2(a[4], a[5]), pack2(a[6], a[7]));
        }
        fence_async();
        __syncwarp();
        if ((tid & 31) == 0) mbar_arrive(of + 8 * wg);
      }
    }
  }
}

struct OutMaps { CUtensorMap a, b, bh; };
constexpr int OSB = 40960;
template <int NST, bool MC> DEVI void out_produce(const OutMaps& M, uint32_t base, uint32_t full, int m, int n, int k0, int nk, int flag = -1) {
  const int r = MC ? blockIdx.x & 1 : 0;
  int s = 0, ph = 1;
#pragma unroll 1
  for (int k = 0; k < nk + (MC ? NST - 1 : 0); k++) {
    mbar_wait(full + 8 * (NST + s), ph);
    if (k < nk) {
      mbar_expect(full + 8 * s, OSB);
#pragma unroll 1
      for (int j = 0; j < 3; j++) {
        if (MC) tma_load_mc(base + s * OSB + 16384 + j * 8192 + r * 4096, &M.bh, n * 192 + j * 64, (k0 + k) * 64 + r * 32, full + 8 * s, 3);
        else tma_load(base + s * OSB + 16384 + j * 8192, &M.b, n * 192 + j * 64, (k0 + k) * 64, full + 8 * s);
      }
      const bool now = flag >= 0 && k == NST - 1;
      if (now) flag_wait(flag, 64, 15);
#pragma unroll 1
      for (int d = now ? NST - 1 : k < NST ? -1 : 0; d >= 0; d--) tma_load(base + (s - d) * OSB, &M.a, (k0 + k - d) * 64, m * 128, full + 8 * (s - d));
    }
    if (++s == NST) { s = 0; ph ^= 1; }
  }
}
template <int NST> DEVI void out_first(const OutMaps& M, uint32_t base, uint32_t full, int m, int k0, int nk, int flag) {
  flag_wait(flag, 64, 3);
#pragma unroll 1
  for (int k = 0; k < NST; k++) tma_load(base + k * OSB, &M.a, (k0 + k) * 64, m * 128, full + 8 * k);
}
template <int NST, bool MC> DEVI void out_consume(float* acc, uint32_t base, uint32_t full, int nk) {
  const uint32_t empty = full + 8 * NST;
  const int wg = threadIdx.x >> 7;
  int s = 0, ph = 0, prev = 0;
#pragma unroll 1
  for (int k = 0; k < nk; k++) {
    mbar_wait(full + 8 * s, ph);
    const uint64_t da = desc_k(base + s * OSB + wg * 8192), db = desc_mn(base + s * OSB + 16384, 8192);
    wg_fence();
#pragma unroll
    for (int kk = 0; kk < 4; kk++) wg_ss192<1>(acc, da + kk * 2, db + kk * 128, k | kk);
    wg_commit();
    if (k) { wg_wait<1>(); if (MC) arrive_pair(empty + 8 * prev); else if ((threadIdx.x & 127) == 0) mbar_arrive(empty + 8 * prev); }
    prev = s;
    if (++s == NST) { s = 0; ph ^= 1; }
  }
  wg_wait<0>();
}
struct OutParams { OutMaps p[2]; CUtensorMap c[2]; int m0, nb, id; };
#define OST 4
constexpr int SM_O = 5 * OSB + 256;
template <bool MC> __global__ void __launch_bounds__(384, 1) out_kernel(const __grid_constant__ OutParams P) {
  extern __shared__ __align__(1024) uint8_t smem_raw[];
  const uint32_t base = s2u(smem_raw), full = base + OST * OSB;
  const int tid = threadIdx.x, wg = tid >> 7;
  const int pb = (int)blockIdx.x < P.nb, t = pb ? blockIdx.x : 47 - (blockIdx.x - P.nb);
  const int m = (pb ? P.m0 : 0) + (MC ? t / 6 * 2 + (t & 1) : t / 3), n = MC ? (t >> 1) % 3 : t % 3;
  TL_START(P.id)
  pdl_trigger();
  if (tid == 0) {
    for (int i = 0; i < OST; i++) { mbar_init(full + 8 * i, 1); mbar_init(full + 8 * (OST + i), MC ? 4 : 2); }
    asm volatile("fence.mbarrier_init.release.cluster;" ::: "memory");
  }
  if (MC) cluster_sync_relaxed(); else __syncthreads();
  if (wg == 2) {
    if (tid == 256) out_produce<OST, MC>(P.p[pb], base, full, m, n, 0, 64);
    if (tid == 288) out_first<OST>(P.p[pb], base, full, m, 0, 64, (pb ? S_CTXB : S_CTXA) + m);
  } else {
    float acc[96];
    if (tid == 0) CT(P.id, 0)
    out_consume<OST, MC>(acc, base, full, 64);
    if (tid == 0) CT(P.id, 2)
    bar_sync(3, 256);
    const uint32_t row = ((tid >> 5) & 3) * 16 + (tid & 15);
    const uint32_t roff = row * 128 + ((((tid >> 4) & 1) ^ (row & 7)) << 4);
#pragma unroll
    for (int i = 0; i < 12; i++) {
      const float* a = acc + i * 8;
      stsm4(base + wg * 24576 + (i >> 2) * 8192 + (roff ^ ((i & 3) * 32)), pack2(a[0], a[1]), pack2(a[2], a[3]), pack2(a[4], a[5]), pack2(a[6], a[7]));
    }
    fence_async();
    bar_sync(1 + wg, 128);
    if ((tid & 127) == 0) {
      for (int c = 0; c < 3; c++) tma_store(&P.c[pb], base + wg * 24576 + c * 8192, n * 192 + c * 64, m * 128 + wg * 64);
      bulk_commit();
      bulk_wait<0>();
    }
    TL_END(P.id)
  }
}
struct FaParams { CUtensorMap q, k, v, o; unsigned nctas; uint8_t nproj[12]; uint16_t order[512]; };
constexpr int SM_F = 7 * 32768 + 256;
constexpr float FA_C = 0.08838834764831845f * 1.4426950408889634f;
DEVI int fa_qt(int w) { return w >> 5; }
DEVI int fa_hc(int w) { return (w & 31) * 128; }

DEVI void fa_exp(const float* S, uint32_t* Pn, float mc0, float mc1, float& s0, float& s1) {
  float a0 = 0.f, a1 = 0.f, b0 = 0.f, b1 = 0.f;
#pragma unroll
  for (int j = 0; j < 16; j++) {
    const float e0 = ex2(fmaf(S[4 * j], FA_C, -mc0)), e1 = ex2(fmaf(S[4 * j + 1], FA_C, -mc0));
    const float e2 = ex2(fmaf(S[4 * j + 2], FA_C, -mc1)), e3 = ex2(fmaf(S[4 * j + 3], FA_C, -mc1));
    a0 += e0; a1 += e1; b0 += e2; b1 += e3;
    Pn[2 * j] = pack2(e0, e1); Pn[2 * j + 1] = pack2(e2, e3);
  }
  s0 = a0 + a1; s1 = b0 + b1;
}

struct FaState { float mc0, mc1, l0, l1; int w, j, qi; uint32_t dq; bool first; };
enum { F_Q = 0, F_K = 2 * 32768, F_V = 4 * 32768, F_O = 6 * 32768, F_QF = 7 * 32768, F_QE = F_QF + 16, F_KF = F_QF + 32, F_KE = F_QF + 48, F_VF = F_QF + 64, F_VE = F_QF + 80,
       F_OF = F_QF + 96, F_OE = F_QF + 112, F_INFO = F_QF + 128 };

template <int SC> DEVI bool fa_step(FaState& T, float* O, float* S, const uint32_t* Pc, uint32_t* Pn, uint32_t base, int tid, int wg, uint32_t ph) {
  const bool el = (tid & 127) == 0, fin = T.j == 0;
  int wn = T.w, jn = T.j - 1;
  const bool okk = mbar_try(base + F_KF + 8 * (SC ^ 1), ph), okv = mbar_try(base + F_VF + 8 * SC, ph ^ SC);
  if (fin) {
    T.qi++; T.dq ^= 2048;
    mbar_wait(base + F_QF + 8 * (T.qi & 1), (T.qi >> 1) & 1);
    asm volatile("ld.shared.b32 %0,[%1];" : "=r"(wn) : "r"(base + F_INFO + (T.qi & 1) * 4) : "memory");
    wn = __shfl_sync(~0u, wn, 0);
    jn = fa_qt(wn);
  }
  if (!(okk && okv)) { mbar_wait(base + F_KF + 8 * (SC ^ 1), ph); mbar_wait(base + F_VF + 8 * SC, ph ^ SC); }
  const bool last = wn < 0;
  {
    const uint64_t dq = desc_k(0) | T.dq, dk = desc_k(base + F_K + (SC ^ 1) * 32768), dv = desc_mn(base + F_V + SC * 32768, 16384);
    bar_sync(3 + wg, 256);
    wg_fence();
#pragma unroll
    for (int kk = 0; kk < 8; kk++) wg_ss128<0>(S, dq + (kk & 3) * 2 + (kk >> 2) * 1024, dk + (kk & 3) * 2 + (kk >> 2) * 1024, kk);
    wg_commit();
#pragma unroll
    for (int kk = 0; kk < 8; kk++) wg_rs128<1>(O, Pc + 4 * kk, dv + kk * 128, kk || !T.first);
    wg_commit();
    bar_arrive(4 - wg, 256);
  }
  wg_wait<1>();
  asm volatile("{.reg .pred p,q; setp.ne.u32 p,%0,0; setp.eq.and.u32 q,%1,0,p; @p mbarrier.arrive.shared::cta.b64 _,[%2]; @q mbarrier.arrive.shared::cta.b64 _,[%3];}"
               ::"r"((uint32_t)el), "r"(jn), "r"(base + F_KE + 8 * (SC ^ 1)), "r"(base + F_QE + 8 * (T.qi & 1)) : "memory");
  const float lp0 = T.l0, lp1 = T.l1;
  float s0 = 0.f, s1 = 0.f, f0 = 1.f, f1 = 1.f;
  bool exact = fin;
  if (!fin) {
    fa_exp(S, Pn, T.mc0, T.mc1, s0, s1);
    exact = __any_sync(~0u, !(fmaxf(s0, s1) <= 1073741824.f));
  }
  if (exact && !last) {
    float a = -INFINITY, b = -INFINITY;
    if (fin) {
      const int row = (tid >> 5) * 16 + ((tid & 31) >> 2) - (tid & 3) * 2;
#pragma unroll
      for (int j = 0; j < 16; j++) {
        if (j * 8 > row) S[4 * j] = -INFINITY;
        if (j * 8 + 1 > row) S[4 * j + 1] = -INFINITY;
        if (j * 8 > row + 8) S[4 * j + 2] = -INFINITY;
        if (j * 8 + 1 > row + 8) S[4 * j + 3] = -INFINITY;
      }
      T.mc0 = T.mc1 = -INFINITY;
    }
#pragma unroll
    for (int j = 0; j < 16; j++) { a = fmaxf(a, fmaxf(S[4 * j], S[4 * j + 1])); b = fmaxf(b, fmaxf(S[4 * j + 2], S[4 * j + 3])); }
    a = fmaxf(a, __shfl_xor_sync(~0u, a, 1)); b = fmaxf(b, __shfl_xor_sync(~0u, b, 1));
    a = fmaxf(a, __shfl_xor_sync(~0u, a, 2)); b = fmaxf(b, __shfl_xor_sync(~0u, b, 2));
    a = fmaxf(a * FA_C, T.mc0); b = fmaxf(b * FA_C, T.mc1);
    f0 = ex2(T.mc0 - a); f1 = ex2(T.mc1 - b);
    T.mc0 = a; T.mc1 = b;
    T.l0 = fin ? 0.f : T.l0 * f0; T.l1 = fin ? 0.f : T.l1 * f1;
    fa_exp(S, Pn, a, b, s0, s1);
  }
  T.l0 += s0; T.l1 += s1;
  wg_wait<0>();
  if (el) mbar_arrive(base + F_VE + 8 * SC);
  if (exact) {
    if (fin) {
      f0 = lp0 + __shfl_xor_sync(~0u, lp0, 1); f1 = lp1 + __shfl_xor_sync(~0u, lp1, 1);
      f0 += __shfl_xor_sync(~0u, f0, 2); f1 += __shfl_xor_sync(~0u, f1, 2);
      f0 = 1.f / f0; f1 = 1.f / f1;
    }
#pragma unroll
    for (int i = 0; i < 16; i++) { O[4 * i] *= f0; O[4 * i + 1] *= f0; O[4 * i + 2] *= f1; O[4 * i + 3] *= f1; }
    if (fin && (T.qi || last)) {
      const uint32_t row = ((tid >> 5) & 3) * 16 + (tid & 15);
      const uint32_t o = base + F_O + wg * 16384 + row * 128 + ((((tid >> 4) & 1) ^ (row & 7)) << 4);
      if (T.qi) mbar_wait(base + F_OE + 8 * wg, T.qi & 1);
#pragma unroll
      for (int i = 0; i < 8; i++) {
        const float* a = O + i * 8;
        stsm4((o ^ ((i & 3) * 32)) + (i >> 2) * 8192, pack2(a[0], a[1]), pack2(a[2], a[3]), pack2(a[4], a[5]), pack2(a[6], a[7]));
      }
      if (el) asm volatile("st.shared.b32 [%0],%1;" ::"r"(base + F_INFO + 8 + wg * 4), "r"(!T.qi ? -1 : T.w | (last ? 1024 : 0)) : "memory");
      fence_async();
      __syncwarp();
      if ((tid & 31) == 0) mbar_arrive(base + F_OF + 8 * wg);
    }
  }
  T.w = wn; T.j = jn; T.first = fin;
  return last;
}

__global__ void __launch_bounds__(384, 1) fa_kernel(const __grid_constant__ FaParams P) {
  extern __shared__ __align__(1024) uint8_t smem_raw[];
  const uint32_t base = s2u(smem_raw);
  const uint32_t sQ = base, sK = base + 2 * 32768, sV = base + 4 * 32768, sO = base + 6 * 32768, bars = base + 7 * 32768;
  const uint32_t qf = bars, qe = bars + 16, kf = bars + 32, ke = bars + 48, vf = bars + 64, ve = bars + 80, of = bars + 96, oe = bars + 112;
  volatile int* info = (volatile int*)(smem_raw + 7 * 32768 + 128);
  const int tid = threadIdx.x, wg = tid >> 7;
  pdl_trigger();
  if (tid == 0) {
    for (int i = 0; i < 16; i++) mbar_init(bars + 8 * i, i >= 14 ? 1 : i >= 12 ? 4 : (i & 2) ? 2 : 1);
    info[4] = 0;
    asm volatile("fence.mbarrier_init.release.cluster;" ::: "memory");
  }
  __syncthreads();
  if (wg == 2) {
    reg_dec<24>();
    if (tid == 256) {
      int it = 0, qi = 0, vc = 0, vr = -1, j = 0, hc = 0;
      CT(gridDim.x > 20 ? 3 : 6, 0)
      auto load_v = [&]() {
        if (vr < 0) return;
        const int s = (it - 1) & 1;
        mbar_wait(ve + 8 * s, (((it - 1) >> 1) & 1) ^ 1 ^ s);
        mbar_expect(vf + 8 * s, 32768);
        tma_load(sV + s * 32768, &P.v, vc, vr, vf + 8 * s);
        tma_load(sV + s * 32768 + 16384, &P.v, vc + 64, vr, vf + 8 * s);
        vr = -1;
      };
      auto ready = [&](uint32_t m) { uint32_t v; asm volatile("ld.acquire.cta.shared.b32 %0,[%1];" : "=r"(v) : "r"(base + F_INFO + 16) : "memory"); return (v & m) == m; };
      for (it = -1;; it++) {
        if (it >= 0) {
          const int s = it & 1;
          mbar_wait(ke + 8 * s, ((it >> 1) & 1) ^ 1);
          if (j < 0) { mbar_arrive(kf + 8 * s); load_v(); break; }
          mbar_expect(kf + 8 * s, 32768);
          tma_load(sK + s * 32768, &P.k, hc, j * 128, kf + 8 * s);
          tma_load(sK + s * 32768 + 16384, &P.k, hc + 64, j * 128, kf + 8 * s);
        }
        int nc = hc, nr = it >= 0 ? j * 128 : -1;
        if (j-- == 0) {
          int w = atomicInc(&g_sync[S_QUEUE], 511 + P.nctas);
          w = w < 512 ? P.order[w] : -1;
          const uint32_t q = qi & 1, m = w < 0 ? 0x3ffff : (1u | (2u << (fa_qt(w) | 1))) << ((w >> 4) & 1);
          if (!ready(m) || !mbar_test(qe + 8 * q, ((qi >> 1) & 1) ^ 1)) {
            load_v(); it++; vc = nc; vr = nr; load_v(); it--; nr = -1;
            for (int n = 0; !ready(m) && n < WAIT_MAX; n++) __nanosleep(64);
            mbar_wait(qe + 8 * q, ((qi >> 1) & 1) ^ 1);
          }
          asm volatile("fence.proxy.async.global;" ::: "memory");
          info[q] = w;
          if (w < 0) mbar_arrive(qf + 8 * q);
          else {
            j = fa_qt(w); hc = fa_hc(w);
            mbar_expect(qf + 8 * q, 32768);
            tma_load(sQ + q * 32768, &P.q, hc, j * 128, qf + 8 * q);
            tma_load(sQ + q * 32768 + 16384, &P.q, hc + 64, j * 128, qf + 8 * q);
          }
          qi++;
        }
        load_v();
        vc = nc; vr = nr;
      }
      if (atomicInc(&g_sync[S_EXIT], P.nctas - 1) == P.nctas - 1)
        for (int i = 0; i < 18; i++) g_sync[S_PROJ + i] = 0;
    } else if (tid >= 352) {
      const int l = tid - 352;
      for (int n = 0; n < WAIT_MAX; n++) {
        unsigned v = 255;
        if (l < 18) asm volatile("ld.acquire.gpu.global.u32 %0, [%1];" : "=r"(v) : "l"(g_sync + S_PROJ + l) : "memory");
        const uint32_t m = __ballot_sync(~0u, v >= P.nproj[(l >> 1) % 9]);
        __syncwarp();
        if (l == 0) asm volatile("st.release.cta.shared.b32 [%0],%1;" ::"r"(base + F_INFO + 16), "r"(m) : "memory");
        if (m == ~0u) break;
        __nanosleep(300);
      }
    } else if (tid == 288 || tid == 320) {
      const int g = tid == 320;
        for (int n = 0;; n++) {
          mbar_wait(of + 8 * g, n & 1);
          const int v = info[2 + g], w = v & 1023, qt = fa_qt(w), hc = fa_hc(w);
          if (v < 0) break;
          tma_store(&P.o, sO + g * 16384, hc, qt * 128 + g * 64);
          tma_store(&P.o, sO + g * 16384 + 8192, hc + 64, qt * 128 + g * 64);
          bulk_commit();
          bulk_wait_read<0>();
          mbar_arrive(oe + 8 * g);
          bulk_wait<0>();
          signal_after_bulk(S_CTXA + qt);
          if (v & 1024) break;
        }
    }
  } else {
    reg_inc<240>();
    float O[64], S[64];
    uint32_t PA[32], PB[32];
#pragma unroll
    for (int i = 0; i < 32; i++) PA[i] = 0;
#pragma unroll
    for (int i = 0; i < 64; i++) O[i] = 0.f;
    const uint32_t ub = __shfl_sync(~0u, base, 0);
    const int uw = __shfl_sync(~0u, wg, 0);
    FaState T = {0.f, 0.f, 1.f, 1.f, 0, 0, -1, ((ub + 32768 + uw * 8192) >> 4) & 0x3fff, true};
    if (wg == 1) bar_arrive(3, 256);
    for (uint32_t ph = 0;; ph ^= 1) {
      if (fa_step<1>(T, O, S, PA, PB, ub, tid, uw, ph)) break;
      if (fa_step<0>(T, O, S, PB, PA, ub, tid, uw, ph)) break;
    }
    if (wg == 0) bar_sync(3, 256);
  }
}
#define PS 20
#define PT(i)
#define GT(i)
#define YD 200
#define NPF 4
#define NRES 6
#define RP 208
#define PD 3
#define SL 1
#define XI 0
#define NPE 4
#define NUP 2
#define LATE 0
#define VR "............r.r.r.r.r.r............."
#define VP "222222222222111111111111------------"
constexpr int vr_index(int k) { int n = 0; for (int i = 0; i < k; i++) n += VR[i] == 'r'; return n; }
constexpr int VB = vr_index(36);
template <int K> struct VIdx { static constexpr int v = vr_index(K); static constexpr char r = VR[K], p = VP[K]; };
#define LF 0
#define XG 6
#define XW 4
#define WOD 5000
#define KA 26
constexpr int R_WV = 0, R_WO = 73728, R_H = 147456, R_OX = R_H + 46080, R_Q = R_OX + 4096, R_K = R_Q + 5120, R_SX = R_K + 5120, R_P = R_SX + 3200, R_U = R_P + 3200,
              R_BAR = R_H + 73728, R_PROF = R_BAR + 256, R_END = R_PROF + 3072;
constexpr int B_W0 = R_BAR, B_W1 = R_BAR + 8, B_XA = R_BAR + 16, B_XB = R_BAR + 24, B_XF = R_BAR + 32, B_Z0 = R_BAR + 40, B_Z1 = R_BAR + 48, B_R = R_BAR + 56,
              B_SM = R_BAR + 64, B_SX = R_BAR + 72, B_U = R_BAR + 80, B_V = R_BAR + 88, B_O = R_BAR + 96, B_W2 = R_BAR + 160, B_W3 = R_BAR + 168;
static_assert(R_U + 4096 <= R_BAR, "");
enum { N_P1 = 1, N_PM, N_PX, N_SUM, N_O, N_INIT, N_INIT1, N_INIT2, N_WO, N_S };
constexpr int YSLOT = 9 * 16 * 1024;
struct RecParams { CUtensorMap wq, wk, wv, wo, x, ctx; OutMaps o; const bf16 *mem0, *x_raw; bf16* out; };
constexpr int TAIL0 = 12;
constexpr int R_RED = 4 * OSB;

DEVI uint64_t mkdesc(uint32_t a, uint32_t lbo, uint32_t sbo, int sw) { return (uint64_t)((a >> 4) & 0x3fff) | ((uint64_t)(lbo >> 4) << 16) | ((uint64_t)(sbo >> 4) << 32) | ((uint64_t)sw << 62); }
DEVI void wg_rs32(float* d, const uint32_t* a, uint64_t db, int acc) {
  asm volatile("{.reg .pred p; setp.ne.b32 p,%21,0;\n wgmma.mma_async.sync.aligned.m64n32k16.f32.bf16.bf16 {%0,%1,%2,%3,%4,%5,%6,%7,%8,%9,%10,%11,%12,%13,%14,%15},{%16,%17,%18,%19},%20,p,1,1,0;}"
               : F8(d, 0), F8(d, 8) : "r"(a[0]), "r"(a[1]), "r"(a[2]), "r"(a[3]), "l"(db), "r"(acc));
}
DEVI void wg_rs40(float* d, const uint32_t* a, uint64_t db, int acc) {
  asm volatile("{.reg .pred p; setp.ne.b32 p,%25,0;\n wgmma.mma_async.sync.aligned.m64n40k16.f32.bf16.bf16 {%0,%1,%2,%3,%4,%5,%6,%7,%8,%9,%10,%11,%12,%13,%14,%15,%16,%17,%18,%19},{%20,%21,%22,%23},%24,p,1,1,0;}"
               : F8(d, 0), F8(d, 8), "+f"(d[16]), "+f"(d[17]), "+f"(d[18]), "+f"(d[19]) : "r"(a[0]), "r"(a[1]), "r"(a[2]), "r"(a[3]), "l"(db), "r"(acc));
}
template <int TB> DEVI void wg_ss40(float* d, uint64_t da, uint64_t db, int acc) {
  asm volatile("{.reg .pred p; setp.ne.b32 p,%22,0;\n wgmma.mma_async.sync.aligned.m64n40k16.f32.bf16.bf16 {%0,%1,%2,%3,%4,%5,%6,%7,%8,%9,%10,%11,%12,%13,%14,%15,%16,%17,%18,%19},%20,%21,p,1,1,1,%23;}"
               : F8(d, 0), F8(d, 8), "+f"(d[16]), "+f"(d[17]), "+f"(d[18]), "+f"(d[19]) : "l"(da), "l"(db), "r"(acc), "n"(TB));
}
DEVI void mma8(float* d, uint32_t a0, uint32_t a1, uint32_t b0) {
  asm volatile("mma.sync.aligned.m16n8k8.row.col.f32.bf16.bf16.f32 {%0,%1,%2,%3},{%4,%5},{%6},{%0,%1,%2,%3};" : "+f"(d[0]), "+f"(d[1]), "+f"(d[2]), "+f"(d[3]) : "r"(a0), "r"(a1), "r"(b0));
}
DEVI void stsm4t(uint32_t a, uint32_t r0, uint32_t r1, uint32_t r2, uint32_t r3) {
  asm volatile("stmatrix.sync.aligned.m8n8.x4.trans.shared.b16 [%0],{%1,%2,%3,%4};" ::"r"(a), "r"(r0), "r"(r1), "r"(r2), "r"(r3) : "memory");
}
DEVI uint32_t movm(uint32_t a) { uint32_t d; asm volatile("movmatrix.sync.aligned.m8n8.trans.b16 %0,%1;" : "=r"(d) : "r"(a)); return d; }
DEVI void sts1(uint32_t a, uint32_t v) { asm volatile("st.shared.b32 [%0],%1;" ::"r"(a), "r"(v) : "memory"); }
DEVI uint32_t lds1(uint32_t a) { uint32_t v; asm volatile("ld.shared.b32 %0,[%1];" : "=r"(v) : "r"(a) : "memory"); return v; }
DEVI void sta1(uint32_t d, uint32_t a, uint32_t bar) { asm volatile("st.async.weak.shared::cluster.mbarrier::complete_tx::bytes.b32 [%0],%1,[%2];" ::"r"(d), "r"(a), "r"(bar) : "memory"); }
DEVI void sta2(uint32_t d, uint32_t a, uint32_t b, uint32_t bar) { asm volatile("st.async.weak.shared::cluster.mbarrier::complete_tx::bytes.v2.b32 [%0],{%1,%2},[%3];" ::"r"(d), "r"(a), "r"(b), "r"(bar) : "memory"); }
DEVI uint32_t clk32() { uint64_t c; asm volatile("mov.u64 %0,%%clock64;" : "=l"(c)::"memory"); return (uint32_t)c; }
DEVI int opq(int x) { asm volatile("" : "+r"(x)); return x; }
DEVI int pin(int x) { return __shfl_sync(~0u, x, threadIdx.x & 31); }
DEVI uint32_t zero_after(float x) { uint32_t t; asm volatile("{.reg .u32 t; popc.b32 t,%1; shr.u32 %0,t,6;}" : "=r"(t) : "r"(__float_as_uint(x))); return t; }
DEVI void x_load(const RecParams& P, uint32_t sb, int c, int seg) {
  asm volatile("cp.async.bulk.tensor.2d.shared::cluster.global.mbarrier::complete_tx::bytes.multicast::cluster [%0],[%1,{%3,%4}],[%2],%5;"
               ::"r"(sb + R_H + c * 5120 + 1024), "l"(&P.x), "r"(sb + (c < XG ? B_XA : B_XB)), "r"(c * 64), "r"(seg * 32), "h"((uint16_t)0xffff) : "memory");
  if (seg + 2 < NSEG) asm volatile("cp.async.bulk.prefetch.tensor.2d.L2.global [%0,{%1,%2}];" ::"l"(&P.x), "r"(c * 64), "r"(seg * 32 + 64) : "memory");
}
DEVI uint32_t hadd2(uint32_t a, uint32_t b) { uint32_t r; asm("add.rn.bf16x2 %0,%1,%2;" : "=r"(r) : "r"(a), "r"(b)); return r; }
DEVI uint32_t hmax2(uint32_t a, uint32_t b) { uint32_t r; asm("max.bf16x2 %0,%1,%2;" : "=r"(r) : "r"(a), "r"(b)); return r; }
DEVI float rcp(float x) { float y; asm("rcp.approx.ftz.f32 %0,%1;" : "=f"(y) : "f"(x)); return y; }
constexpr float SCL = 0.08838834764831845f * 1.4426950408889634f;

DEVI void y_store(const float* a, uint32_t off, int s) {
  const uint32_t x = movm(pack2(a[0], a[1])), y = movm(pack2(a[2], a[3]));
  const uint32_t tag = ((s >> 1) & 1) ^ 1;
  asm volatile("st.relaxed.gpu.global.b64 [%0],%1;" ::"l"((uint8_t*)g_Y + (s & 1) * YSLOT + off), "l"((uint64_t)((x & ~1u) | tag) | ((uint64_t)y << 32)) : "memory");
}
DEVI void y_load(uint32_t* w, const uint8_t* p) {
#pragma unroll
  for (int i = 0; i < 4; i++) asm volatile("{.reg .b64 t; ld.relaxed.gpu.global.b64 t,[%2]; mov.b64 {%0,%1},t;}" : "=r"(w[2 * i]), "=r"(w[2 * i + 1]) : "l"(p + i * 256) : "memory");
}
DEVI bool y_missing(const uint32_t* w, uint32_t tag) {
  uint32_t r;
  asm volatile("{.reg .b32 a,b; .reg .pred p; lop3.b32 a,%1,%2,%5,0x7e; lop3.b32 b,%3,%4,%5,0x7e; lop3.b32 a,a,b,1,0xa8; setp.ne.u32 p,a,0; vote.sync.any.pred p,p,0xffffffff; selp.u32 %0,1,0,p;}"
               : "=r"(r) : "r"(w[0]), "r"(w[2]), "r"(w[4]), "r"(w[6]), "r"(tag));
  return r;
}
DEVI void y_reload(uint32_t* w, const uint8_t* p, uint32_t tag) {
#pragma unroll
  for (int i = 0; i < 4; i++)
    asm volatile("{.reg .b64 t; .reg .b32 a; .reg .pred q; lop3.b32 a,%0,%3,1,0x28; setp.ne.u32 q,a,0; mov.b64 t,{%0,%1}; @q ld.relaxed.gpu.global.b64 t,[%2]; mov.b64 {%0,%1},t;}"
                 : "+r"(w[2 * i]), "+r"(w[2 * i + 1]) : "l"(p + i * 256), "r"(tag) : "memory");
}
DEVI void y_sum(uint32_t* r, const uint32_t* w, uint32_t sel) {
  float d0[4] = {0, 0, 0, 0}, d1[4] = {0, 0, 0, 0};
  mma16(d0, w[0], w[1], w[2], w[3], sel, sel); mma16(d1, w[4], w[5], w[6], w[7], sel, sel);
  r[0] = pack2(d0[0] + d1[0], d0[1] + d1[1]); r[1] = pack2(d0[2] + d1[2], d0[3] + d1[3]);
}
DEVI void y_send(const uint32_t* r, uint32_t sb, uint32_t dst, uint32_t bar, int lane) {
#pragma unroll
  for (int i = 0; i < 4; i++) { const uint32_t rs = mapa(sb, (lane & 3) * 4 + i); sta2(rs + dst, r[0], r[1], rs + bar); }
}
DEVI void wo_convert(uint32_t sb, int lane) {
  const int g = lane >> 2;
  TL_END(11)
  mbar_wait(sb + B_W3, 0);
  TL_END(9)
#pragma unroll 1
  for (uint32_t a = sb + R_WO + ((threadIdx.x >> 5) & 3) * 2048, i = 0; i < 9; i++, a += 8192) {
    uint32_t r[4][4];
#pragma unroll
    for (int k = 0; k < 4; k++) ldsm4t(r[k], a + k * 512 + ((lane & 7) + (lane >> 4) * 8) * 32 + ((lane >> 3) & 1) * 16);
    __syncwarp();
#pragma unroll
    for (int k = 0; k < 4; k++)
#pragma unroll
      for (int m = 0; m < 4; m++) sts1(a + k * 512 + ((((m & 1) * 2 + (g >> 2)) * 2 + (g & 1)) * 4 + (lane & 3)) * 16 + ((m >> 1) * 2 + ((g >> 1) & 1)) * 4, r[k][m]);
  }
  __syncwarp();
}
template <int NR, int NP, int NE, int UP> DEVI void wo_tile(const uint32_t (*A0)[4], uint32_t sb, int chunk, int cta, int lane, uint32_t yo, int s) {
  uint32_t u[8][4], A[16][4];
  const uint32_t wa = sb + R_WO + chunk * 8192 + lane * 16, ua = sb + R_U + lane * 16;
  float a[4] = {0, 0, 0, 0}, b[4] = {0, 0, 0, 0};
  auto fetch = [&](int i) { if (i < 16 - NR) lds4(A[i], wa + i * 512); };
  auto uload = [&](int i) { if (i < 8) ldsm4t(u[i], ua + i * 512); };
#pragma unroll
  for (int i = 0; i < NE; i++) fetch(i);
  mwait(sb + B_V, s & 1);
  PT(6)
  uload(0); uload(1);
#pragma unroll
  for (int i = NE; i < NP; i++) fetch(i);
#pragma unroll
  for (int i = 0; i < 16; i++) {
    if (i == 4) {
      mwait(sb + B_U, s & 1);
      PT(7)
#pragma unroll
      for (int k = 2; k < 2 + UP; k++) uload(k);
    }
    const uint32_t* f = i >= 16 - NR ? A0[i >= 16 - NR ? i - 16 + NR : 0] : A[i];
    mma16(i & 1 ? b : a, f[0], f[1], f[2], f[3], u[i >> 1][(i & 1) * 2], u[i >> 1][(i & 1) * 2 + 1]);
    fetch(i + NP);
    if (i >= 4 && (i & 1)) uload((i >> 1) + UP);
  }
#pragma unroll
  for (int i = 0; i < 4; i++) a[i] += b[i];
  y_store(a, yo, s);
}
template <bool X> DEVI void softmax8(const uint32_t* h, uint32_t a4, uint32_t a1) {
  uint32_t y[5];
  lds4(y, a4 + R_SX); y[4] = lds1(a1 + R_SX);
#pragma unroll
  for (int j = 0; j < 5; j++) y[j] = hadd2(h[j], y[j]);
  const uint32_t m2 = hmax2(hmax2(hmax2(y[0], y[1]), hmax2(y[2], y[3])), y[4]);
  const float mc = fmaxf(blo(m2), bhi(m2)) * SCL;
  const float m1 = __shfl_xor_sync(~0u, mc, 1), m3 = __shfl_xor_sync(~0u, mc, 2), m4 = __shfl_xor_sync(~0u, mc, 3);
  float e[10];
#pragma unroll
  for (int j = 0; j < 5; j++) { e[2 * j] = ex2(fmaf(blo(y[j]), SCL, -mc)); e[2 * j + 1] = ex2(fmaf(bhi(y[j]), SCL, -mc)); }
  const float c = ex2(mc - fmaxf(fmaxf(mc, m1), fmaxf(m3, m4)));
  const float l = c * ((((e[0] + e[1]) + (e[2] + e[3])) + ((e[4] + e[5]) + (e[6] + e[7]))) + (e[8] + e[9]));
  const float r = c * rcp((l + __shfl_xor_sync(~0u, l, 1)) + (__shfl_xor_sync(~0u, l, 2) + __shfl_xor_sync(~0u, l, 3)));
#pragma unroll
  for (int j = 0; j < 5; j++) y[j] = pack2(e[2 * j] * r, e[2 * j + 1] * r);
  if (!X) sts4(a4 + R_P, y[0], y[1], y[2], y[3]);
  else stsm4(a4 + R_P, y[0], y[1], y[2], y[3]);
  sts1(a1 + R_P, y[4]);
  if (X) fence_async();
}

DEVI void rec_proj(const RecParams& P, const uint32_t sb, const int cta) {
  uint32_t W[36][4], A0[NRES ? NRES : 1][4];
  const int tid = pin(threadIdx.x);
  const uint32_t yo = pin(((threadIdx.x >> 2) * 2 + ((cta >> 1) & 1)) * 1024 + (cta >> 4) * 256 + (cta & 1) * 128 + ((cta >> 2) & 3) * 32 + (threadIdx.x & 3) * 8);
  const int warp = __shfl_sync(~0u, threadIdx.x >> 5, 0), role = warp >> 2;
  const uint32_t qk = sb + R_Q + warp * 1280;
  {
    const int lane = threadIdx.x & 31, w4 = (threadIdx.x >> 5) & 3;
    const uint32_t a = sb + role * R_H + ((lane & 7) + (lane >> 4) * 8) * 128 + (((w4 * 2 + ((lane >> 3) & 1)) ^ (lane & 7)) << 4);
    mbar_wait(sb + B_W0 + role * 8, 0);
    TL_END(8)
#pragma unroll
    for (int k = 0; k < 36; k++) ldsm4t(W[k], a + k * 2048);
    if (LATE == 1) pdl_trigger();
    bar_arrive(N_INIT + role, 256);
    cluster_sync_relaxed();
    if (tid == 0 && (cta & 15) < 9) x_load(P, sb, cta & 15, 0);
#pragma unroll
    for (int i = 0; i < NRES; i++) A0[i][0] = A0[i][1] = A0[i][2] = A0[i][3] = 0;
  }
  for (int s = -1; s < NSEG; s++) {
    if (s >= 0) {
      PT(0)
      {
        const int lane = opq(tid) & 31;
        const uint32_t hb = sb + R_H + (lane & 7) * 128 + (((lane >> 3) ^ (lane & 7)) << 4);
        float a[4] = {0, 0, 0, 0}, b[4] = {0, 0, 0, 0};
        mwait(sb + B_Z0, (s - 1) & 1);
        PT(1) if (role) { GT(0) }
        uint32_t f[18][4];
#pragma unroll
        for (int c = -PD; c < 18; c++) {
          if (c + PD == 8) mwait(sb + B_Z1, (s - 1) & 1);
          if (c + PD < 18) ldsm4(f[c + PD], (hb ^ (((c + PD) & 1) * 64)) + ((c + PD) >> 1) * 5120);
          if (c >= 0) {
            mma16(a, W[2 * c][0], W[2 * c][1], W[2 * c][2], W[2 * c][3], f[c][0], f[c][1]);
            mma16(b, W[2 * c + 1][0], W[2 * c + 1][1], W[2 * c + 1][2], W[2 * c + 1][3], f[c][2], f[c][3]);
          }
        }
        sts1(qk + 512 + lane * 4, pack2(a[0] + b[0], a[1] + b[1]));
        sts1(qk + 1152 + lane * 4, pack2(a[2] + b[2], a[3] + b[3]));
        fence_async();
      }
      PT(2)
      const int lane = opq(tid) & 31;
      if (role) {
        bar_arrive(N_P1, 256);
        if (tid == 128) {
          mbar_expect(sb + B_SM, 640); mbar_expect(sb + B_SX, 2560);
          if (s < NSEG - 1) {
            mbar_expect(sb + B_U, 3072);
            mbar_expect(sb + B_Z0, 4096); mbar_expect(sb + B_Z1, 5120);
            mbar_expect(sb + B_XA, XG * 4096); mbar_expect(sb + B_XB, (9 - XG) * 4096);
          }
        }
        const uint32_t o4 = sb + (warp - 4) * 640 + lane * 16, o1 = sb + (warp - 4) * 640 + 512 + lane * 4;
        uint32_t h[5];
        bar_sync(N_PX, 192);
        lds4(h, o4 + R_P); h[4] = lds1(o1 + R_P);
        mwait(sb + B_SX, s & 1);
        PT(4)
        softmax8<true>(h, o4, o1);
        PT(5)
      } else {
        float S[20];
        const uint64_t da = mkdesc(sb + R_Q, 640, 128, 0), db = mkdesc(sb + R_K, 640, 128, 0);
        const uint32_t rs = mapa(sb, (cta & 15) ^ 1);
        const uint32_t o4 = warp * 1280 + lane * 16, o1 = warp * 1280 + 512 + lane * 4;
        bar_sync(N_P1, 256);
        wg_fence();
#pragma unroll
        for (int k = 0; k < 4; k++) wg_ss40<1>(S, da + k * 80, db + k * 80, k);
        wg_commit();
        bar_arrive(N_S, 256);
        wg_wait<0>();
        PT(3)
        uint32_t h[2][5];
        if (warp == 2) {
#pragma unroll
          for (int j = 0; j < 5; j++) h[0][j] = pack2(S[4 * j], S[4 * j + 1]);
          sta4(rs + R_SX + o4, h[0][0], h[0][1], h[0][2], h[0][3], rs + B_SM); sta1(rs + R_SX + o1, h[0][4], rs + B_SM);
          mwait(sb + B_SM, s & 1);
          PT(4)
          softmax8<false>(h[0], sb + o4, sb + o1);
          bar_arrive(N_PM, 160);
        } else if (warp < 2) {
          const int row = warp * 16 + (lane >> 2) - (lane & 3) * 2;
#pragma unroll
          for (int g = 0; g < 2; g++) {
#pragma unroll
            for (int j = 0; j < 5; j++) h[g][j] = pack2(j < 4 && j * 8 > row + g * 8 ? -INFINITY : S[4 * j + 2 * g], j < 4 && j * 8 + 1 > row + g * 8 ? -INFINITY : S[4 * j + 2 * g + 1]);
            sts4(sb + R_P + o4 + g * 640, h[g][0], h[g][1], h[g][2], h[g][3]); sts1(sb + R_P + o1 + g * 640, h[g][4]);
            sta4(rs + R_SX + o4 + g * 640, h[g][0], h[g][1], h[g][2], h[g][3], rs + B_SX); sta1(rs + R_SX + o1 + g * 640, h[g][4], rs + B_SX);
          }
          bar_arrive(N_PX, 192);
        } else {
          if (s) bar_sync(N_O, 160);
          if (tid == 96) {
            if (s) {
              bulk_wait<0>();
              tma_store(&P.ctx, sb + R_OX, cta * 64, s * 32 - 32); bulk_commit();
              if ((s & 3) == 1 && s > 1) signal_after_bulk(S_CTXB + (s >> 2) - 1);
              bulk_wait_read<0>();
            }
            if (XI && (cta & 15) < XG && s < NSEG - 1) { mbar_wait(sb + B_XF, s & 1); x_load(P, sb, cta & 15, s + 1); }
          }
        }
        __syncwarp();
        PT(5)
      }
      {
        if (s == 0) {
          bar_sync(N_INIT2, 384);
#pragma unroll
          for (int i = 0; i < NRES; i++) lds4(A0[i], sb + R_WO + warp * 8192 + lane * 16 + (16 - NRES + i) * 512);
        }
        if (s == NSEG - 1) break;
        wo_tile<NRES, NPF, NPE, NUP>(A0, sb, warp, cta, lane, yo, s);
        if (role) { GT(1) }
        PT(8)
        bar_sync(N_WO, 384);
      }
    }
    {
      float acc[16];
      const uint64_t db = mkdesc(sb + R_H + 1024, 16, 1024, 1);
      mwait(sb + B_XA, (s + 1) & 1);
      PT(9) if (role) { GT(2) }
      wg_fence();
#pragma unroll
      for (int k = 0; k < (KA < XG * 4 ? KA : XG * 4); k++) wg_rs32(acc, W[k], db + (k >> 2) * 320 + (k & 3) * 2, k);
      wg_commit();
      mwait(sb + B_XB, (s + 1) & 1);
      wg_fence();
#pragma unroll
      for (int k = XG * 4; k < KA; k++) wg_rs32(acc, W[k], db + (k >> 2) * 320 + (k & 3) * 2, 1);
      wg_commit();
      wg_wait<0>();
      PT(10)
      if (KA < 36 || s < 0) bar_sync(N_SUM, 384);
      wg_fence();
#pragma unroll
      for (int k = KA; k < 36; k++) wg_rs32(acc, W[k], db + (k >> 2) * 320 + (k & 3) * 2, 1);
      wg_commit();
      const uint32_t o = qk + (opq(tid) & 31) * 16;
      wg_wait<0>();
      PT(11)
      stsm4(o, pack2(acc[0], acc[1]), pack2(acc[4], acc[5]), pack2(acc[8], acc[9]), pack2(acc[12], acc[13]));
      stsm4(o + 640, pack2(acc[2], acc[3]), pack2(acc[6], acc[7]), pack2(acc[10], acc[11]), pack2(acc[14], acc[15]));
    }
  }
  bar_arrive(N_WO, 384);
  for (int i = 0; i < (warp ? 1 : 2); i++)
    asm volatile("st.relaxed.gpu.global.b64 [%0],%1;" ::"l"((uint8_t*)g_Y + YSLOT + yo + i * 8 * 16384), "l"(0ull) : "memory");
  TL_END(6)
  if (tid == 0) CT(1, 0)
  if (warp == 3) {
    bar_sync(N_O, 160);
    if (tid == 96) { tma_store(&P.ctx, sb + R_OX, cta * 64, SEQ - 32); bulk_commit(); bulk_wait<0>(); CT(2, 0) signal_after_bulk(S_CTXB + 15); CT(2, 1) }
    __syncwarp();
  }
  asm volatile("barrier.cluster.arrive.relaxed.aligned;" ::: "memory");
  float acc[96];
  const int rk = opq(cta) & 15, n = rk / 5, q = rk - n * 5;
  out_consume<4, false>(acc, sb, sb + B_O, rk == 15 ? 0 : q == 4 ? 12 : 13);
  if (tid == 0) CT(1, 1)
  asm volatile("barrier.cluster.wait.aligned;" ::: "memory");
  bar_sync(N_P1, 256);
  {
#pragma unroll
    for (int u = 0; u < 12; u++) {
      const int d = u % 5;
      const float* a = acc + u * 8;
      const uint32_t x = pack2(a[0], a[1]), y = pack2(a[2], a[3]), z = pack2(a[4], a[5]), w = pack2(a[6], a[7]);
      const uint32_t rs = mapa(sb, rk == 15 ? 15 : n * 5 + d);
      if (d == q) sts4(sb + R_RED - 12288 + (u / 5) * 4096 + tid * 16, x, y, z, w);
      else sta4(rs + R_RED + (q < d ? q : q - 1) * 12288 + (u / 5) * 4096 + tid * 16, x, y, z, w, rs + B_R);
    }
    mbar_wait(sb + B_R, 0);
    if (tid == 0) CT(1, 2)
    const int lane = tid & 31;
    const uint32_t st = sb + warp * 1024 + (lane & 15) * 48 + (lane >> 4) * 16, ld = sb + warp * 1024 + (lane >> 1) * 48 + (lane & 1) * 16;
    bf16* out = P.out + (size_t)((TAIL0 + (cta >> 4)) * 128 + warp * 16 + (lane >> 1)) * (2 * DM) + DM + n * 192 + q * 16 + (lane & 1) * 8;
#pragma unroll 1
    for (int i = 0; i < (q < 2 ? 3 : 2); i++) {
      uint32_t v[5][4], r[4];
#pragma unroll
      for (int p = 0; p < 5; p++) lds4(v[p], sb + R_RED + (p - 1) * 12288 + i * 4096 + tid * 16);
#pragma unroll
      for (int j = 0; j < 4; j++)
        r[j] = pack2((blo(v[0][j]) + blo(v[1][j])) + (blo(v[2][j]) + blo(v[3][j])) + blo(v[4][j]), (bhi(v[0][j]) + bhi(v[1][j])) + (bhi(v[2][j]) + bhi(v[3][j])) + bhi(v[4][j]));
      stsm4(st + i * 8192, r[0], r[1], r[2], r[3]);
      __syncwarp();
      lds4(r, ld + i * 8192);
      asm volatile("{.reg .pred p; setp.ne.s32 p,%5,15; @p st.global.v4.b32 [%0],{%1,%2,%3,%4};}" ::"l"(out + i * 80), "r"(r[0]), "r"(r[1]), "r"(r[2]), "r"(r[3]), "r"(rk) : "memory");
    }
  }
}

template <int K> DEVI void v_resident(uint32_t (*F)[4], uint32_t wv) {
  if constexpr (K < 36) { if (VIdx<K>::r == 'r') ldsm4t(F[VIdx<K>::v], wv + K * 2048); v_resident<K + 1>(F, wv); }
}
template <int K> DEVI void v_pass(float* acc, const uint32_t (*F)[4], uint64_t da, uint64_t db, uint32_t xf, uint32_t t, uint32_t nrel) {
  if constexpr (K < 36) {
    wg_fence();
    if (VIdx<K>::r == 'r') wg_rs40(acc, F[VIdx<K>::v], db + (K >> 2) * 320 + (K & 3) * 2, K);
    else wg_ss40<0>(acc, da + K * 128, db + (K >> 2) * 320 + (K & 3) * 2, K);
    wg_commit();
    if constexpr (VIdx<K>::p != '-') wg_wait<VIdx<K>::p - '0'>();
    if (K == XG * 4 - 1 + XW) { wg_wait<XW>(); asm volatile("{.reg .pred p; .reg .b32 a; setp.lt.u32 p,%1,%2; @p mapa.shared::cluster.u32 a,%0,%1; @p mbarrier.arrive.shared::cluster.b64 _,[a];}" ::"r"(xf), "r"(t), "r"(nrel) : "memory"); }
    v_pass<K + 1>(acc, F, da, db, xf, t, nrel);
  }
}
DEVI void rec_aux(const RecParams& P, const uint32_t sb, const int cta) {
  const int tid = pin(threadIdx.x);
  {
    uint4 v[5];
#pragma unroll
    for (int j = 0; j < 5; j++) if (j * 128 + tid - 256 < 576) v[j] = ((const uint4*)P.mem0)[j * 128 + tid - 256];
    bar_sync(N_INIT, 256);
    if (tid == 256) {
      mbar_expect(sb + B_W2, 73728);
#pragma unroll 1
      for (int i = 0; i < 3; i++) tma_load(sb + R_WV + i * 24576, &P.wv, cta * 64, i * 192, sb + B_W2);
    }
    bar_sync(N_INIT1, 256);
#pragma unroll
    for (int j = 0; j < 5; j++) {
      const int i = j * 128 + tid - 256, t = i / 72, c = i - t * 72;
      if (i < 576) sts4(sb + R_H + (c >> 3) * 5120 + t * 128 + (((c & 7) ^ t) << 4), v[j].x, v[j].y, v[j].z, v[j].w);
    }
    fence_async();
    bar_arrive(N_SUM, 384);
    cluster_sync_relaxed();
    TL_END(12)
    wo_convert(sb, threadIdx.x & 31);
    bar_sync(N_O, 128);
    bar_arrive(N_INIT2, 384);
    TL_END(10)
  }
  const int rk = cta & 15, w4 = __shfl_sync(~0u, (threadIdx.x >> 5) & 3, 0);
  const uint32_t yg = pin((((threadIdx.x >> 5) & 3) * 16 + rk) * 1024 + ((threadIdx.x >> 4) & 1) * 128 + (threadIdx.x & 3) * 32 + ((threadIdx.x >> 2) & 3) * 8);
  uint32_t F[VB][4];
  mbar_wait(sb + B_W2, 0);
  TL_END(7)
  if (LATE == 2) pdl_trigger();
  v_resident<0>(F, sb + R_WV + ((tid & 7) + ((tid >> 4) & 1) * 8) * 128 + (((w4 * 2 + ((tid >> 3) & 1)) ^ (tid & 7)) << 4));
  for (int s = 0; s < NSEG; s++) {
    const bool last = s == NSEG - 1;
    uint32_t va[12], p[5];
    int lane = opq(tid) & 31;
    {
      float acc[20];
      const uint64_t da = mkdesc(sb + R_WV, 0, 1024, 1), db = mkdesc(sb + R_H, 16, 1024, 1);
      PT(0)
      bar_sync(N_S, 256);
      asm volatile("fence.proxy.async::generic.acquire.sync_restrict::shared::cluster.cluster;" ::: "memory");
      v_pass<0>(acc, F, da, db, sb + B_XF, tid - 256, last ? 0 : XG);
      PT(13)
      bar_sync(N_PM, 160);
      lds4(p, sb + R_P + 2560 + lane * 16); p[4] = lds1(sb + R_P + 3072 + lane * 4);
      wg_wait<0>();
      PT(1)
#pragma unroll
      for (int i = 0; i < 10; i++) va[i < 2 ? i + 8 : i - 2] = pack2(acc[2 * i], acc[2 * i + 1]);
      va[10] = va[11] = 0;
    }
    lane = opq(tid) & 31;
    if (!last) {
      const uint32_t uo = R_U + w4 * 256 + lane * 4;
      float a[4] = {0, 0, 0, 0}, b[4] = {0, 0, 0, 0}, c[4] = {0, 0, 0, 0};
      mma16(a, va[0], va[1], va[2], va[3], p[0], p[1]); mma16(b, va[4], va[5], va[6], va[7], p[2], p[3]); mma8(c, va[8], va[9], p[4]);
      const uint32_t u0 = pack2(a[0] + b[0] + c[0], a[1] + b[1] + c[1]), u1 = pack2(a[2] + b[2] + c[2], a[3] + b[3] + c[3]);
      sts1(sb + uo, u0); sts1(sb + uo + 128, u1);
      __syncwarp();
      if (lane == 0) mbar_arrive(sb + B_V);
#pragma unroll
      for (int q = 1; q < 4; q++) { const uint32_t rs = mapa(sb, rk ^ q); sta1(rs + uo + q * 1024, u0, rs + B_U); sta1(rs + uo + q * 1024 + 128, u1, rs + B_U); }
      asm volatile("{.reg .pred p; .reg .b32 a; setp.lt.u32 p,%1,%3; @p mapa.shared::cluster.u32 a,%0,%2; @p mbarrier.arrive.shared::cluster.b64 _,[a];}" ::"r"(sb + B_XF), "r"(tid - 256 - XG), "r"(tid - 256), "r"(last ? 0 : 9 - XG) : "memory");
      PT(4)
      if (w4 == 3) {
        wo_tile<0, 4, 4, 2>(nullptr, sb, 8, cta, lane, ((64 + (lane >> 2)) * 2 + ((cta >> 1) & 1)) * 1024 + (cta >> 4) * 256 + (cta & 1) * 128 + ((cta >> 2) & 3) * 32 + (lane & 3) * 8, s);
      } else if (tid == 288 && rk < 9 && (!XI || rk >= XG) && !last) { mbar_wait(sb + B_XF, s & 1); x_load(P, sb, rk, s + 1); }
      PT(2)
    }
    lane = opq(tid) & 31;
    const uint8_t* y = (const uint8_t*)g_Y + (s & 1) * YSLOT + yg;
    uint32_t w0[8], w1[8], w2[8], ox[8];
    {
      float o[16];
      const uint64_t dp = mkdesc(sb + R_P, 128, 640, 0);
      bar_sync(N_WO, 384);
      wg_fence();
      wg_rs32(o, va, dp, 0); wg_rs32(o, va + 4, dp + 16, 1); wg_rs32(o, va + 8, mkdesc(sb + R_P + 512, 0, 640, 0), 1);
      wg_commit();
      const uint32_t tu = clk32();
      wg_wait<0>();
      PT(3)
#pragma unroll
      for (int i = 0; i < 8; i++) ox[i] = pack2(o[2 * i], o[2 * i + 1]);
      while (clk32() - tu < (uint32_t)YD) {}
      y_load(w0, y); y_load(w1, y + 4 * 16384);
      if (w4 == 0) y_load(w2, y + 8 * 16384);
      else {
#pragma unroll
        for (int i = 0; i < 8; i++) w2[i] = ((s >> 1) & 1) ^ 1;
      }
      PT(5)
    }
    if (!last) {
      const uint32_t dst = R_H + w4 * 5120 + (rk >> 1) * 128 + ((((rk & 1) * 4 + (lane >> 3)) ^ (rk >> 1)) << 4) + (lane & 4) * 2;
      const uint32_t tag = ((s >> 1) & 1) ^ 1, sel = (lane & 4) ? 0x3f800000u : 0x3f80u;
      uint32_t r0[2], r1[2], r2[2];
#pragma unroll 1
      for (int it = 0; (y_missing(w0, tag) | y_missing(w1, tag) | y_missing(w2, tag)) && it < (1 << 20); it++) {
        y_reload(w0, y, tag); y_reload(w1, y + 4 * 16384, tag); y_reload(w2, y + 8 * 16384, tag);
      }
      PT(7) GT(3)
      y_sum(r0, w0, sel); y_sum(r1, w1, sel); y_sum(r2, w2, sel);
      if (KA < 36 && SL == 0) bar_arrive(N_SUM + zero_after(__uint_as_float(r2[0])), 384);
      y_send(r0, sb, dst, B_Z0, lane);
      if (KA < 36 && SL == 1) bar_arrive(N_SUM, 384);
      y_send(r1, sb, dst + 4 * 5120, B_Z1, lane);
      if (w4 == 0) y_send(r2, sb, dst + 8 * 5120, B_Z1, lane);
      if (SL == 2) bar_arrive(N_SUM, 384);
      PT(9) GT(4)
    }
#pragma unroll
    for (int h = 0; h < 2; h++) stsm4t(sb + R_OX + lane * 128 + (((w4 * 2 + h) ^ (lane & 7)) << 4), ox[h], ox[2 + h], ox[4 + h], ox[6 + h]);
    if (last) break;
    fence_async();
    bar_arrive(N_O, 160);
    PT(11)
  }
  fence_async();
  bar_arrive(N_O, 160);
  asm volatile("barrier.cluster.arrive.relaxed.aligned;" ::: "memory");
  if (tid == 256) {
    const int m = TAIL0 + (cta >> 4), n = rk / 5, q = rk - n * 5;
    mbar_expect(sb + B_R, rk == 15 ? 9 * 4096 : q < 2 ? 12 * 4096 : 8 * 4096);
    if (rk < 15) out_produce<4, false>(P.o, sb, sb + B_O, m, n, q * 13, q == 4 ? 12 : 13, S_CTXB + m);
  }
  __syncwarp();
  asm volatile("barrier.cluster.wait.aligned;" ::: "memory");
}

__global__ void __launch_bounds__(384, 1) rec_kernel(const __grid_constant__ RecParams P) {
  extern __shared__ __align__(1024) uint8_t smem_raw[];
  const uint32_t sb = s2u(smem_raw);
  const int tid = threadIdx.x, cta = blockIdx.x;
  TL_START(1)
  if (!LATE) pdl_trigger();
  if (tid == 0) {
    for (int i = 0; i < 22; i++) mbar_init(sb + R_BAR + 8 * i, 8 * i == B_XF - R_BAR ? 16 : 8 * i == B_V - R_BAR ? 4 : i >= 16 && i < 20 ? 2 : 1);
    asm volatile("fence.mbarrier_init.release.cluster;" ::: "memory");
    asm volatile("cp.async.bulk.prefetch.L2.global [%0],%1;" ::"l"(P.x_raw + cta * DM), "r"(DM * 2) : "memory");
    mbar_expect(sb + B_W0, 73728); mbar_expect(sb + B_W1, 73728); mbar_expect(sb + B_W3, 73728);
#pragma unroll 1
    for (int i = 0; i < 3; i++) { tma_load(sb + R_WV + i * 24576, &P.wq, cta * 64, i * 192, sb + B_W0); tma_load(sb + R_H + i * 24576, &P.wk, cta * 64, i * 192, sb + B_W1); }
    mbar_expect(sb + B_XA, XG * 4096); mbar_expect(sb + B_XB, (9 - XG) * 4096);
  }
  __syncthreads();
  if (tid == 288) {
    if (WOD) { const uint32_t t0 = clk32(); while (clk32() - t0 < (uint32_t)WOD) {} }
#pragma unroll 1
    for (int i = 0; i < 36; i++) tma_load(sb + R_WO + i * 2048, &P.wo, (i >> 2) * 64 + (cta & 3) * 16, (cta ^ (i & 3)) * 64, sb + B_W3);
    for (int i = 0; i < 3; i++) asm volatile("cp.async.bulk.prefetch.tensor.2d.L2.global [%0,{%1,%2}];" ::"l"(&P.wv), "r"(cta * 64), "r"(i * 192) : "memory");
  }
  __syncwarp();
  if (tid >= 256) { reg_dec<504 - 2 * RP>(); rec_aux(P, sb, cta); }
  else { reg_inc<RP>(); rec_proj(P, sb, cta); }
  TL_END(1)
  cluster_sync_relaxed();
}
typedef CUresult (*EncFn)(CUtensorMap*, CUtensorMapDataType, cuuint32_t, void*, const cuuint64_t*, const cuuint64_t*, const cuuint32_t*, const cuuint32_t*,
                          CUtensorMapInterleave, CUtensorMapSwizzle, CUtensorMapL2promotion, CUtensorMapFloatOOBfill);
static EncFn g_enc;
static CUtensorMap mk(const void* p, uint64_t cols, uint64_t rows, uint64_t pitch_elems, uint32_t box_rows, uint32_t box_cols = 64) {
  CUtensorMap m;
  cuuint64_t dim[2] = {cols, rows}, str[1] = {pitch_elems * 2};
  cuuint32_t box[2] = {box_cols, box_rows}, es[2] = {1, 1};
  g_enc(&m, CU_TENSOR_MAP_DATA_TYPE_BFLOAT16, 2, (void*)p, dim, str, box, es, CU_TENSOR_MAP_INTERLEAVE_NONE, box_cols == 64 ? CU_TENSOR_MAP_SWIZZLE_128B : CU_TENSOR_MAP_SWIZZLE_NONE,
        CU_TENSOR_MAP_L2_PROMOTION_L2_256B, CU_TENSOR_MAP_FLOAT_OOB_FILL_NONE);
  return m;
}
template <class T> static void* sym(T& s) { void* p; cudaGetSymbolAddress(&p, s); return p; }

#define FHC 22
#define FSL 4
#define NOE 6
#define OMC true
template <class K, class A> static void launch(K k, int grid, int smem, int cluster, bool pdl, const A& arg) {
  cudaLaunchConfig_t c = {};
  cudaLaunchAttribute at[2];
  int n = 0;
  if (cluster > 1) { at[n].id = cudaLaunchAttributeClusterDimension; at[n].val.clusterDim.x = cluster; at[n].val.clusterDim.y = at[n].val.clusterDim.z = 1; n++; }
  if (pdl) { at[n].id = cudaLaunchAttributeProgrammaticStreamSerialization; at[n].val.programmaticStreamSerializationAllowed = 1; n++; }
  c.gridDim = grid; c.blockDim = 384; c.dynamicSmemBytes = smem; c.stream = cudaStreamPerThread; c.attrs = at; c.numAttrs = n;
  cudaLaunchKernelEx(&c, k, arg);
}

extern "C" void kernel_launch(void* const* d_in, const int* in_sizes, int n_in, void* d_out, int out_size) {
  static int nb;
  if (!g_enc) {
    cudaDriverEntryPointQueryResult qr;
    cudaGetDriverEntryPoint("cuTensorMapEncodeTiled", (void**)&g_enc, cudaEnableDefault, &qr);
    cudaDeviceGetAttribute(&nb, cudaDevAttrMultiProcessorCount, 0);
    nb = nb - 64 < 16 ? 16 : nb - 64 > 128 ? 128 : (nb - 64) & ~1;
    cudaFuncSetAttribute(proj_kernel, cudaFuncAttributeMaxDynamicSharedMemorySize, SM_P);
    cudaFuncSetAttribute(out_kernel<false>, cudaFuncAttributeMaxDynamicSharedMemorySize, SM_O);
    cudaFuncSetAttribute(out_kernel<true>, cudaFuncAttributeMaxDynamicSharedMemorySize, SM_O);
    cudaFuncSetAttribute(fa_kernel, cudaFuncAttributeMaxDynamicSharedMemorySize, SM_F);
    cudaFuncSetAttribute(rec_kernel, cudaFuncAttributeMaxDynamicSharedMemorySize, R_END);
    cudaFuncSetAttribute(rec_kernel, cudaFuncAttributeNonPortableClusterSizeAllowed, 1);
  }
  const bf16 *Ax = (const bf16*)d_in[0], *Ac = (const bf16*)d_in[1], *Awq = (const bf16*)d_in[2], *Awk = (const bf16*)d_in[3], *Awv = (const bf16*)d_in[4],
             *Awo = (const bf16*)d_in[5], *Bx = (const bf16*)d_in[6], *Bm = (const bf16*)d_in[7], *Bwq = (const bf16*)d_in[8], *Bwk = (const bf16*)d_in[9],
             *Bwv = (const bf16*)d_in[10], *Bwo = (const bf16*)d_in[11];
  bf16* out = (bf16*)d_out;
  ProjParams p;
  p.a[0] = mk(Ac, 512, SEQ, 512, 128); p.a[1] = mk(Ax, DM, SEQ, DM, 128);
  p.w[0] = mk(Awk, HD, 512, HD, 64); p.w[1] = mk(Awv, HD, 512, HD, 64); p.w[2] = mk(Awq, HD, DM, HD, 64);
  p.c[0] = mk(sym(g_kA), HD, SEQ, HD, 64); p.c[1] = mk(sym(g_vA), HD, SEQ, HD, 64); p.c[2] = mk(sym(g_qA), HD, SEQ, HD, 64);
  {
    int parts[16];
    for (int i = 0; i < 16; i++) parts[i] = 1;
    for (int e = 0; e < nb / 2 - 16; e++) parts[e % 24 < 16 ? e % 8 : 15 - (e % 24 - 16)]++;
    p.nitems = 0;
    for (int i = 15; i >= 0; i--)
      for (int j = 0, nc = i < 8 ? 32 : 16, a = parts[i]; j < a; j++) {
        ProjItem& I = p.item[p.nitems++];
        I.pa = i >> 3; I.m = i & 7;
        I.c0[0] = j * nc / a; I.n[0] = (j + 1) * nc / a - I.c0[0];
        I.c0[1] = (j * nc + a - 1) / a; I.n[1] = ((j + 1) * nc + a - 1) / a - I.c0[1];
      }
  }
  OutParams o;
  for (int i = 0; i < 2; i++) {
    o.p[i].a = mk(i ? sym(g_ctxB) : sym(g_qA), HD, SEQ, HD, 128); o.p[i].b = mk(i ? Bwo : Awo, DM, HD, DM, 64); o.p[i].bh = mk(i ? Bwo : Awo, DM, HD, DM, 32);
    o.c[i] = mk(out + i * DM, DM, SEQ, 2 * DM, 64);
  }
  FaParams f;
  f.q = mk(sym(g_qA), HD, SEQ, HD, 128); f.k = mk(sym(g_kA), HD, SEQ, HD, 128); f.v = mk(sym(g_vA), HD, SEQ, HD, 128); f.o = mk(sym(g_qA), HD, SEQ, HD, 64);
  f.nctas = nb;
  for (int i = 0; i < 9; i++) f.nproj[i] = 0;
  for (int i = 0; i < p.nitems; i++) f.nproj[p.item[i].pa * (p.item[i].m + 1)] += 4;
  for (int key = -30, n = 0; n < 512; key++)
    for (int h = 0; h < 32; h++)
      for (int qt = 0; qt < 16; qt++)
        if ((h < FHC ? h : FHC) * FSL - qt * 2 == key) f.order[n++] = qt * 32 + h;
  RecParams r;
  r.wq = mk(Bwq, HD, DM, HD, 192); r.wk = mk(Bwk, HD, DM, HD, 192); r.wv = mk(Bwv, HD, DM, HD, 192); r.wo = mk(Bwo, DM, HD, DM, 64, 16);
  r.x_raw = Bx;
  r.x = mk(Bx, DM, SEQ, DM, 32); r.ctx = mk(sym(g_ctxB), HD, SEQ, HD, 32); r.mem0 = Bm; r.o = o.p[1]; r.out = out;

  launch(rec_kernel, 64, R_END, 16, false, r);
  launch(proj_kernel, nb, SM_P, 2, true, p);
  launch(fa_kernel, nb - NOE * 3, SM_F, 1, true, f);
  o.m0 = 0; o.nb = NOE * 3; o.id = 4;
  launch(out_kernel<false>, o.nb, SM_O, 1, true, o);
  launch(fa_kernel, NOE * 3, SM_F, 1, true, f);
  o.m0 = NOE; o.nb = (TAIL0 - NOE) * 3; o.id = 5;
  launch(out_kernel<OMC>, o.nb + 48, SM_O, OMC ? 2 : 1, true, o);
}
```

```cpp
#include <cuda_runtime.h>
#include <cuda_bf16.h>
#include <cuda.h>
#include <stdint.h>

typedef __nv_bfloat16 bf16;
#define DEVI __device__ __forceinline__
#define WAIT_FAIL(code) break
#define WAIT_MAX (1 << 22)

constexpr int SEQ = 2048, HD = 4096, DM = 576, NSEG = 64;

__device__ __align__(1024) bf16 g_qA[SEQ * HD], g_kA[SEQ * HD], g_vA[SEQ * HD];
__device__ __align__(1024) bf16 g_ctxB[SEQ * HD];
__device__ __align__(1024) uint4 g_Y[2 * 9 * 16 * 64];
enum { S_QUEUE = 0, S_EXIT = 1, S_PROJ = 32, S_CTXA = 64, S_CTXB = 96 };
__device__ unsigned g_sync[128];
#define LT(i)
#define CT(k, i) {}
#define TL_START(i)
#define TL_END(i)

DEVI uint32_t s2u(const void* p) { return (uint32_t)__cvta_generic_to_shared(p); }
DEVI void mbar_init(uint32_t b, uint32_t c) { asm volatile("mbarrier.init.shared::cta.b64 [%0],%1;" ::"r"(b), "r"(c)); }
DEVI void mbar_expect(uint32_t b, uint32_t n) { asm volatile("mbarrier.arrive.expect_tx.shared::cta.b64 _,[%0],%1;" ::"r"(b), "r"(n) : "memory"); }
DEVI void mbar_arrive(uint32_t b) { asm volatile("mbarrier.arrive.shared::cta.b64 _,[%0];" ::"r"(b) : "memory"); }
DEVI void mbar_wait(uint32_t b, uint32_t ph) {
  uint32_t ok; int it = 0;
  do {
    asm volatile("{.reg .pred p; mbarrier.try_wait.parity.shared::cta.b64 p,[%1],%2; selp.u32 %0,1,0,p;}" : "=r"(ok) : "r"(b), "r"(ph) : "memory");
    if (!ok && ++it > WAIT_MAX) WAIT_FAIL(b & 0xffffff);
  } while (!ok);
}
DEVI bool mbar_try(uint32_t b, uint32_t ph) {
  uint32_t ok;
  asm volatile("{.reg .pred p; mbarrier.try_wait.parity.shared::cta.b64 p,[%1],%2; selp.u32 %0,1,0,p;}" : "=r"(ok) : "r"(b), "r"(ph) : "memory");
  return ok;
}
DEVI bool mbar_test(uint32_t b, uint32_t ph) {
  uint32_t ok;
  asm volatile("{.reg .pred p; mbarrier.test_wait.parity.shared::cta.b64 p,[%1],%2; selp.u32 %0,1,0,p;}" : "=r"(ok) : "r"(b), "r"(ph) : "memory");
  return ok;
}
DEVI void mwait(uint32_t b, uint32_t ph) { if (__builtin_expect(!mbar_try(b, ph), 0)) mbar_wait(b, ph); }
DEVI void tma_load(uint32_t dst, const CUtensorMap* tm, int c0, int c1, uint32_t bar) {
  asm volatile("cp.async.bulk.tensor.2d.shared::cluster.global.mbarrier::complete_tx::bytes [%0],[%1,{%3,%4}],[%2];" ::"r"(dst), "l"(tm), "r"(bar), "r"(c0), "r"(c1) : "memory");
}
DEVI void tma_store(const CUtensorMap* tm, uint32_t src, int c0, int c1) {
  asm volatile("cp.async.bulk.tensor.2d.global.shared::cta.bulk_group [%0,{%2,%3}],[%1];" ::"l"(tm), "r"(src), "r"(c0), "r"(c1) : "memory");
}
DEVI void bulk_commit() { asm volatile("cp.async.bulk.commit_group;" ::: "memory"); }
template <int N> DEVI void bulk_wait_read() { asm volatile("cp.async.bulk.wait_group.read %0;" ::"n"(N) : "memory"); }
template <int N> DEVI void bulk_wait() { asm volatile("cp.async.bulk.wait_group %0;" ::"n"(N) : "memory"); }
DEVI void fence_async() { asm volatile("fence.proxy.async.shared::cta;" ::: "memory"); }
DEVI void bar_sync(int id, int n) { asm volatile("bar.sync %0,%1;" ::"r"(id), "r"(n) : "memory"); }
DEVI void bar_arrive(int id, int n) { asm volatile("bar.arrive %0,%1;" ::"r"(id), "r"(n) : "memory"); }
template <int R> DEVI void reg_inc() { asm volatile("setmaxnreg.inc.sync.aligned.u32 %0;" ::"n"(R)); }
template <int R> DEVI void reg_dec() { asm volatile("setmaxnreg.dec.sync.aligned.u32 %0;" ::"n"(R)); }
DEVI void wg_fence() { asm volatile("wgmma.fence.sync.aligned;" ::: "memory"); }
DEVI void wg_commit() { asm volatile("wgmma.commit_group.sync.aligned;" ::: "memory"); }
template <int N> DEVI void wg_wait() { asm volatile("wgmma.wait_group.sync.aligned %0;" ::"n"(N) : "memory"); }
DEVI uint64_t desc_k(uint32_t a) { return (uint64_t)((a >> 4) & 0x3fff) | (1ull << 16) | (64ull << 32) | (1ull << 62); }
DEVI uint64_t desc_mn(uint32_t a, uint32_t lbo) { return (uint64_t)((a >> 4) & 0x3fff) | ((uint64_t)(lbo >> 4) << 16) | (64ull << 32) | (1ull << 62); }
DEVI uint32_t pack2(float lo, float hi) { uint32_t r; asm("cvt.rn.bf16x2.f32 %0,%1,%2;" : "=r"(r) : "f"(hi), "f"(lo)); return r; }
DEVI float ex2(float x) { float y; asm("ex2.approx.ftz.f32 %0,%1;" : "=f"(y) : "f"(x)); return y; }
DEVI void stsm4(uint32_t a, uint32_t r0, uint32_t r1, uint32_t r2, uint32_t r3) {
  asm volatile("stmatrix.sync.aligned.m8n8.x4.shared.b16 [%0],{%1,%2,%3,%4};" ::"r"(a), "r"(r0), "r"(r1), "r"(r2), "r"(r3) : "memory");
}
DEVI void ldsm4(uint32_t* r, uint32_t a) {
  asm volatile("ldmatrix.sync.aligned.m8n8.x4.shared.b16 {%0,%1,%2,%3},[%4];" : "=r"(r[0]), "=r"(r[1]), "=r"(r[2]), "=r"(r[3]) : "r"(a) : "memory");
}
DEVI void ldsm4t(uint32_t* r, uint32_t a) {
  asm volatile("ldmatrix.sync.aligned.m8n8.x4.trans.shared.b16 {%0,%1,%2,%3},[%4];" : "=r"(r[0]), "=r"(r[1]), "=r"(r[2]), "=r"(r[3]) : "r"(a) : "memory");
}
DEVI void mma16(float* d, uint32_t a0, uint32_t a1, uint32_t a2, uint32_t a3, uint32_t b0, uint32_t b1) {
  asm volatile("mma.sync.aligned.m16n8k16.row.col.f32.bf16.bf16.f32 {%0,%1,%2,%3},{%4,%5,%6,%7},{%8,%9},{%0,%1,%2,%3};"
               : "+f"(d[0]), "+f"(d[1]), "+f"(d[2]), "+f"(d[3]) : "r"(a0), "r"(a1), "r"(a2), "r"(a3), "r"(b0), "r"(b1));
}

DEVI void pdl_trigger() { asm volatile("griddepcontrol.launch_dependents;" ::: "memory"); }
DEVI void signal_after_bulk(int f) {
  asm volatile("fence.proxy.async.global;" ::: "memory");
  asm volatile("red.release.gpu.global.add.u32 [%0], 1;" ::"l"(g_sync + f) : "memory");
}
DEVI void flag_wait(int f, unsigned n, unsigned waiters) {
  for (int it = 0;; it++) {
    if (it > WAIT_MAX) WAIT_FAIL(f);
    unsigned v; asm volatile("ld.acquire.gpu.global.u32 %0, [%1];" : "=r"(v) : "l"(g_sync + f) : "memory");
    if (v >= n) break;
    __nanosleep(64);
  }
  if (waiters) asm volatile("red.relaxed.gpu.global.inc.u32 [%0], %1;" ::"l"(g_sync + f), "r"(n + waiters - 1) : "memory");
  asm volatile("fence.proxy.async.global;" ::: "memory");
}
DEVI uint32_t mapa(uint32_t a, uint32_t r) { uint32_t o; asm("mapa.shared::cluster.u32 %0,%1,%2;" : "=r"(o) : "r"(a), "r"(r)); return o; }
DEVI void tma_load_mc(uint32_t dst, const CUtensorMap* tm, int c0, int c1, uint32_t bar, uint16_t mask) {
  asm volatile("cp.async.bulk.tensor.2d.shared::cluster.global.mbarrier::complete_tx::bytes.multicast::cluster [%0],[%1,{%3,%4}],[%2],%5;" ::"r"(dst), "l"(tm), "r"(bar), "r"(c0), "r"(c1), "h"(mask) : "memory");
}
DEVI void arrive_pair(uint32_t b) { if ((threadIdx.x & 127) < 2) asm volatile("mbarrier.arrive.shared::cluster.b64 _,[%0];" ::"r"(mapa(b, threadIdx.x & 1)) : "memory"); }
DEVI void cluster_sync_relaxed() { asm volatile("barrier.cluster.arrive.relaxed.aligned; barrier.cluster.wait.aligned;" ::: "memory"); }
DEVI void cluster_sync() { asm volatile("barrier.cluster.arrive.aligned; barrier.cluster.wait.aligned;" ::: "memory"); }
DEVI void sts4(uint32_t a, uint32_t x, uint32_t y, uint32_t z, uint32_t w) { asm volatile("st.shared.v4.b32 [%0],{%1,%2,%3,%4};" ::"r"(a), "r"(x), "r"(y), "r"(z), "r"(w) : "memory"); }
DEVI void lds4(uint32_t* r, uint32_t a) { asm volatile("ld.shared.v4.b32 {%0,%1,%2,%3},[%4];" : "=r"(r[0]), "=r"(r[1]), "=r"(r[2]), "=r"(r[3]) : "r"(a) : "memory"); }
DEVI void sta4(uint32_t d, uint32_t a, uint32_t b, uint32_t c, uint32_t e, uint32_t bar) {
  asm volatile("st.async.weak.shared::cluster.mbarrier::complete_tx::bytes.v4.b32 [%0],{%1,%2,%3,%4},[%5];" ::"r"(d), "r"(a), "r"(b), "r"(c), "r"(e), "r"(bar) : "memory");
}
DEVI float blo(uint32_t u) { return __uint_as_float(u << 16); }
DEVI float bhi(uint32_t u) { return __uint_as_float(u & 0xffff0000u); }

#define F8(a, o) "+f"(a[o]), "+f"(a[o + 1]), "+f"(a[o + 2]), "+f"(a[o + 3]), "+f"(a[o + 4]), "+f"(a[o + 5]), "+f"(a[o + 6]), "+f"(a[o + 7])
#define F32(a, o) F8(a, o), F8(a, o + 8), F8(a, o + 16), F8(a, o + 24)
template<int TB> DEVI void wg_ss128(float* d, uint64_t da, uint64_t db, int acc){
 asm volatile("{.reg .pred p; setp.ne.b32 p,%66,0;\n wgmma.mma_async.sync.aligned.m64n128k16.f32.bf16.bf16 {%0,%1,%2,%3,%4,%5,%6,%7,%8,%9,%10,%11,%12,%13,%14,%15,%16,%17,%18,%19,%20,%21,%22,%23,%24,%25,%26,%27,%28,%29,%30,%31,%32,%33,%34,%35,%36,%37,%38,%39,%40,%41,%42,%43,%44,%45,%46,%47,%48,%49,%50,%51,%52,%53,%54,%55,%56,%57,%58,%59,%60,%61,%62,%63},%64,%65,p,1,1,0,%67;}"
 : F32(d,0),F32(d,32) : "l"(da),"l"(db),"r"(acc),"n"(TB));}
template<int TB> DEVI void wg_ss192(float* d, uint64_t da, uint64_t db, int acc){
 asm volatile("{.reg .pred p; setp.ne.b32 p,%98,0;\n wgmma.mma_async.sync.aligned.m64n192k16.f32.bf16.bf16 {%0,%1,%2,%3,%4,%5,%6,%7,%8,%9,%10,%11,%12,%13,%14,%15,%16,%17,%18,%19,%20,%21,%22,%23,%24,%25,%26,%27,%28,%29,%30,%31,%32,%33,%34,%35,%36,%37,%38,%39,%40,%41,%42,%43,%44,%45,%46,%47,%48,%49,%50,%51,%52,%53,%54,%55,%56,%57,%58,%59,%60,%61,%62,%63,%64,%65,%66,%67,%68,%69,%70,%71,%72,%73,%74,%75,%76,%77,%78,%79,%80,%81,%82,%83,%84,%85,%86,%87,%88,%89,%90,%91,%92,%93,%94,%95},%96,%97,p,1,1,0,%99;}"
 : F32(d,0),F32(d,32),F32(d,64) : "l"(da),"l"(db),"r"(acc),"n"(TB));}
template<int TB> DEVI void wg_rs128(float* d, const uint32_t* a, uint64_t db, int acc){
 asm volatile("{.reg .pred p; setp.ne.b32 p,%69,0;\n wgmma.mma_async.sync.aligned.m64n128k16.f32.bf16.bf16 {%0,%1,%2,%3,%4,%5,%6,%7,%8,%9,%10,%11,%12,%13,%14,%15,%16,%17,%18,%19,%20,%21,%22,%23,%24,%25,%26,%27,%28,%29,%30,%31,%32,%33,%34,%35,%36,%37,%38,%39,%40,%41,%42,%43,%44,%45,%46,%47,%48,%49,%50,%51,%52,%53,%54,%55,%56,%57,%58,%59,%60,%61,%62,%63},{%64,%65,%66,%67},%68,p,1,1,%70;}"
 : F32(d,0),F32(d,32) : "r"(a[0]),"r"(a[1]),"r"(a[2]),"r"(a[3]),"l"(db),"r"(acc),"n"(TB));}
struct ProjItem { uint8_t pa, m, c0[2], n[2]; };
struct ProjParams { CUtensorMap a[2], w[3], c[3]; ProjItem item[64]; int nitems; };
#define PWD 1
constexpr int PST = 12, SM_P = PST * 16384 + 32768 + 256;
DEVI void proj_decode(const ProjItem& I, int t, int& pw, int& n) {
  const int g = t >= I.n[0], c = g ? I.c0[1] + t - I.n[0] : I.c0[0] + t;
  pw = I.pa ? 2 : c >> 4; n = (c & 15) + g * 16;
}
__global__ void __launch_bounds__(384, 1) proj_kernel(const __grid_constant__ ProjParams P) {
  extern __shared__ __align__(1024) uint8_t smem_raw[];
  const uint32_t base = __shfl_sync(~0u, s2u(smem_raw), 0), stg = base + PST * 16384, full = stg + 32768, empty = full + 8 * PST, of = empty + 8 * PST, oe = of + 16;
  const int tid = threadIdx.x, wg = __shfl_sync(~0u, tid >> 7, 0);
  TL_START(2)
  pdl_trigger();
  if (tid == 0) {
    for (int i = 0; i < PST; i++) { mbar_init(full + 8 * i, 1); mbar_init(empty + 8 * i, 4); }
    for (int i = 0; i < 2; i++) { mbar_init(of + 8 * i, 4); mbar_init(oe + 8 * i, 1); }
    asm volatile("fence.mbarrier_init.release.cluster;" ::: "memory");
  }
  cluster_sync_relaxed();
  if (wg == 2) {
    reg_dec<24>();
    const int r = blockIdx.x & 1;
    if (tid == 256) {
      int s = 0, ph = 1;
      for (int it = blockIdx.x >> 1; it < P.nitems; it += gridDim.x >> 1) {
        const ProjItem& I = P.item[it];
        const int nk = 8 + I.pa;
        for (int t = -1; t < I.n[0] + I.n[1]; t++) {
          int pw, n; proj_decode(I, t, pw, n);
          for (int k = 0; k < nk; k++) {
            mbar_wait(empty + 8 * s, ph);
            mbar_expect(full + 8 * s, 16384);
            if (t < 0) tma_load(base + s * 16384, &P.a[I.pa], k * 64, (I.m * 2 + r) * 128, full + 8 * s);
            else tma_load_mc(base + s * 16384 + r * 8192, &P.w[pw], n * 128 + r * 64, k * 64, full + 8 * s, 3);
            if (++s == PST) { s = 0; ph ^= 1; }
          }
        }
      }
      for (int i = 0; i < PST; i++) { mbar_wait(empty + 8 * s, ph); if (++s == PST) { s = 0; ph ^= 1; } }
    } else if (tid == 288 || tid == 320) {
      const int g = tid == 320;
      int c = 0;
      for (int it = blockIdx.x >> 1; it < P.nitems; it += gridDim.x >> 1) {
        const ProjItem& I = P.item[it];
        for (int t = 0; t < I.n[0] + I.n[1]; t++, c++) {
          int pw, n; proj_decode(I, t, pw, n);
          mbar_wait(of + 8 * g, c & 1);
          tma_store(&P.c[pw], stg + g * 16384, n * 128, (I.m * 2 + r) * 128 + g * 64);
          tma_store(&P.c[pw], stg + g * 16384 + 8192, n * 128 + 64, (I.m * 2 + r) * 128 + g * 64);
          bulk_commit();
          bulk_wait_read<0>();
          mbar_arrive(oe + 8 * g);
          if (t == 3 && !g) CT(0, 1)
          if (t == I.n[0] - 1) { bulk_wait<0>(); signal_after_bulk(S_PROJ + I.pa * (I.m + 1) * 2); }
        }
        bulk_wait<0>(); signal_after_bulk(S_PROJ + I.pa * (I.m + 1) * 2 + 1);
      }
      if (!g) CT(0, 2)
    }
  } else {
    reg_inc<240>();
    uint32_t A[36][4];
    float acc[64];
    uint32_t s = 0, ph = 0, c = 1;
    const uint32_t row = ((tid >> 5) & 3) * 16 + (tid & 15);
    const uint32_t roff = row * 128 + ((((tid >> 4) & 1) ^ (row & 7)) << 4);
    const uint32_t rel = mapa(empty, tid & 1);
    auto release = [&](uint32_t st) { asm volatile("{.reg .pred p; setp.lt.u32 p,%1,2; @p mbarrier.arrive.shared::cluster.b64 _,[%0];}" ::"r"(rel + 8 * st), "r"(tid & 127) : "memory"); };
    for (int it = blockIdx.x >> 1; it < P.nitems; it += gridDim.x >> 1) {
      const int pa = P.item[it].pa, nt = P.item[it].n[0] + P.item[it].n[1];
#pragma unroll
      for (int k = 0; k < 9; k++) {
        if (k < 8 || pa) {
          mbar_wait(full + 8 * s, ph);
#pragma unroll
          for (int kk = 0; kk < 4; kk++) ldsm4(A[4 * k + kk], base + s * 16384 + wg * 8192 + (roff ^ (kk * 32)));
          bar_sync(1 + wg, 128);
          release(s);
          if (++s == PST) { s = 0; ph ^= 1; }
        }
      }
      if (tid == 0) CT(0, 0)
      if (wg) bar_sync(3, 256);
      bool ok = false;
      for (int t = 0; t < nt; t++, c ^= 1) {
        uint32_t p1 = 0, p2 = 0;
#pragma unroll
        for (int k = 0; k < 9; k++) {
          if (k < 8 || pa) {
            if (!ok) mbar_wait(full + 8 * s, ph);
            const uint64_t db = desc_mn(base + s * 16384, 8192);
            wg_fence();
#pragma unroll
            for (int kk = 0; kk < 4; kk++) wg_rs128<1>(acc, A[4 * k + kk], db + kk * 128, k | kk);
            wg_commit();
            const uint32_t cur = s;
            if (++s == PST) { s = 0; ph ^= 1; }
            ok = mbar_test(full + 8 * s, ph);
            if (PWD == 1) { if (k) { wg_wait<1>(); release(p1); } }
            else if (k > 1) { wg_wait<2>(); release(p2); }
            if (k == 4 && t == 0 && !wg) bar_arrive(3, 256);
            p2 = p1; p1 = cur;
          }
        }
        mwait(oe + 8 * wg, c);
        if (PWD == 2) { wg_wait<1>(); release(p2); }
        wg_wait<0>();
        release(p1);
#pragma unroll
        for (int i = 0; i < 8; i++) {
          const float* a = acc + i * 8;
          stsm4(stg + wg * 16384 + (i >> 2) * 8192 + (roff ^ ((i & 3) * 32)), pack2(a[0], a[1]), pack2(a[2], a[3]), pack2(a[4], a[5]), pack2(a[6], a[7]));
        }
        fence_async();
        __syncwarp();
        if ((tid & 31) == 0) mbar_arrive(of + 8 * wg);
      }
    }
  }
}

struct OutMaps { CUtensorMap a, b, bh; };
#define TF 0
constexpr int OSB = 40960;
template <int NST, bool MC> DEVI void out_produce(const OutMaps& M, uint32_t base, uint32_t full, int m, int n, int k0, int nk, int flag = -1) {
  const int r = MC ? blockIdx.x & 1 : 0;
  int s = 0, ph = 1;
#pragma unroll 1
  for (int k = 0; k < nk + (MC ? NST - 1 : 0); k++) {
    mbar_wait(full + 8 * (NST + s), ph);
    if (k < nk) {
      mbar_expect(full + 8 * s, OSB);
#pragma unroll 1
      for (int j = 0; j < 3; j++) {
        if (MC) tma_load_mc(base + s * OSB + 16384 + j * 8192 + r * 4096, &M.bh, n * 192 + j * 64, (k0 + k) * 64 + r * 32, full + 8 * s, 3);
        else tma_load(base + s * OSB + 16384 + j * 8192, &M.b, n * 192 + j * 64, (k0 + k) * 64, full + 8 * s);
      }
      const bool now = flag >= 0 && k == TF;
      if (now) flag_wait(flag, 64, 15);
#pragma unroll 1
      for (int d = now ? TF : k < (flag >= 0 ? TF : NST) ? -1 : 0; d >= 0; d--) tma_load(base + (s - d) * OSB, &M.a, (k0 + k - d) * 64, m * 128, full + 8 * (s - d));
    }
    if (++s == NST) { s = 0; ph ^= 1; }
  }
}
template <int NST> DEVI void out_first(const OutMaps& M, uint32_t base, uint32_t full, int m, int k0, int nk, int flag) {
  flag_wait(flag, 64, 3);
#pragma unroll 1
  for (int k = 0; k < NST; k++) tma_load(base + k * OSB, &M.a, (k0 + k) * 64, m * 128, full + 8 * k);
}
template <int NST, bool MC> DEVI void out_consume(float* acc, uint32_t base, uint32_t full, int nk) {
  const uint32_t empty = full + 8 * NST;
  const int wg = threadIdx.x >> 7;
  int s = 0, ph = 0, prev = 0;
#pragma unroll 1
  for (int k = 0; k < nk; k++) {
    mbar_wait(full + 8 * s, ph);
    const uint64_t da = desc_k(base + s * OSB + wg * 8192), db = desc_mn(base + s * OSB + 16384, 8192);
    wg_fence();
#pragma unroll
    for (int kk = 0; kk < 4; kk++) wg_ss192<1>(acc, da + kk * 2, db + kk * 128, k | kk);
    wg_commit();
    if (k) { wg_wait<1>(); if (MC) arrive_pair(empty + 8 * prev); else if ((threadIdx.x & 127) == 0) mbar_arrive(empty + 8 * prev); }
    prev = s;
    if (++s == NST) { s = 0; ph ^= 1; }
  }
  wg_wait<0>();
}
struct OutParams { OutMaps p[2]; CUtensorMap c[2]; int m0, nb, id; };
#define OST 4
constexpr int SM_O = 5 * OSB + 256;
template <bool MC> __global__ void __launch_bounds__(384, 1) out_kernel(const __grid_constant__ OutParams P) {
  extern __shared__ __align__(1024) uint8_t smem_raw[];
  const uint32_t base = s2u(smem_raw), full = base + OST * OSB;
  const int tid = threadIdx.x, wg = tid >> 7;
  const int pb = (int)blockIdx.x < P.nb, t = pb ? blockIdx.x : 47 - (blockIdx.x - P.nb);
  const int m = (pb ? P.m0 : 0) + (MC ? t / 6 * 2 + (t & 1) : t / 3), n = MC ? (t >> 1) % 3 : t % 3;
  TL_START(P.id)
  pdl_trigger();
  if (tid == 0) {
    for (int i = 0; i < OST; i++) { mbar_init(full + 8 * i, 1); mbar_init(full + 8 * (OST + i), MC ? 4 : 2); }
    asm volatile("fence.mbarrier_init.release.cluster;" ::: "memory");
  }
  if (MC) cluster_sync_relaxed(); else __syncthreads();
  if (wg == 2) {
    if (tid == 256) out_produce<OST, MC>(P.p[pb], base, full, m, n, 0, 64);
    if (tid == 288) out_first<OST>(P.p[pb], base, full, m, 0, 64, (pb ? S_CTXB : S_CTXA) + m);
  } else {
    float acc[96];
    if (tid == 0) CT(P.id, 0)
    out_consume<OST, MC>(acc, base, full, 64);
    if (tid == 0) CT(P.id, 2)
    bar_sync(3, 256);
    const uint32_t row = ((tid >> 5) & 3) * 16 + (tid & 15);
    const uint32_t roff = row * 128 + ((((tid >> 4) & 1) ^ (row & 7)) << 4);
#pragma unroll
    for (int i = 0; i < 12; i++) {
      const float* a = acc + i * 8;
      stsm4(base + wg * 24576 + (i >> 2) * 8192 + (roff ^ ((i & 3) * 32)), pack2(a[0], a[1]), pack2(a[2], a[3]), pack2(a[4], a[5]), pack2(a[6], a[7]));
    }
    fence_async();
    bar_sync(1 + wg, 128);
    if ((tid & 127) == 0) {
      for (int c = 0; c < 3; c++) tma_store(&P.c[pb], base + wg * 24576 + c * 8192, n * 192 + c * 64, m * 128 + wg * 64);
      bulk_commit();
      bulk_wait<0>();
    }
    TL_END(P.id)
  }
}
struct FaParams { CUtensorMap q, k, v, o; unsigned nctas; uint8_t nproj[12]; uint16_t order[512]; };
constexpr int SM_F = 7 * 32768 + 256;
constexpr float FA_C = 0.08838834764831845f * 1.4426950408889634f;
DEVI int fa_qt(int w) { return w >> 5; }
DEVI int fa_hc(int w) { return (w & 31) * 128; }

DEVI void fa_exp(const float* S, uint32_t* Pn, float mc0, float mc1, float& s0, float& s1) {
  float a0 = 0.f, a1 = 0.f, b0 = 0.f, b1 = 0.f;
#pragma unroll
  for (int j = 0; j < 16; j++) {
    const float e0 = ex2(fmaf(S[4 * j], FA_C, -mc0)), e1 = ex2(fmaf(S[4 * j + 1], FA_C, -mc0));
    const float e2 = ex2(fmaf(S[4 * j + 2], FA_C, -mc1)), e3 = ex2(fmaf(S[4 * j + 3], FA_C, -mc1));
    a0 += e0; a1 += e1; b0 += e2; b1 += e3;
    Pn[2 * j] = pack2(e0, e1); Pn[2 * j + 1] = pack2(e2, e3);
  }
  s0 = a0 + a1; s1 = b0 + b1;
}

struct FaState { float mc0, mc1, l0, l1; int w, j, qi; uint32_t dq; bool first; };
enum { F_Q = 0, F_K = 2 * 32768, F_V = 4 * 32768, F_O = 6 * 32768, F_QF = 7 * 32768, F_QE = F_QF + 16, F_KF = F_QF + 32, F_KE = F_QF + 48, F_VF = F_QF + 64, F_VE = F_QF + 80,
       F_OF = F_QF + 96, F_OE = F_QF + 112, F_INFO = F_QF + 128 };

template <int SC> DEVI bool fa_step(FaState& T, float* O, float* S, const uint32_t* Pc, uint32_t* Pn, uint32_t base, int tid, int wg, uint32_t ph) {
  const bool el = (tid & 127) == 0, fin = T.j == 0;
  int wn = T.w, jn = T.j - 1;
  const bool okk = mbar_try(base + F_KF + 8 * (SC ^ 1), ph), okv = mbar_try(base + F_VF + 8 * SC, ph ^ SC);
  if (fin) {
    T.qi++; T.dq ^= 2048;
    mbar_wait(base + F_QF + 8 * (T.qi & 1), (T.qi >> 1) & 1);
    asm volatile("ld.shared.b32 %0,[%1];" : "=r"(wn) : "r"(base + F_INFO + (T.qi & 1) * 4) : "memory");
    wn = __shfl_sync(~0u, wn, 0);
    jn = fa_qt(wn);
  }
  if (!(okk && okv)) { mbar_wait(base + F_KF + 8 * (SC ^ 1), ph); mbar_wait(base + F_VF + 8 * SC, ph ^ SC); }
  const bool last = wn < 0;
  {
    const uint64_t dq = desc_k(0) | T.dq, dk = desc_k(base + F_K + (SC ^ 1) * 32768), dv = desc_mn(base + F_V + SC * 32768, 16384);
    bar_sync(3 + wg, 256);
    wg_fence();
#pragma unroll
    for (int kk = 0; kk < 8; kk++) wg_ss128<0>(S, dq + (kk & 3) * 2 + (kk >> 2) * 1024, dk + (kk & 3) * 2 + (kk >> 2) * 1024, kk);
    wg_commit();
#pragma unroll
    for (int kk = 0; kk < 8; kk++) wg_rs128<1>(O, Pc + 4 * kk, dv + kk * 128, kk || !T.first);
    wg_commit();
    bar_arrive(4 - wg, 256);
  }
  wg_wait<1>();
  asm volatile("{.reg .pred p,q; setp.ne.u32 p,%0,0; setp.eq.and.u32 q,%1,0,p; @p mbarrier.arrive.shared::cta.b64 _,[%2]; @q mbarrier.arrive.shared::cta.b64 _,[%3];}"
               ::"r"((uint32_t)el), "r"(jn), "r"(base + F_KE + 8 * (SC ^ 1)), "r"(base + F_QE + 8 * (T.qi & 1)) : "memory");
  const float lp0 = T.l0, lp1 = T.l1;
  float s0 = 0.f, s1 = 0.f, f0 = 1.f, f1 = 1.f;
  bool exact = fin;
  if (!fin) {
    fa_exp(S, Pn, T.mc0, T.mc1, s0, s1);
    exact = __any_sync(~0u, !(fmaxf(s0, s1) <= 1073741824.f));
  }
  if (exact && !last) {
    float a = -INFINITY, b = -INFINITY;
    if (fin) {
      const int row = (tid >> 5) * 16 + ((tid & 31) >> 2) - (tid & 3) * 2;
#pragma unroll
      for (int j = 0; j < 16; j++) {
        if (j * 8 > row) S[4 * j] = -INFINITY;
        if (j * 8 + 1 > row) S[4 * j + 1] = -INFINITY;
        if (j * 8 > row + 8) S[4 * j + 2] = -INFINITY;
        if (j * 8 + 1 > row + 8) S[4 * j + 3] = -INFINITY;
      }
      T.mc0 = T.mc1 = -INFINITY;
    }
#pragma unroll
    for (int j = 0; j < 16; j++) { a = fmaxf(a, fmaxf(S[4 * j], S[4 * j + 1])); b = fmaxf(b, fmaxf(S[4 * j + 2], S[4 * j + 3])); }
    a = fmaxf(a, __shfl_xor_sync(~0u, a, 1)); b = fmaxf(b, __shfl_xor_sync(~0u, b, 1));
    a = fmaxf(a, __shfl_xor_sync(~0u, a, 2)); b = fmaxf(b, __shfl_xor_sync(~0u, b, 2));
    a = fmaxf(a * FA_C, T.mc0); b = fmaxf(b * FA_C, T.mc1);
    f0 = ex2(T.mc0 - a); f1 = ex2(T.mc1 - b);
    T.mc0 = a; T.mc1 = b;
    T.l0 = fin ? 0.f : T.l0 * f0; T.l1 = fin ? 0.f : T.l1 * f1;
    fa_exp(S, Pn, a, b, s0, s1);
  }
  T.l0 += s0; T.l1 += s1;
  wg_wait<0>();
  if (el) mbar_arrive(base + F_VE + 8 * SC);
  if (exact) {
    if (fin) {
      f0 = lp0 + __shfl_xor_sync(~0u, lp0, 1); f1 = lp1 + __shfl_xor_sync(~0u, lp1, 1);
      f0 += __shfl_xor_sync(~0u, f0, 2); f1 += __shfl_xor_sync(~0u, f1, 2);
      f0 = 1.f / f0; f1 = 1.f / f1;
    }
#pragma unroll
    for (int i = 0; i < 16; i++) { O[4 * i] *= f0; O[4 * i + 1] *= f0; O[4 * i + 2] *= f1; O[4 * i + 3] *= f1; }
    if (fin && (T.qi || last)) {
      const uint32_t row = ((tid >> 5) & 3) * 16 + (tid & 15);
      const uint32_t o = base + F_O + wg * 16384 + row * 128 + ((((tid >> 4) & 1) ^ (row & 7)) << 4);
      if (T.qi) mbar_wait(base + F_OE + 8 * wg, T.qi & 1);
#pragma unroll
      for (int i = 0; i < 8; i++) {
        const float* a = O + i * 8;
        stsm4((o ^ ((i & 3) * 32)) + (i >> 2) * 8192, pack2(a[0], a[1]), pack2(a[2], a[3]), pack2(a[4], a[5]), pack2(a[6], a[7]));
      }
      if (el) asm volatile("st.shared.b32 [%0],%1;" ::"r"(base + F_INFO + 8 + wg * 4), "r"(!T.qi ? -1 : T.w | (last ? 1024 : 0)) : "memory");
      fence_async();
      __syncwarp();
      if ((tid & 31) == 0) mbar_arrive(base + F_OF + 8 * wg);
    }
  }
  T.w = wn; T.j = jn; T.first = fin;
  return last;
}

__global__ void __launch_bounds__(384, 1) fa_kernel(const __grid_constant__ FaParams P) {
  extern __shared__ __align__(1024) uint8_t smem_raw[];
  const uint32_t base = s2u(smem_raw);
  const uint32_t sQ = base, sK = base + 2 * 32768, sV = base + 4 * 32768, sO = base + 6 * 32768, bars = base + 7 * 32768;
  const uint32_t qf = bars, qe = bars + 16, kf = bars + 32, ke = bars + 48, vf = bars + 64, ve = bars + 80, of = bars + 96, oe = bars + 112;
  volatile int* info = (volatile int*)(smem_raw + 7 * 32768 + 128);
  const int tid = threadIdx.x, wg = tid >> 7;
  pdl_trigger();
  if (tid == 0) {
    for (int i = 0; i < 16; i++) mbar_init(bars + 8 * i, i >= 14 ? 1 : i >= 12 ? 4 : (i & 2) ? 2 : 1);
    info[4] = 0;
    asm volatile("fence.mbarrier_init.release.cluster;" ::: "memory");
  }
  __syncthreads();
  if (wg == 2) {
    reg_dec<24>();
    if (tid == 256) {
      int it = 0, qi = 0, vc = 0, vr = -1, j = 0, hc = 0;
      CT(gridDim.x > 20 ? 3 : 6, 0)
      auto load_v = [&]() {
        if (vr < 0) return;
        const int s = (it - 1) & 1;
        mbar_wait(ve + 8 * s, (((it - 1) >> 1) & 1) ^ 1 ^ s);
        mbar_expect(vf + 8 * s, 32768);
        tma_load(sV + s * 32768, &P.v, vc, vr, vf + 8 * s);
        tma_load(sV + s * 32768 + 16384, &P.v, vc + 64, vr, vf + 8 * s);
        vr = -1;
      };
      auto ready = [&](uint32_t m) { uint32_t v; asm volatile("ld.acquire.cta.shared.b32 %0,[%1];" : "=r"(v) : "r"(base + F_INFO + 16) : "memory"); return (v & m) == m; };
      for (it = -1;; it++) {
        if (it >= 0) {
          const int s = it & 1;
          mbar_wait(ke + 8 * s, ((it >> 1) & 1) ^ 1);
          if (j < 0) { mbar_arrive(kf + 8 * s); load_v(); break; }
          mbar_expect(kf + 8 * s, 32768);
          tma_load(sK + s * 32768, &P.k, hc, j * 128, kf + 8 * s);
          tma_load(sK + s * 32768 + 16384, &P.k, hc + 64, j * 128, kf + 8 * s);
        }
        int nc = hc, nr = it >= 0 ? j * 128 : -1;
        if (j-- == 0) {
          int w = atomicInc(&g_sync[S_QUEUE], 511 + P.nctas);
          w = w < 512 ? P.order[w] : -1;
          const uint32_t q = qi & 1, m = w < 0 ? 0x3ffff : (1u | (2u << (fa_qt(w) | 1))) << ((w >> 4) & 1);
          if (!ready(m) || !mbar_test(qe + 8 * q, ((qi >> 1) & 1) ^ 1)) {
            load_v(); it++; vc = nc; vr = nr; load_v(); it--; nr = -1;
            for (int n = 0; !ready(m) && n < WAIT_MAX; n++) __nanosleep(64);
            mbar_wait(qe + 8 * q, ((qi >> 1) & 1) ^ 1);
          }
          asm volatile("fence.proxy.async.global;" ::: "memory");
          info[q] = w;
          if (w < 0) mbar_arrive(qf + 8 * q);
          else {
            j = fa_qt(w); hc = fa_hc(w);
            mbar_expect(qf + 8 * q, 32768);
            tma_load(sQ + q * 32768, &P.q, hc, j * 128, qf + 8 * q);
            tma_load(sQ + q * 32768 + 16384, &P.q, hc + 64, j * 128, qf + 8 * q);
          }
          qi++;
        }
        load_v();
        vc = nc; vr = nr;
      }
      if (atomicInc(&g_sync[S_EXIT], P.nctas - 1) == P.nctas - 1)
        for (int i = 0; i < 18; i++) g_sync[S_PROJ + i] = 0;
    } else if (tid >= 352) {
      const int l = tid - 352;
      for (int n = 0; n < WAIT_MAX; n++) {
        unsigned v = 255;
        if (l < 18) asm volatile("ld.acquire.gpu.global.u32 %0, [%1];" : "=r"(v) : "l"(g_sync + S_PROJ + l) : "memory");
        const uint32_t m = __ballot_sync(~0u, v >= P.nproj[(l >> 1) % 9]);
        __syncwarp();
        if (l == 0) asm volatile("st.release.cta.shared.b32 [%0],%1;" ::"r"(base + F_INFO + 16), "r"(m) : "memory");
        if (m == ~0u) break;
        __nanosleep(300);
      }
    } else if (tid == 288 || tid == 320) {
      const int g = tid == 320;
        for (int n = 0;; n++) {
          mbar_wait(of + 8 * g, n & 1);
          const int v = info[2 + g], w = v & 1023, qt = fa_qt(w), hc = fa_hc(w);
          if (v < 0) break;
          tma_store(&P.o, sO + g * 16384, hc, qt * 128 + g * 64);
          tma_store(&P.o, sO + g * 16384 + 8192, hc + 64, qt * 128 + g * 64);
          bulk_commit();
          bulk_wait_read<0>();
          mbar_arrive(oe + 8 * g);
          bulk_wait<0>();
          signal_after_bulk(S_CTXA + qt);
          if (v & 1024) break;
        }
    }
  } else {
    reg_inc<240>();
    float O[64], S[64];
    uint32_t PA[32], PB[32];
#pragma unroll
    for (int i = 0; i < 32; i++) PA[i] = 0;
#pragma unroll
    for (int i = 0; i < 64; i++) O[i] = 0.f;
    const uint32_t ub = __shfl_sync(~0u, base, 0);
    const int uw = __shfl_sync(~0u, wg, 0);
    FaState T = {0.f, 0.f, 1.f, 1.f, 0, 0, -1, ((ub + 32768 + uw * 8192) >> 4) & 0x3fff, true};
    if (wg == 1) bar_arrive(3, 256);
    for (uint32_t ph = 0;; ph ^= 1) {
      if (fa_step<1>(T, O, S, PA, PB, ub, tid, uw, ph)) break;
      if (fa_step<0>(T, O, S, PB, PA, ub, tid, uw, ph)) break;
    }
    if (wg == 0) bar_sync(3, 256);
  }
}
#define PS 20
#define PT(i)
#define GT(i)
#define YD 200
#define NPF 4
#define NRES 6
#define RP 208
#define PD 2
#define SL 1
#define XI 0
#define NPE 4
#define NUP 2
#define LATE 0
#define VR "............rrrrrr.................."
#define VP "222222222222111111111111------------"
constexpr int vr_index(int k) { int n = 0; for (int i = 0; i < k; i++) n += VR[i] == 'r'; return n; }
constexpr int VB = vr_index(36);
template <int K> struct VIdx { static constexpr int v = vr_index(K); static constexpr char r = VR[K], p = VP[K]; };
#define LF 0
#define XG 6
#define XW 2
#define WOD 4000
#define WVP 1
#define SP 0
#define UO 0
#define AW 0
#define CTR 0
#define CF 0
#define ROT 3
#define KA 26
constexpr int R_WV = 0, R_WO = 73728, R_H = 147456, R_OX = R_H + 46080, R_Q = R_OX + 4096, R_K = R_Q + 5120, R_SX = R_K + 5120, R_P = R_SX + 3200, R_U = R_P + 3200,
              R_BAR = R_H + 73728, R_PROF = R_BAR + 256, R_END = R_PROF + 3072;
constexpr int B_W0 = R_BAR, B_W1 = R_BAR + 8, B_XA = R_BAR + 16, B_XB = R_BAR + 24, B_XF = R_BAR + 32, B_Z0 = R_BAR + 40, B_Z1 = R_BAR + 48, B_R = R_BAR + 56,
              B_SM = R_BAR + 64, B_SX = R_BAR + 72, B_U = R_BAR + 80, B_V = R_BAR + 88, B_O = R_BAR + 96, B_W2 = R_BAR + 160, B_W3 = R_BAR + 168;
static_assert(R_U + 4096 <= R_BAR, "");
enum { N_P1 = 1, N_PM, N_PX, N_SUM, N_O, N_INIT, N_INIT1, N_INIT2, N_WO, N_S };
constexpr int YSLOT = 9 * 16 * 1024;
struct RecParams { CUtensorMap wq, wk, wv, wo, x, ctx; OutMaps o; const bf16 *mem0, *x_raw; bf16* out; };
constexpr int TAIL0 = 12;
constexpr int R_RED = 4 * OSB;

DEVI uint64_t mkdesc(uint32_t a, uint32_t lbo, uint32_t sbo, int sw) { return (uint64_t)((a >> 4) & 0x3fff) | ((uint64_t)(lbo >> 4) << 16) | ((uint64_t)(sbo >> 4) << 32) | ((uint64_t)sw << 62); }
DEVI void wg_rs32(float* d, const uint32_t* a, uint64_t db, int acc) {
  asm volatile("{.reg .pred p; setp.ne.b32 p,%21,0;\n wgmma.mma_async.sync.aligned.m64n32k16.f32.bf16.bf16 {%0,%1,%2,%3,%4,%5,%6,%7,%8,%9,%10,%11,%12,%13,%14,%15},{%16,%17,%18,%19},%20,p,1,1,0;}"
               : F8(d, 0), F8(d, 8) : "r"(a[0]), "r"(a[1]), "r"(a[2]), "r"(a[3]), "l"(db), "r"(acc));
}
DEVI void wg_rs40(float* d, const uint32_t* a, uint64_t db, int acc) {
  asm volatile("{.reg .pred p; setp.ne.b32 p,%25,0;\n wgmma.mma_async.sync.aligned.m64n40k16.f32.bf16.bf16 {%0,%1,%2,%3,%4,%5,%6,%7,%8,%9,%10,%11,%12,%13,%14,%15,%16,%17,%18,%19},{%20,%21,%22,%23},%24,p,1,1,0;}"
               : F8(d, 0), F8(d, 8), "+f"(d[16]), "+f"(d[17]), "+f"(d[18]), "+f"(d[19]) : "r"(a[0]), "r"(a[1]), "r"(a[2]), "r"(a[3]), "l"(db), "r"(acc));
}
template <int TB> DEVI void wg_ss40(float* d, uint64_t da, uint64_t db, int acc) {
  asm volatile("{.reg .pred p; setp.ne.b32 p,%22,0;\n wgmma.mma_async.sync.aligned.m64n40k16.f32.bf16.bf16 {%0,%1,%2,%3,%4,%5,%6,%7,%8,%9,%10,%11,%12,%13,%14,%15,%16,%17,%18,%19},%20,%21,p,1,1,1,%23;}"
               : F8(d, 0), F8(d, 8), "+f"(d[16]), "+f"(d[17]), "+f"(d[18]), "+f"(d[19]) : "l"(da), "l"(db), "r"(acc), "n"(TB));
}
DEVI void mma8(float* d, uint32_t a0, uint32_t a1, uint32_t b0) {
  asm volatile("mma.sync.aligned.m16n8k8.row.col.f32.bf16.bf16.f32 {%0,%1,%2,%3},{%4,%5},{%6},{%0,%1,%2,%3};" : "+f"(d[0]), "+f"(d[1]), "+f"(d[2]), "+f"(d[3]) : "r"(a0), "r"(a1), "r"(b0));
}
DEVI void stsm4t(uint32_t a, uint32_t r0, uint32_t r1, uint32_t r2, uint32_t r3) {
  asm volatile("stmatrix.sync.aligned.m8n8.x4.trans.shared.b16 [%0],{%1,%2,%3,%4};" ::"r"(a), "r"(r0), "r"(r1), "r"(r2), "r"(r3) : "memory");
}
DEVI uint32_t movm(uint32_t a) { uint32_t d; asm volatile("movmatrix.sync.aligned.m8n8.trans.b16 %0,%1;" : "=r"(d) : "r"(a)); return d; }
DEVI void sts1(uint32_t a, uint32_t v) { asm volatile("st.shared.b32 [%0],%1;" ::"r"(a), "r"(v) : "memory"); }
DEVI uint32_t lds1(uint32_t a) { uint32_t v; asm volatile("ld.shared.b32 %0,[%1];" : "=r"(v) : "r"(a) : "memory"); return v; }
DEVI void sta1(uint32_t d, uint32_t a, uint32_t bar) { asm volatile("st.async.weak.shared::cluster.mbarrier::complete_tx::bytes.b32 [%0],%1,[%2];" ::"r"(d), "r"(a), "r"(bar) : "memory"); }
DEVI void sta2(uint32_t d, uint32_t a, uint32_t b, uint32_t bar) { asm volatile("st.async.weak.shared::cluster.mbarrier::complete_tx::bytes.v2.b32 [%0],{%1,%2},[%3];" ::"r"(d), "r"(a), "r"(b), "r"(bar) : "memory"); }
DEVI void mspin(uint32_t b, uint32_t ph) { for (int it = 0; !mbar_test(b, ph) && it < (1 << 24); it++) {} }
DEVI uint32_t clk32() { uint64_t c; asm volatile("mov.u64 %0,%%clock64;" : "=l"(c)::"memory"); return (uint32_t)c; }
DEVI int opq(int x) { asm volatile("" : "+r"(x)); return x; }
DEVI int pin(int x) { return __shfl_sync(~0u, x, threadIdx.x & 31); }
DEVI uint32_t zero_after(float x) { uint32_t t; asm volatile("{.reg .u32 t; popc.b32 t,%1; shr.u32 %0,t,6;}" : "=r"(t) : "r"(__float_as_uint(x))); return t; }
DEVI void x_load(const RecParams& P, uint32_t sb, int c, int seg) {
  asm volatile("cp.async.bulk.tensor.2d.shared::cluster.global.mbarrier::complete_tx::bytes.multicast::cluster [%0],[%1,{%3,%4}],[%2],%5;"
               ::"r"(sb + R_H + c * 5120 + 1024), "l"(&P.x), "r"(sb + (c < XG ? B_XA : B_XB)), "r"(c * 64), "r"(seg * 32), "h"((uint16_t)0xffff) : "memory");
  if (seg + 2 < NSEG) asm volatile("cp.async.bulk.prefetch.tensor.2d.L2.global [%0,{%1,%2}];" ::"l"(&P.x), "r"(c * 64), "r"(seg * 32 + 64) : "memory");
}
DEVI uint32_t hadd2(uint32_t a, uint32_t b) { uint32_t r; asm("add.rn.bf16x2 %0,%1,%2;" : "=r"(r) : "r"(a), "r"(b)); return r; }
DEVI uint32_t hmax2(uint32_t a, uint32_t b) { uint32_t r; asm("max.bf16x2 %0,%1,%2;" : "=r"(r) : "r"(a), "r"(b)); return r; }
DEVI float rcp(float x) { float y; asm("rcp.approx.ftz.f32 %0,%1;" : "=f"(y) : "f"(x)); return y; }
constexpr float SCL = 0.08838834764831845f * 1.4426950408889634f;

DEVI void y_store(const float* a, uint32_t off, int s) {
  const uint32_t x = movm(pack2(a[0], a[1])), y = movm(pack2(a[2], a[3]));
  const uint32_t tag = ((s >> 1) & 1) ^ 1;
  asm volatile("st.relaxed.gpu.global.b64 [%0],%1;" ::"l"((uint8_t*)g_Y + (s & 1) * YSLOT + off), "l"((uint64_t)((x & ~1u) | tag) | ((uint64_t)y << 32)) : "memory");
}
DEVI void y_load(uint32_t* w, const uint8_t* p) {
#pragma unroll
  for (int i = 0; i < 4; i++) asm volatile("{.reg .b64 t; ld.relaxed.gpu.global.b64 t,[%2]; mov.b64 {%0,%1},t;}" : "=r"(w[2 * i]), "=r"(w[2 * i + 1]) : "l"(p + i * 256) : "memory");
}
DEVI bool y_missing(const uint32_t* w, uint32_t tag) {
  uint32_t r;
  asm volatile("{.reg .b32 a,b; .reg .pred p; lop3.b32 a,%1,%2,%5,0x7e; lop3.b32 b,%3,%4,%5,0x7e; lop3.b32 a,a,b,1,0xa8; setp.ne.u32 p,a,0; vote.sync.any.pred p,p,0xffffffff; selp.u32 %0,1,0,p;}"
               : "=r"(r) : "r"(w[0]), "r"(w[2]), "r"(w[4]), "r"(w[6]), "r"(tag));
  return r;
}
DEVI void y_reload(uint32_t* w, const uint8_t* p, uint32_t tag) {
#pragma unroll
  for (int i = 0; i < 4; i++)
    asm volatile("{.reg .b64 t; .reg .b32 a; .reg .pred q; lop3.b32 a,%0,%3,1,0x28; setp.ne.u32 q,a,0; mov.b64 t,{%0,%1}; @q ld.relaxed.gpu.global.b64 t,[%2]; mov.b64 {%0,%1},t;}"
                 : "+r"(w[2 * i]), "+r"(w[2 * i + 1]) : "l"(p + i * 256), "r"(tag) : "memory");
}
DEVI void y_sum(uint32_t* r, const uint32_t* w, uint32_t sel) {
  float d0[4] = {0, 0, 0, 0}, d1[4] = {0, 0, 0, 0};
  mma16(d0, w[0], w[1], w[2], w[3], sel, sel); mma16(d1, w[4], w[5], w[6], w[7], sel, sel);
  r[0] = pack2(d0[0] + d1[0], d0[1] + d1[1]); r[1] = pack2(d0[2] + d1[2], d0[3] + d1[3]);
}
DEVI void y_send(const uint32_t* r, uint32_t sb, uint32_t dst, uint32_t bar, int lane, int rk) {
#pragma unroll
  for (int i = 0; i < 4; i++) { const uint32_t rs = mapa(sb, ROT == 1 ? ((lane & 3) * 4 + i) ^ rk : ROT == 2 ? ((lane & 3) + i * 4) ^ rk : ROT == 3 ? (lane & 3) + i * 4 : (lane & 3) * 4 + i); sta2(rs + dst, r[0], r[1], rs + bar); }
}
DEVI void wo_convert(uint32_t sb, int lane) {
  TL_END(11)
  mbar_wait(sb + B_W3, 0);
  TL_END(9)
#pragma unroll 1
  for (uint32_t a = sb + R_WO + ((threadIdx.x >> 5) & 3) * 4608, i = 0; i < 4; i++, a += 18432) {
    uint32_t r[9][4];
#pragma unroll
    for (int k = 0; k < 9; k++) ldsm4t(r[k], a + k * 32 + ((lane & 7) + (lane >> 4) * 8) * 288 + ((lane >> 3) & 1) * 16);
    __syncwarp();
#pragma unroll
    for (int k = 0; k < 9; k++) stsm4(a + k * 512 + ((lane >> 4) * 2 + ((lane >> 1) & 1)) * 128 + (((lane >> 2) & 3) * 2 + (lane & 1)) * 16, r[k][0], r[k][1], r[k][2], r[k][3]);
  }
  __syncwarp();
}
DEVI uint32_t y_offset(int cta, int tile, int lane) {
  const int T = (cta & 3) * 9 + tile;
  return (((T >> 2) * 8 + (lane >> 2)) * 2 + ((T >> 1) & 1)) * 1024 + (cta >> 4) * 256 + (T & 1) * 128 + ((cta >> 2) & 3) * 32 + (lane & 3) * 8;
}
template <int NR, int NP, int NE, int UP> DEVI void wo_tile(const uint32_t (*A0)[4], uint32_t sb, int chunk, int cta, int lane, uint32_t yo, int s) {
  uint32_t u[8][4], A[16][4];
  const uint32_t wa = sb + R_WO + chunk * 512 + lane * 16, ua = sb + R_U + lane * 16;
  float a[4] = {0, 0, 0, 0}, b[4] = {0, 0, 0, 0};
  auto fetch = [&](int i) { if (i < 16 - NR) ldsm4(A[i], wa + i * 4608); };
  auto uload = [&](int i) { if (i < 8) ldsm4t(u[i], ua + i * 512); };
#pragma unroll
  for (int i = 0; i < NE; i++) fetch(i);
  if (SP & 8) mspin(sb + B_V, s & 1); else mwait(sb + B_V, s & 1);
  PT(6)
  uload(0); uload(1);
#pragma unroll
  for (int i = NE; i < NP; i++) fetch(i);
#pragma unroll
  for (int i = 0; i < 16; i++) {
    if (i == 4) {
      if (SP & 2) mspin(sb + B_U, s & 1); else mwait(sb + B_U, s & 1);
      PT(7)
#pragma unroll
      for (int k = 2; k < 2 + UP; k++) uload(k);
    }
    const uint32_t* f = i >= 16 - NR ? A0[i >= 16 - NR ? i - 16 + NR : 0] : A[i];
    mma16(i & 1 ? b : a, f[0], f[1], f[2], f[3], u[i >> 1][(i & 1) * 2], u[i >> 1][(i & 1) * 2 + 1]);
    fetch(i + NP);
    if (i >= 4 && (i & 1)) uload((i >> 1) + UP);
  }
#pragma unroll
  for (int i = 0; i < 4; i++) a[i] += b[i];
  y_store(a, yo, s);
}
template <bool X> DEVI void softmax8(const uint32_t* h, uint32_t a4, uint32_t a1, uint32_t a2 = 0) {
  uint32_t y[5];
  if (X && CTR && a2) { asm volatile("ld.shared.v2.b32 {%0,%1},[%2];" : "=r"(y[0]), "=r"(y[1]) : "r"(a2 + R_SX) : "memory"); y[2] = y[3] = 0; }
  else lds4(y, a4 + R_SX);
  y[4] = lds1(a1 + R_SX);
#pragma unroll
  for (int j = 0; j < 5; j++) y[j] = hadd2(h[j], y[j]);
  const uint32_t m2 = hmax2(hmax2(hmax2(y[0], y[1]), hmax2(y[2], y[3])), y[4]);
  const float mc = fmaxf(blo(m2), bhi(m2)) * SCL;
  const float m1 = __shfl_xor_sync(~0u, mc, 1), m3 = __shfl_xor_sync(~0u, mc, 2), m4 = __shfl_xor_sync(~0u, mc, 3);
  float e[10];
#pragma unroll
  for (int j = 0; j < 5; j++) { e[2 * j] = ex2(fmaf(blo(y[j]), SCL, -mc)); e[2 * j + 1] = ex2(fmaf(bhi(y[j]), SCL, -mc)); }
  const float c = ex2(mc - fmaxf(fmaxf(mc, m1), fmaxf(m3, m4)));
  const float l = c * ((((e[0] + e[1]) + (e[2] + e[3])) + ((e[4] + e[5]) + (e[6] + e[7]))) + (e[8] + e[9]));
  const float r = c * rcp((l + __shfl_xor_sync(~0u, l, 1)) + (__shfl_xor_sync(~0u, l, 2) + __shfl_xor_sync(~0u, l, 3)));
#pragma unroll
  for (int j = 0; j < 5; j++) y[j] = pack2(e[2 * j] * r, e[2 * j + 1] * r);
  if (!X) sts4(a4 + R_P, y[0], y[1], y[2], y[3]);
  else stsm4(a4 + R_P, y[0], y[1], y[2], y[3]);
  sts1(a1 + R_P, y[4]);
  if (X) fence_async();
}

DEVI void arm_step(uint32_t sb, int s) {
  mbar_expect(sb + B_SM, 640); mbar_expect(sb + B_SX, CTR ? 2048 : 2560);
  if (s < NSEG - 1) {
    mbar_expect(sb + B_U, 3072); mbar_expect(sb + B_Z0, 4096); mbar_expect(sb + B_Z1, 5120);
    mbar_expect(sb + B_XA, XG * 4096); mbar_expect(sb + B_XB, (9 - XG) * 4096);
  }
}
DEVI void rec_proj(const RecParams& P, const uint32_t sb, const int cta) {
  uint32_t W[36][4], A0[NRES ? NRES : 1][4];
  const int tid = pin(threadIdx.x);
  const uint32_t yo = pin(y_offset(cta, threadIdx.x >> 5, threadIdx.x & 31));
  const int warp = __shfl_sync(~0u, threadIdx.x >> 5, 0), role = warp >> 2;
  const uint32_t qk = sb + R_Q + warp * 1280;
  {
    const int lane = threadIdx.x & 31, w4 = (threadIdx.x >> 5) & 3;
    const uint32_t a = sb + role * R_H + ((lane & 7) + (lane >> 4) * 8) * 128 + (((w4 * 2 + ((lane >> 3) & 1)) ^ (lane & 7)) << 4);
    mbar_wait(sb + B_W0 + role * 8, 0);
    TL_END(8)
#pragma unroll
    for (int k = 0; k < 36; k++) ldsm4t(W[k], a + k * 2048);
    if (LATE == 1) pdl_trigger();
    if (role) bar_arrive(N_INIT1, 256); else bar_sync(N_INIT, 128);
    cluster_sync_relaxed();
#pragma unroll
    for (int i = 0; i < NRES; i++) A0[i][0] = A0[i][1] = A0[i][2] = A0[i][3] = 0;
  }
  for (int s = -1; s < NSEG; s++) {
    if (s >= 0) {
      PT(0)
      {
        const int lane = opq(tid) & 31;
        const uint32_t hb = sb + R_H + (lane & 7) * 128 + (((lane >> 3) ^ (lane & 7)) << 4);
        float a[4] = {0, 0, 0, 0}, b[4] = {0, 0, 0, 0};
        if (SP & 4) mspin(sb + B_Z0, (s - 1) & 1); else mwait(sb + B_Z0, (s - 1) & 1);
        PT(1) if (role) { GT(0) }
        uint32_t f[18][4];
#pragma unroll
        for (int c = -PD; c < 18; c++) {
          if (c + PD == 8) mwait(sb + B_Z1, (s - 1) & 1);
          if (c + PD < 18) ldsm4(f[c + PD], (hb ^ (((c + PD) & 1) * 64)) + ((c + PD) >> 1) * 5120);
          if (c >= 0) {
            mma16(a, W[2 * c][0], W[2 * c][1], W[2 * c][2], W[2 * c][3], f[c][0], f[c][1]);
            mma16(b, W[2 * c + 1][0], W[2 * c + 1][1], W[2 * c + 1][2], W[2 * c + 1][3], f[c][2], f[c][3]);
          }
        }
        sts1(qk + 512 + lane * 4, pack2(a[0] + b[0], a[1] + b[1]));
        sts1(qk + 1152 + lane * 4, pack2(a[2] + b[2], a[3] + b[3]));
        if (!CF) fence_async();
      }
      PT(2)
      const int lane = opq(tid) & 31;
      if (role) {
        bar_arrive(N_P1, 256);
        if (!AW && tid == 128) arm_step(sb, s);
        const uint32_t o4 = sb + (warp - 4) * 640 + lane * 16, o1 = sb + (warp - 4) * 640 + 512 + lane * 4;
        uint32_t h[5];
        bar_sync(N_PX, 192);
        lds4(h, o4 + R_P); h[4] = lds1(o1 + R_P);
        mwait(sb + B_SX, s & 1);
        PT(4)
        softmax8<true>(h, o4, o1, warp < 6 ? o4 - lane * 8 : 0);
        PT(5)
      } else {
        float S[20];
        const uint64_t da = mkdesc(sb + R_Q, 640, 128, 0), db = mkdesc(sb + R_K, 640, 128, 0);
        const uint32_t rs = mapa(sb, (cta & 15) ^ 1);
        const uint32_t o4 = warp * 1280 + lane * 16, o1 = warp * 1280 + 512 + lane * 4;
        bar_sync(N_P1, 256);
        if (CF) fence_async();
        wg_fence();
#pragma unroll
        for (int k = 0; k < 4; k++) wg_ss40<1>(S, da + k * 80, db + k * 80, k);
        wg_commit();
        bar_arrive(N_S, 256);
        wg_wait<0>();
        PT(3)
        uint32_t h[2][5];
        if (warp == 2) {
#pragma unroll
          for (int j = 0; j < 5; j++) h[0][j] = pack2(S[4 * j], S[4 * j + 1]);
          sta4(rs + R_SX + o4, h[0][0], h[0][1], h[0][2], h[0][3], rs + B_SM); sta1(rs + R_SX + o1, h[0][4], rs + B_SM);
          if (SP & 1) mspin(sb + B_SM, s & 1); else mwait(sb + B_SM, s & 1);
          PT(4)
          softmax8<false>(h[0], sb + o4, sb + o1);
          bar_arrive(N_PM, 160);
        } else if (warp < 2) {
          const int row = warp * 16 + (lane >> 2) - (lane & 3) * 2;
#pragma unroll
          for (int g = 0; g < 2; g++) {
#pragma unroll
            for (int j = 0; j < 5; j++) h[g][j] = pack2(j < 4 && j * 8 > row + g * 8 ? -INFINITY : S[4 * j + 2 * g], j < 4 && j * 8 + 1 > row + g * 8 ? -INFINITY : S[4 * j + 2 * g + 1]);
            sts4(sb + R_P + o4 + g * 640, h[g][0], h[g][1], h[g][2], h[g][3]); sts1(sb + R_P + o1 + g * 640, h[g][4]);
            if (CTR && warp == 0) sta2(rs + R_SX + g * 640 + lane * 8, h[g][0], h[g][1], rs + B_SX);
            else sta4(rs + R_SX + o4 + g * 640, h[g][0], h[g][1], h[g][2], h[g][3], rs + B_SX);
            sta1(rs + R_SX + o1 + g * 640, h[g][4], rs + B_SX);
          }
          bar_arrive(N_PX, 192);
        } else {
          if (s) bar_sync(N_O, 160);
          if (tid == 96) {
            if (s) {
              bulk_wait<0>();
              tma_store(&P.ctx, sb + R_OX, cta * 64, s * 32 - 32); bulk_commit();
              if ((s & 3) == 1 && s > 1) signal_after_bulk(S_CTXB + (s >> 2) - 1);
              bulk_wait_read<0>();
            }
            if (XI && (cta & 15) < XG && s < NSEG - 1) { mbar_wait(sb + B_XF, s & 1); x_load(P, sb, cta & 15, s + 1); }
          }
        }
        __syncwarp();
        PT(5)
      }
      {
        if (s == 0) {
          bar_sync(N_INIT2, 384);
#pragma unroll
          for (int i = 0; i < NRES; i++) ldsm4(A0[i], sb + R_WO + warp * 512 + lane * 16 + (16 - NRES + i) * 4608);
        }
        if (s == NSEG - 1) break;
        wo_tile<NRES, NPF, NPE, NUP>(A0, sb, warp, cta, lane, yo, s);
        if (role) { GT(1) }
        PT(8)
        bar_sync(N_WO, 384);
      }
    }
    {
      float acc[16];
      const uint64_t db = mkdesc(sb + R_H + 1024, 16, 1024, 1);
      mwait(sb + B_XA, (s + 1) & 1);
      PT(9) if (role) { GT(2) }
      wg_fence();
#pragma unroll
      for (int k = 0; k < (KA < XG * 4 ? KA : XG * 4); k++) wg_rs32(acc, W[k], db + (k >> 2) * 320 + (k & 3) * 2, k);
      wg_commit();
      mwait(sb + B_XB, (s + 1) & 1);
      wg_fence();
#pragma unroll
      for (int k = XG * 4; k < KA; k++) wg_rs32(acc, W[k], db + (k >> 2) * 320 + (k & 3) * 2, 1);
      wg_commit();
      wg_wait<0>();
      PT(10)
      if (KA < 36 || s < 0) bar_sync(N_SUM, 384);
      wg_fence();
#pragma unroll
      for (int k = KA; k < 36; k++) wg_rs32(acc, W[k], db + (k >> 2) * 320 + (k & 3) * 2, 1);
      wg_commit();
      const uint32_t o = qk + (opq(tid) & 31) * 16;
      wg_wait<0>();
      PT(11)
      stsm4(o, pack2(acc[0], acc[1]), pack2(acc[4], acc[5]), pack2(acc[8], acc[9]), pack2(acc[12], acc[13]));
      stsm4(o + 640, pack2(acc[2], acc[3]), pack2(acc[6], acc[7]), pack2(acc[10], acc[11]), pack2(acc[14], acc[15]));
    }
  }
  bar_arrive(N_WO, 384);
  for (int i = 0; i < (warp ? 1 : 2); i++)
    asm volatile("st.relaxed.gpu.global.b64 [%0],%1;" ::"l"((uint8_t*)g_Y + YSLOT + yo + i * 2 * 16384), "l"(0ull) : "memory");
  TL_END(6)
  if (tid == 0) CT(1, 0)
  if (warp == 3) {
    if (tid == 96) { bulk_wait<0>(); asm volatile("fence.proxy.async.global;" ::: "memory"); }
    __syncwarp();
    bar_arrive(N_O, 160);
  }
  asm volatile("barrier.cluster.arrive.relaxed.aligned;" ::: "memory");
  float acc[96];
  const int rk = opq(cta) & 15, n = rk / 5, q = rk - n * 5;
  out_consume<4, false>(acc, sb, sb + B_O, rk == 15 ? 0 : q == 4 ? 12 : 13);
  if (tid == 0) CT(7, 1)
  if (tid == 0) CT(1, 1)
  asm volatile("barrier.cluster.wait.aligned;" ::: "memory");
  bar_sync(N_P1, 256);
  {
#pragma unroll
    for (int u = 0; u < 12; u++) {
      const int d = u % 5;
      const float* a = acc + u * 8;
      const uint32_t x = pack2(a[0], a[1]), y = pack2(a[2], a[3]), z = pack2(a[4], a[5]), w = pack2(a[6], a[7]);
      const uint32_t rs = mapa(sb, rk == 15 ? 15 : n * 5 + d);
      if (d == q) sts4(sb + R_RED - 12288 + (u / 5) * 4096 + tid * 16, x, y, z, w);
      else sta4(rs + R_RED + (q < d ? q : q - 1) * 12288 + (u / 5) * 4096 + tid * 16, x, y, z, w, rs + B_R);
    }
    mbar_wait(sb + B_R, 0);
    if (tid == 0) CT(1, 2)
    const int lane = tid & 31;
    const uint32_t st = sb + warp * 1024 + (lane & 15) * 48 + (lane >> 4) * 16, ld = sb + warp * 1024 + (lane >> 1) * 48 + (lane & 1) * 16;
    bf16* out = P.out + (size_t)((TAIL0 + (cta >> 4)) * 128 + warp * 16 + (lane >> 1)) * (2 * DM) + DM + n * 192 + q * 16 + (lane & 1) * 8;
#pragma unroll 1
    for (int i = 0; i < (q < 2 ? 3 : 2); i++) {
      uint32_t v[5][4], r[4];
#pragma unroll
      for (int p = 0; p < 5; p++) lds4(v[p], sb + R_RED + (p - 1) * 12288 + i * 4096 + tid * 16);
#pragma unroll
      for (int j = 0; j < 4; j++)
        r[j] = pack2((blo(v[0][j]) + blo(v[1][j])) + (blo(v[2][j]) + blo(v[3][j])) + blo(v[4][j]), (bhi(v[0][j]) + bhi(v[1][j])) + (bhi(v[2][j]) + bhi(v[3][j])) + bhi(v[4][j]));
      stsm4(st + i * 8192, r[0], r[1], r[2], r[3]);
      __syncwarp();
      lds4(r, ld + i * 8192);
      asm volatile("{.reg .pred p; setp.ne.s32 p,%5,15; @p st.global.v4.b32 [%0],{%1,%2,%3,%4};}" ::"l"(out + i * 80), "r"(r[0]), "r"(r[1]), "r"(r[2]), "r"(r[3]), "r"(rk) : "memory");
    }
  }
}

template <int K> DEVI void v_resident(uint32_t (*F)[4], uint32_t wv) {
  if constexpr (K < 36) { if (VIdx<K>::r == 'r') ldsm4t(F[VIdx<K>::v], wv + K * 2048); v_resident<K + 1>(F, wv); }
}
template <int K> DEVI void v_pass(float* acc, const uint32_t (*F)[4], uint64_t da, uint64_t db, uint32_t xf, uint32_t t, uint32_t nrel) {
  if constexpr (K < 36) {
    wg_fence();
    if (VIdx<K>::r == 'r') wg_rs40(acc, F[VIdx<K>::v], db + (K >> 2) * 320 + (K & 3) * 2, K);
    else wg_ss40<0>(acc, da + K * 128, db + (K >> 2) * 320 + (K & 3) * 2, K);
    wg_commit();
    if constexpr (VIdx<K>::p != '-') wg_wait<VIdx<K>::p - '0'>();
    if (K == XG * 4 - 1 + XW) { wg_wait<XW>(); asm volatile("{.reg .pred p; .reg .b32 a; setp.lt.u32 p,%1,%2; @p mapa.shared::cluster.u32 a,%0,%1; @p mbarrier.arrive.shared::cluster.b64 _,[a];}" ::"r"(xf), "r"(t), "r"(nrel) : "memory"); }
    v_pass<K + 1>(acc, F, da, db, xf, t, nrel);
  }
}
DEVI void rec_aux(const RecParams& P, const uint32_t sb, const int cta) {
  const int tid = pin(threadIdx.x);
  {
    uint4 v[5];
#pragma unroll
    for (int j = 0; j < 5; j++) if (j * 128 + tid - 256 < 576) v[j] = ((const uint4*)P.mem0)[j * 128 + tid - 256];
    if (tid == 288) {
      const uint32_t t0 = clk32();
      while (clk32() - t0 < (uint32_t)WOD) {}
#pragma unroll 1
      for (int i = 0; i < 4; i++) tma_load(sb + R_WO + i * 18432, &P.wo, (cta & 3) * 144, (cta ^ i) * 64, sb + B_W3);
      if (WVP) for (int i = 0; i < 3; i++) asm volatile("cp.async.bulk.prefetch.tensor.2d.L2.global [%0,{%1,%2}];" ::"l"(&P.wv), "r"(cta * 64), "r"(i * 192) : "memory");
    }
    __syncwarp();
    bar_sync(N_INIT1, 256);
#pragma unroll
    for (int j = 0; j < 5; j++) {
      const int i = j * 128 + tid - 256, t = i / 72, c = i - t * 72;
      if (i < 576) sts4(sb + R_H + (c >> 3) * 5120 + t * 128 + (((c & 7) ^ t) << 4), v[j].x, v[j].y, v[j].z, v[j].w);
    }
    fence_async();
    bar_arrive(N_SUM, 384);
    cluster_sync_relaxed();
    if (tid == 288) {
      if ((cta & 15) < 9) x_load(P, sb, cta & 15, 0);
#pragma unroll 1
      for (int i = 0; i < 3; i++) tma_load(sb + R_WV + i * 24576, &P.wv, cta * 64, i * 192, sb + B_W2);
    }
    __syncwarp();
    TL_END(12)
    wo_convert(sb, threadIdx.x & 31);
    bar_sync(N_O, 128);
    bar_arrive(N_INIT2, 384);
    TL_END(10)
  }
  const int rk = cta & 15, w4 = __shfl_sync(~0u, (threadIdx.x >> 5) & 3, 0);
  const uint32_t yg = pin((((threadIdx.x >> 5) & 3) * 16 + rk) * 1024 + ((threadIdx.x >> 4) & 1) * 128 + (threadIdx.x & 3) * 32 + ((threadIdx.x >> 2) & 3) * 8);
  uint32_t F[VB][4];
  mbar_wait(sb + B_W2, 0);
  TL_END(7)
  if (LATE == 2) pdl_trigger();
  v_resident<0>(F, sb + R_WV + ((tid & 7) + ((tid >> 4) & 1) * 8) * 128 + (((w4 * 2 + ((tid >> 3) & 1)) ^ (tid & 7)) << 4));
  LT(0)
  for (int s = 0; s < NSEG; s++) {
    const bool last = s == NSEG - 1;
    uint32_t va[12], p[5];
    int lane = opq(tid) & 31;
    {
      float acc[20];
      const uint64_t da = mkdesc(sb + R_WV, 0, 1024, 1), db = mkdesc(sb + R_H, 16, 1024, 1);
      PT(0)
      if (AW && tid == 320) {
        mbar_wait(sb + B_XA, s & 1); mbar_wait(sb + B_XB, s & 1); mbar_wait(sb + B_Z0, (s - 1) & 1); mbar_wait(sb + B_Z1, (s - 1) & 1);
        arm_step(sb, s);
      }
      bar_sync(N_S, 256);
      asm volatile("fence.proxy.async::generic.acquire.sync_restrict::shared::cluster.cluster;" ::: "memory");
      v_pass<0>(acc, F, da, db, sb + B_XF, tid - 256, last ? 0 : XG);
      PT(13)
      bar_sync(N_PM, 160);
      lds4(p, sb + R_P + 2560 + lane * 16); p[4] = lds1(sb + R_P + 3072 + lane * 4);
      wg_wait<0>();
      PT(1)
#pragma unroll
      for (int i = 0; i < 10; i++) va[i < 2 ? i + 8 : i - 2] = pack2(acc[2 * i], acc[2 * i + 1]);
      va[10] = va[11] = 0;
    }
    lane = opq(tid) & 31;
    if (!last) {
      const uint32_t uo = R_U + w4 * 256 + lane * 4;
      float a[4] = {0, 0, 0, 0}, b[4] = {0, 0, 0, 0}, c[4] = {0, 0, 0, 0};
      mma16(a, va[0], va[1], va[2], va[3], p[0], p[1]); mma16(b, va[4], va[5], va[6], va[7], p[2], p[3]); mma8(c, va[8], va[9], p[4]);
      const uint32_t u0 = pack2(a[0] + b[0] + c[0], a[1] + b[1] + c[1]), u1 = pack2(a[2] + b[2] + c[2], a[3] + b[3] + c[3]);
      if (!UO) { sts1(sb + uo, u0); sts1(sb + uo + 128, u1); __syncwarp(); if (lane == 0) mbar_arrive(sb + B_V); }
#pragma unroll
      for (int q = 1; q < 4; q++) { const uint32_t rs = mapa(sb, rk ^ q); sta1(rs + uo + q * 1024, u0, rs + B_U); sta1(rs + uo + q * 1024 + 128, u1, rs + B_U); }
      if (UO) { sts1(sb + uo, u0); sts1(sb + uo + 128, u1); __syncwarp(); if (lane == 0) mbar_arrive(sb + B_V); }
      asm volatile("{.reg .pred p; .reg .b32 a; setp.lt.u32 p,%1,%3; @p mapa.shared::cluster.u32 a,%0,%2; @p mbarrier.arrive.shared::cluster.b64 _,[a];}" ::"r"(sb + B_XF), "r"(tid - 256 - XG), "r"(tid - 256), "r"(last ? 0 : 9 - XG) : "memory");
      PT(4)
      if (w4 == 3) {
        wo_tile<0, 4, 4, 2>(nullptr, sb, 8, cta, lane, y_offset(cta, 8, lane), s);
      } else if (tid == 288 && rk < 9 && (!XI || rk >= XG) && !last) { mbar_wait(sb + B_XF, s & 1); x_load(P, sb, rk, s + 1); }
      PT(2)
    }
    lane = opq(tid) & 31;
    const uint8_t* y = (const uint8_t*)g_Y + (s & 1) * YSLOT + yg;
    uint32_t w0[8], w1[8], w2[8], ox[8];
    {
      float o[16];
      const uint64_t dp = mkdesc(sb + R_P, 128, 640, 0);
      bar_sync(N_WO, 384);
      wg_fence();
      wg_rs32(o, va, dp, 0); wg_rs32(o, va + 4, dp + 16, 1); wg_rs32(o, va + 8, mkdesc(sb + R_P + 512, 0, 640, 0), 1);
      wg_commit();
      const uint32_t tu = clk32();
      wg_wait<0>();
      PT(3)
#pragma unroll
      for (int i = 0; i < 8; i++) ox[i] = pack2(o[2 * i], o[2 * i + 1]);
      while (clk32() - tu < (uint32_t)YD) {}
      y_load(w0, y); y_load(w1, y + 4 * 16384);
      if (w4 == 0) y_load(w2, y + 8 * 16384);
      else {
#pragma unroll
        for (int i = 0; i < 8; i++) w2[i] = ((s >> 1) & 1) ^ 1;
      }
      PT(5)
    }
    if (!last) {
      const uint32_t dst = R_H + w4 * 5120 + (rk >> 1) * 128 + ((((rk & 1) * 4 + (lane >> 3)) ^ (rk >> 1)) << 4) + (lane & 4) * 2;
      const uint32_t tag = ((s >> 1) & 1) ^ 1, sel = (lane & 4) ? 0x3f800000u : 0x3f80u;
      uint32_t r0[2], r1[2], r2[2];
#pragma unroll 1
      for (int it = 0; (y_missing(w0, tag) | y_missing(w1, tag) | y_missing(w2, tag)) && it < (1 << 20); it++) {
        y_reload(w0, y, tag); y_reload(w1, y + 4 * 16384, tag); y_reload(w2, y + 8 * 16384, tag);
      }
      PT(7) GT(3)
      y_sum(r0, w0, sel); y_sum(r1, w1, sel); y_sum(r2, w2, sel);
      if (KA < 36 && SL == 0) bar_arrive(N_SUM + zero_after(__uint_as_float(r2[0])), 384);
      y_send(r0, sb, dst, B_Z0, lane, rk);
      if (KA < 36 && SL == 1) bar_arrive(N_SUM, 384);
      if (KA < 36 && SL == 3) bar_sync(N_SUM, 384);
      y_send(r1, sb, dst + 4 * 5120, B_Z1, lane, rk);
      if (w4 == 0) y_send(r2, sb, dst + 8 * 5120, B_Z1, lane, rk);
      if (SL == 2) bar_arrive(N_SUM, 384);
      PT(9) GT(4)
    }
#pragma unroll
    for (int h = 0; h < 2; h++) stsm4t(sb + R_OX + lane * 128 + (((w4 * 2 + h) ^ (lane & 7)) << 4), ox[h], ox[2 + h], ox[4 + h], ox[6 + h]);
    if (last) break;
    fence_async();
    bar_arrive(N_O, 160);
    PT(11)
  }
  fence_async();
  bar_sync(N_O, 160);
  if (tid == 256) {
    tma_store(&P.ctx, sb + R_OX, cta * 64, SEQ - 32); bulk_commit(); bulk_wait<0>(); CT(2, 0) signal_after_bulk(S_CTXB + 15); CT(2, 1)
  }
  __syncwarp();
  LT(1)
  asm volatile("barrier.cluster.arrive.relaxed.aligned;" ::: "memory");
  if (tid == 256) {
    const int m = TAIL0 + (cta >> 4), n = rk / 5, q = rk - n * 5;
    mbar_expect(sb + B_R, rk == 15 ? 9 * 4096 : q < 2 ? 12 * 4096 : 8 * 4096);
    if (rk < 15) out_produce<4, false>(P.o, sb, sb + B_O, m, n, q * 13, q == 4 ? 12 : 13, S_CTXB + m);
  }
  __syncwarp();
  asm volatile("barrier.cluster.wait.aligned;" ::: "memory");
}

__global__ void __launch_bounds__(384, 1) rec_kernel(const __grid_constant__ RecParams P) {
  extern __shared__ __align__(1024) uint8_t smem_raw[];
  const uint32_t sb = s2u(smem_raw);
  const int tid = threadIdx.x, cta = blockIdx.x;
  TL_START(1)
  if (!LATE) pdl_trigger();
  if (tid == 0) {
    for (int i = 0; i < 22; i++) mbar_init(sb + R_BAR + 8 * i, 8 * i == B_XF - R_BAR ? 16 : 8 * i == B_V - R_BAR ? 4 : i >= 16 && i < 20 ? 2 : 1);
    asm volatile("fence.mbarrier_init.release.cluster;" ::: "memory");
    asm volatile("cp.async.bulk.prefetch.L2.global [%0],%1;" ::"l"(P.x_raw + cta * DM), "r"(DM * 2) : "memory");
    mbar_expect(sb + B_W0, 73728); mbar_expect(sb + B_W1, 73728); mbar_expect(sb + B_W2, 73728); mbar_expect(sb + B_W3, 73728);
#pragma unroll 1
    for (int i = 0; i < 3; i++) { tma_load(sb + R_WV + i * 24576, &P.wq, cta * 64, i * 192, sb + B_W0); tma_load(sb + R_H + i * 24576, &P.wk, cta * 64, i * 192, sb + B_W1); }
    mbar_expect(sb + B_XA, XG * 4096); mbar_expect(sb + B_XB, (9 - XG) * 4096);
  }
  __syncthreads();
  if (tid >= 256) { reg_dec<504 - 2 * RP>(); rec_aux(P, sb, cta); }
  else { reg_inc<RP>(); rec_proj(P, sb, cta); }
  TL_END(1)
  if (tid == 0) CT(7, 2)
  cluster_sync_relaxed();
}
typedef CUresult (*EncFn)(CUtensorMap*, CUtensorMapDataType, cuuint32_t, void*, const cuuint64_t*, const cuuint64_t*, const cuuint32_t*, const cuuint32_t*,
                          CUtensorMapInterleave, CUtensorMapSwizzle, CUtensorMapL2promotion, CUtensorMapFloatOOBfill);
static EncFn g_enc;
static CUtensorMap mk(const void* p, uint64_t cols, uint64_t rows, uint64_t pitch_elems, uint32_t box_rows, uint32_t box_cols = 64) {
  CUtensorMap m;
  cuuint64_t dim[2] = {cols, rows}, str[1] = {pitch_elems * 2};
  cuuint32_t box[2] = {box_cols, box_rows}, es[2] = {1, 1};
  g_enc(&m, CU_TENSOR_MAP_DATA_TYPE_BFLOAT16, 2, (void*)p, dim, str, box, es, CU_TENSOR_MAP_INTERLEAVE_NONE, box_cols == 64 ? CU_TENSOR_MAP_SWIZZLE_128B : CU_TENSOR_MAP_SWIZZLE_NONE,
        CU_TENSOR_MAP_L2_PROMOTION_L2_256B, CU_TENSOR_MAP_FLOAT_OOB_FILL_NONE);
  return m;
}
template <class T> static void* sym(T& s) { void* p; cudaGetSymbolAddress(&p, s); return p; }

#define FE 6
#define STG 10
#define FHC 22
#define FSL 4
#define NOE 6
#define OMC true
template <class K, class A> static void launch(K k, int grid, int smem, int cluster, bool pdl, const A& arg) {
  cudaLaunchConfig_t c = {};
  cudaLaunchAttribute at[2];
  int n = 0;
  if (cluster > 1) { at[n].id = cudaLaunchAttributeClusterDimension; at[n].val.clusterDim.x = cluster; at[n].val.clusterDim.y = at[n].val.clusterDim.z = 1; n++; }
  if (pdl) { at[n].id = cudaLaunchAttributeProgrammaticStreamSerialization; at[n].val.programmaticStreamSerializationAllowed = 1; n++; }
  c.gridDim = grid; c.blockDim = 384; c.dynamicSmemBytes = smem; c.stream = cudaStreamPerThread; c.attrs = at; c.numAttrs = n;
  cudaLaunchKernelEx(&c, k, arg);
}

extern "C" void kernel_launch(void* const* d_in, const int* in_sizes, int n_in, void* d_out, int out_size) {
  static int nb;
  if (!g_enc) {
    cudaDriverEntryPointQueryResult qr;
    cudaGetDriverEntryPoint("cuTensorMapEncodeTiled", (void**)&g_enc, cudaEnableDefault, &qr);
    cudaDeviceGetAttribute(&nb, cudaDevAttrMultiProcessorCount, 0);
    nb = nb - 64 < 16 ? 16 : nb - 64 > 128 ? 128 : (nb - 64) & ~1;
    cudaFuncSetAttribute(proj_kernel, cudaFuncAttributeMaxDynamicSharedMemorySize, SM_P);
    cudaFuncSetAttribute(out_kernel<false>, cudaFuncAttributeMaxDynamicSharedMemorySize, SM_O);
    cudaFuncSetAttribute(out_kernel<true>, cudaFuncAttributeMaxDynamicSharedMemorySize, SM_O);
    cudaFuncSetAttribute(fa_kernel, cudaFuncAttributeMaxDynamicSharedMemorySize, SM_F);
    cudaFuncSetAttribute(rec_kernel, cudaFuncAttributeMaxDynamicSharedMemorySize, R_END);
    cudaFuncSetAttribute(rec_kernel, cudaFuncAttributeNonPortableClusterSizeAllowed, 1);
  }
  const bf16 *Ax = (const bf16*)d_in[0], *Ac = (const bf16*)d_in[1], *Awq = (const bf16*)d_in[2], *Awk = (const bf16*)d_in[3], *Awv = (const bf16*)d_in[4],
             *Awo = (const bf16*)d_in[5], *Bx = (const bf16*)d_in[6], *Bm = (const bf16*)d_in[7], *Bwq = (const bf16*)d_in[8], *Bwk = (const bf16*)d_in[9],
             *Bwv = (const bf16*)d_in[10], *Bwo = (const bf16*)d_in[11];
  bf16* out = (bf16*)d_out;
  ProjParams p;
  p.a[0] = mk(Ac, 512, SEQ, 512, 128); p.a[1] = mk(Ax, DM, SEQ, DM, 128);
  p.w[0] = mk(Awk, HD, 512, HD, 64); p.w[1] = mk(Awv, HD, 512, HD, 64); p.w[2] = mk(Awq, HD, DM, HD, 64);
  p.c[0] = mk(sym(g_kA), HD, SEQ, HD, 64); p.c[1] = mk(sym(g_vA), HD, SEQ, HD, 64); p.c[2] = mk(sym(g_qA), HD, SEQ, HD, 64);
  {
    int parts[16];
    for (int i = 0; i < 16; i++) parts[i] = 1;
    for (int e = 0; e < nb / 2 - 16; e++) parts[e % 24 < 16 ? e % 8 : 15 - (e % 24 - 16)]++;
    p.nitems = 0;
    for (int i = 15; i >= 0; i--)
      for (int j = 0, nc = i < 8 ? 32 : 16, a = parts[i]; j < a; j++) {
        ProjItem& I = p.item[p.nitems++];
        I.pa = i >> 3; I.m = i & 7;
        I.c0[0] = j * nc / a; I.n[0] = (j + 1) * nc / a - I.c0[0];
        I.c0[1] = (j * nc + a - 1) / a; I.n[1] = ((j + 1) * nc + a - 1) / a - I.c0[1];
        if (i < 8 && a == 3) { const int d = STG * (i + 4) / 11, b1 = 11 - d, b2 = 22 - d + (i - 4) * STG / 16; I.c0[1] = j == 0 ? 0 : j == 1 ? b1 : b2; I.n[1] = (j == 0 ? b1 : j == 1 ? b2 : 32) - I.c0[1]; }
      }
  }
  OutParams o;
  for (int i = 0; i < 2; i++) {
    o.p[i].a = mk(i ? sym(g_ctxB) : sym(g_qA), HD, SEQ, HD, 128); o.p[i].b = mk(i ? Bwo : Awo, DM, HD, DM, 64); o.p[i].bh = mk(i ? Bwo : Awo, DM, HD, DM, 32);
    o.c[i] = mk(out + i * DM, DM, SEQ, 2 * DM, 64);
  }
  FaParams f;
  f.q = mk(sym(g_qA), HD, SEQ, HD, 128); f.k = mk(sym(g_kA), HD, SEQ, HD, 128); f.v = mk(sym(g_vA), HD, SEQ, HD, 128); f.o = mk(sym(g_qA), HD, SEQ, HD, 64);
  f.nctas = nb;
  for (int i = 0; i < 9; i++) f.nproj[i] = 0;
  for (int i = 0; i < p.nitems; i++) f.nproj[p.item[i].pa * (p.item[i].m + 1)] += 4;
  for (int key = -90, n = 0; n < 512; key++)
    for (int h = 0; h < 32; h++)
      for (int qt = 0; qt < 16; qt++)
        if ((h < FHC ? h : FHC) * FSL - qt * 2 - (qt >= 12 && h < FE ? 60 : 0) == key) f.order[n++] = qt * 32 + h;
  RecParams r;
  r.wq = mk(Bwq, HD, DM, HD, 192); r.wk = mk(Bwk, HD, DM, HD, 192); r.wv = mk(Bwv, HD, DM, HD, 192); r.wo = mk(Bwo, DM, HD, DM, 64, 144);
  r.x_raw = Bx;
  r.x = mk(Bx, DM, SEQ, DM, 32); r.ctx = mk(sym(g_ctxB), HD, SEQ, HD, 32); r.mem0 = Bm; r.o = o.p[1]; r.out = out;

  launch(rec_kernel, 64, R_END, 16, false, r);
  launch(proj_kernel, nb, SM_P, 2, true, p);
  launch(fa_kernel, nb - NOE * 3, SM_F, 1, true, f);
  o.m0 = 0; o.nb = NOE * 3; o.id = 4;
  launch(out_kernel<false>, o.nb, SM_O, 1, true, o);
  launch(fa_kernel, NOE * 3, SM_F, 1, true, f);
  o.m0 = NOE; o.nb = (TAIL0 - NOE) * 3; o.id = 5;
  launch(out_kernel<OMC>, o.nb + 48, SM_O, OMC ? 2 : 1, true, o);
}
```

```cpp
#include <cuda_runtime.h>
#include <cuda_bf16.h>
#include <cuda.h>
#include <stdint.h>

typedef __nv_bfloat16 bf16;
#define DEVI __device__ __forceinline__
#define WAIT_FAIL(code) break
#define WAIT_MAX (1 << 22)

constexpr int SEQ = 2048, HD = 4096, DM = 576, NSEG = 64;

__device__ __align__(1024) bf16 g_qA[SEQ * HD], g_kA[SEQ * HD], g_vA[SEQ * HD];
__device__ __align__(1024) bf16 g_ctxB[SEQ * HD];
__device__ __align__(1024) uint4 g_Y[2 * 9 * 16 * 64];
enum { S_QUEUE = 0, S_EXIT = 1, S_PROJ = 32, S_CTXA = 64, S_CTXB = 96 };
__device__ unsigned g_sync[128];
#define LT(i)
#define CT(k, i) {}
#define TL_START(i)
#define TL_END(i)

DEVI uint32_t s2u(const void* p) { return (uint32_t)__cvta_generic_to_shared(p); }
DEVI void mbar_init(uint32_t b, uint32_t c) { asm volatile("mbarrier.init.shared::cta.b64 [%0],%1;" ::"r"(b), "r"(c)); }
DEVI void mbar_expect(uint32_t b, uint32_t n) { asm volatile("mbarrier.arrive.expect_tx.shared::cta.b64 _,[%0],%1;" ::"r"(b), "r"(n) : "memory"); }
DEVI void mbar_arrive(uint32_t b) { asm volatile("mbarrier.arrive.shared::cta.b64 _,[%0];" ::"r"(b) : "memory"); }
DEVI void mbar_wait(uint32_t b, uint32_t ph) {
  uint32_t ok; int it = 0;
  do {
    asm volatile("{.reg .pred p; mbarrier.try_wait.parity.shared::cta.b64 p,[%1],%2; selp.u32 %0,1,0,p;}" : "=r"(ok) : "r"(b), "r"(ph) : "memory");
    if (!ok && ++it > WAIT_MAX) WAIT_FAIL(b & 0xffffff);
  } while (!ok);
}
DEVI bool mbar_try(uint32_t b, uint32_t ph) {
  uint32_t ok;
  asm volatile("{.reg .pred p; mbarrier.try_wait.parity.shared::cta.b64 p,[%1],%2; selp.u32 %0,1,0,p;}" : "=r"(ok) : "r"(b), "r"(ph) : "memory");
  return ok;
}
DEVI bool mbar_test(uint32_t b, uint32_t ph) {
  uint32_t ok;
  asm volatile("{.reg .pred p; mbarrier.test_wait.parity.shared::cta.b64 p,[%1],%2; selp.u32 %0,1,0,p;}" : "=r"(ok) : "r"(b), "r"(ph) : "memory");
  return ok;
}
DEVI void mwait(uint32_t b, uint32_t ph) { if (__builtin_expect(!mbar_try(b, ph), 0)) mbar_wait(b, ph); }
DEVI void tma_load(uint32_t dst, const CUtensorMap* tm, int c0, int c1, uint32_t bar) {
  asm volatile("cp.async.bulk.tensor.2d.shared::cluster.global.mbarrier::complete_tx::bytes [%0],[%1,{%3,%4}],[%2];" ::"r"(dst), "l"(tm), "r"(bar), "r"(c0), "r"(c1) : "memory");
}
DEVI void tma_store(const CUtensorMap* tm, uint32_t src, int c0, int c1) {
  asm volatile("cp.async.bulk.tensor.2d.global.shared::cta.bulk_group [%0,{%2,%3}],[%1];" ::"l"(tm), "r"(src), "r"(c0), "r"(c1) : "memory");
}
DEVI void bulk_commit() { asm volatile("cp.async.bulk.commit_group;" ::: "memory"); }
template <int N> DEVI void bulk_wait_read() { asm volatile("cp.async.bulk.wait_group.read %0;" ::"n"(N) : "memory"); }
template <int N> DEVI void bulk_wait() { asm volatile("cp.async.bulk.wait_group %0;" ::"n"(N) : "memory"); }
DEVI void fence_async() { asm volatile("fence.proxy.async.shared::cta;" ::: "memory"); }
DEVI void bar_sync(int id, int n) { asm volatile("bar.sync %0,%1;" ::"r"(id), "r"(n) : "memory"); }
DEVI void bar_arrive(int id, int n) { asm volatile("bar.arrive %0,%1;" ::"r"(id), "r"(n) : "memory"); }
template <int R> DEVI void reg_inc() { asm volatile("setmaxnreg.inc.sync.aligned.u32 %0;" ::"n"(R)); }
template <int R> DEVI void reg_dec() { asm volatile("setmaxnreg.dec.sync.aligned.u32 %0;" ::"n"(R)); }
DEVI void wg_fence() { asm volatile("wgmma.fence.sync.aligned;" ::: "memory"); }
DEVI void wg_commit() { asm volatile("wgmma.commit_group.sync.aligned;" ::: "memory"); }
template <int N> DEVI void wg_wait() { asm volatile("wgmma.wait_group.sync.aligned %0;" ::"n"(N) : "memory"); }
DEVI uint64_t desc_k(uint32_t a) { return (uint64_t)((a >> 4) & 0x3fff) | (1ull << 16) | (64ull << 32) | (1ull << 62); }
DEVI uint64_t desc_mn(uint32_t a, uint32_t lbo) { return (uint64_t)((a >> 4) & 0x3fff) | ((uint64_t)(lbo >> 4) << 16) | (64ull << 32) | (1ull << 62); }
DEVI uint32_t pack2(float lo, float hi) { uint32_t r; asm("cvt.rn.bf16x2.f32 %0,%1,%2;" : "=r"(r) : "f"(hi), "f"(lo)); return r; }
DEVI float ex2(float x) { float y; asm("ex2.approx.ftz.f32 %0,%1;" : "=f"(y) : "f"(x)); return y; }
DEVI void stsm4(uint32_t a, uint32_t r0, uint32_t r1, uint32_t r2, uint32_t r3) {
  asm volatile("stmatrix.sync.aligned.m8n8.x4.shared.b16 [%0],{%1,%2,%3,%4};" ::"r"(a), "r"(r0), "r"(r1), "r"(r2), "r"(r3) : "memory");
}
DEVI void ldsm4(uint32_t* r, uint32_t a) {
  asm volatile("ldmatrix.sync.aligned.m8n8.x4.shared.b16 {%0,%1,%2,%3},[%4];" : "=r"(r[0]), "=r"(r[1]), "=r"(r[2]), "=r"(r[3]) : "r"(a) : "memory");
}
DEVI void ldsm4t(uint32_t* r, uint32_t a) {
  asm volatile("ldmatrix.sync.aligned.m8n8.x4.trans.shared.b16 {%0,%1,%2,%3},[%4];" : "=r"(r[0]), "=r"(r[1]), "=r"(r[2]), "=r"(r[3]) : "r"(a) : "memory");
}
DEVI void mma16(float* d, uint32_t a0, uint32_t a1, uint32_t a2, uint32_t a3, uint32_t b0, uint32_t b1) {
  asm volatile("mma.sync.aligned.m16n8k16.row.col.f32.bf16.bf16.f32 {%0,%1,%2,%3},{%4,%5,%6,%7},{%8,%9},{%0,%1,%2,%3};"
               : "+f"(d[0]), "+f"(d[1]), "+f"(d[2]), "+f"(d[3]) : "r"(a0), "r"(a1), "r"(a2), "r"(a3), "r"(b0), "r"(b1));
}

DEVI void pdl_trigger() { asm volatile("griddepcontrol.launch_dependents;" ::: "memory"); }
DEVI void signal_after_bulk(int f) {
  asm volatile("fence.proxy.async.global;" ::: "memory");
  asm volatile("red.release.gpu.global.add.u32 [%0], 1;" ::"l"(g_sync + f) : "memory");
}
DEVI void flag_wait(int f, unsigned n, unsigned waiters) {
  for (int it = 0;; it++) {
    if (it > WAIT_MAX) WAIT_FAIL(f);
    unsigned v; asm volatile("ld.acquire.gpu.global.u32 %0, [%1];" : "=r"(v) : "l"(g_sync + f) : "memory");
    if (v >= n) break;
    __nanosleep(64);
  }
  if (waiters) asm volatile("red.relaxed.gpu.global.inc.u32 [%0], %1;" ::"l"(g_sync + f), "r"(n + waiters - 1) : "memory");
  asm volatile("fence.proxy.async.global;" ::: "memory");
}
DEVI uint32_t mapa(uint32_t a, uint32_t r) { uint32_t o; asm("mapa.shared::cluster.u32 %0,%1,%2;" : "=r"(o) : "r"(a), "r"(r)); return o; }
DEVI void tma_load_mc(uint32_t dst, const CUtensorMap* tm, int c0, int c1, uint32_t bar, uint16_t mask) {
  asm volatile("cp.async.bulk.tensor.2d.shared::cluster.global.mbarrier::complete_tx::bytes.multicast::cluster [%0],[%1,{%3,%4}],[%2],%5;" ::"r"(dst), "l"(tm), "r"(bar), "r"(c0), "r"(c1), "h"(mask) : "memory");
}
DEVI void arrive_pair(uint32_t b) { if ((threadIdx.x & 127) < 2) asm volatile("mbarrier.arrive.shared::cluster.b64 _,[%0];" ::"r"(mapa(b, threadIdx.x & 1)) : "memory"); }
DEVI void cluster_sync_relaxed() { asm volatile("barrier.cluster.arrive.relaxed.aligned; barrier.cluster.wait.aligned;" ::: "memory"); }
DEVI void cluster_sync() { asm volatile("barrier.cluster.arrive.aligned; barrier.cluster.wait.aligned;" ::: "memory"); }
DEVI void sts4(uint32_t a, uint32_t x, uint32_t y, uint32_t z, uint32_t w) { asm volatile("st.shared.v4.b32 [%0],{%1,%2,%3,%4};" ::"r"(a), "r"(x), "r"(y), "r"(z), "r"(w) : "memory"); }
DEVI void lds4(uint32_t* r, uint32_t a) { asm volatile("ld.shared.v4.b32 {%0,%1,%2,%3},[%4];" : "=r"(r[0]), "=r"(r[1]), "=r"(r[2]), "=r"(r[3]) : "r"(a) : "memory"); }
DEVI void sta4(uint32_t d, uint32_t a, uint32_t b, uint32_t c, uint32_t e, uint32_t bar) {
  asm volatile("st.async.weak.shared::cluster.mbarrier::complete_tx::bytes.v4.b32 [%0],{%1,%2,%3,%4},[%5];" ::"r"(d), "r"(a), "r"(b), "r"(c), "r"(e), "r"(bar) : "memory");
}
DEVI float blo(uint32_t u) { return __uint_as_float(u << 16); }
DEVI float bhi(uint32_t u) { return __uint_as_float(u & 0xffff0000u); }

#define F8(a, o) "+f"(a[o]), "+f"(a[o + 1]), "+f"(a[o + 2]), "+f"(a[o + 3]), "+f"(a[o + 4]), "+f"(a[o + 5]), "+f"(a[o + 6]), "+f"(a[o + 7])
#define F32(a, o) F8(a, o), F8(a, o + 8), F8(a, o + 16), F8(a, o + 24)
template<int TB> DEVI void wg_ss128(float* d, uint64_t da, uint64_t db, int acc){
 asm volatile("{.reg .pred p; setp.ne.b32 p,%66,0;\n wgmma.mma_async.sync.aligned.m64n128k16.f32.bf16.bf16 {%0,%1,%2,%3,%4,%5,%6,%7,%8,%9,%10,%11,%12,%13,%14,%15,%16,%17,%18,%19,%20,%21,%22,%23,%24,%25,%26,%27,%28,%29,%30,%31,%32,%33,%34,%35,%36,%37,%38,%39,%40,%41,%42,%43,%44,%45,%46,%47,%48,%49,%50,%51,%52,%53,%54,%55,%56,%57,%58,%59,%60,%61,%62,%63},%64,%65,p,1,1,0,%67;}"
 : F32(d,0),F32(d,32) : "l"(da),"l"(db),"r"(acc),"n"(TB));}
template<int TB> DEVI void wg_ss192(float* d, uint64_t da, uint64_t db, int acc){
 asm volatile("{.reg .pred p; setp.ne.b32 p,%98,0;\n wgmma.mma_async.sync.aligned.m64n192k16.f32.bf16.bf16 {%0,%1,%2,%3,%4,%5,%6,%7,%8,%9,%10,%11,%12,%13,%14,%15,%16,%17,%18,%19,%20,%21,%22,%23,%24,%25,%26,%27,%28,%29,%30,%31,%32,%33,%34,%35,%36,%37,%38,%39,%40,%41,%42,%43,%44,%45,%46,%47,%48,%49,%50,%51,%52,%53,%54,%55,%56,%57,%58,%59,%60,%61,%62,%63,%64,%65,%66,%67,%68,%69,%70,%71,%72,%73,%74,%75,%76,%77,%78,%79,%80,%81,%82,%83,%84,%85,%86,%87,%88,%89,%90,%91,%92,%93,%94,%95},%96,%97,p,1,1,0,%99;}"
 : F32(d,0),F32(d,32),F32(d,64) : "l"(da),"l"(db),"r"(acc),"n"(TB));}
template<int TB> DEVI void wg_rs128(float* d, const uint32_t* a, uint64_t db, int acc){
 asm volatile("{.reg .pred p; setp.ne.b32 p,%69,0;\n wgmma.mma_async.sync.aligned.m64n128k16.f32.bf16.bf16 {%0,%1,%2,%3,%4,%5,%6,%7,%8,%9,%10,%11,%12,%13,%14,%15,%16,%17,%18,%19,%20,%21,%22,%23,%24,%25,%26,%27,%28,%29,%30,%31,%32,%33,%34,%35,%36,%37,%38,%39,%40,%41,%42,%43,%44,%45,%46,%47,%48,%49,%50,%51,%52,%53,%54,%55,%56,%57,%58,%59,%60,%61,%62,%63},{%64,%65,%66,%67},%68,p,1,1,%70;}"
 : F32(d,0),F32(d,32) : "r"(a[0]),"r"(a[1]),"r"(a[2]),"r"(a[3]),"l"(db),"r"(acc),"n"(TB));}
struct ProjItem { uint8_t pa, m, c0[2], n[2]; };
struct ProjParams { CUtensorMap a[2], w[3], c[3]; ProjItem item[64]; int nitems; };
constexpr int PST = 12, SM_P = PST * 16384 + 32768 + 256;
DEVI void proj_decode(const ProjItem& I, int t, int& pw, int& n) {
  const int g = t >= I.n[0], c = g ? I.c0[1] + t - I.n[0] : I.c0[0] + t;
  pw = I.pa ? 2 : c >> 4; n = (c & 15) + g * 16;
}
__global__ void __launch_bounds__(384, 1) proj_kernel(const __grid_constant__ ProjParams P) {
  extern __shared__ __align__(1024) uint8_t smem_raw[];
  const uint32_t base = __shfl_sync(~0u, s2u(smem_raw), 0), stg = base + PST * 16384, full = stg + 32768, empty = full + 8 * PST, of = empty + 8 * PST, oe = of + 16;
  const int tid = threadIdx.x, wg = __shfl_sync(~0u, tid >> 7, 0);
  TL_START(2)
  pdl_trigger();
  if (tid == 0) {
    for (int i = 0; i < PST; i++) { mbar_init(full + 8 * i, 1); mbar_init(empty + 8 * i, 4); }
    for (int i = 0; i < 2; i++) { mbar_init(of + 8 * i, 4); mbar_init(oe + 8 * i, 1); }
    asm volatile("fence.mbarrier_init.release.cluster;" ::: "memory");
  }
  cluster_sync_relaxed();
  if (wg == 2) {
    reg_dec<24>();
    const int r = blockIdx.x & 1;
    if (tid == 256) {
      int s = 0, ph = 1;
      for (int it = blockIdx.x >> 1; it < P.nitems; it += gridDim.x >> 1) {
        const ProjItem& I = P.item[it];
        const int nk = 8 + I.pa;
        for (int t = -1; t < I.n[0] + I.n[1]; t++) {
          int pw, n; proj_decode(I, t, pw, n);
          for (int k = 0; k < nk; k++) {
            mbar_wait(empty + 8 * s, ph);
            mbar_expect(full + 8 * s, 16384);
            if (t < 0) tma_load(base + s * 16384, &P.a[I.pa], k * 64, (I.m * 2 + r) * 128, full + 8 * s);
            else tma_load_mc(base + s * 16384 + r * 8192, &P.w[pw], n * 128 + r * 64, k * 64, full + 8 * s, 3);
            if (++s == PST) { s = 0; ph ^= 1; }
          }
        }
      }
      for (int i = 0; i < PST; i++) { mbar_wait(empty + 8 * s, ph); if (++s == PST) { s = 0; ph ^= 1; } }
    } else if (tid == 288 || tid == 320) {
      const int g = tid == 320;
      int c = 0;
      for (int it = blockIdx.x >> 1; it < P.nitems; it += gridDim.x >> 1) {
        const ProjItem& I = P.item[it];
        for (int t = 0; t < I.n[0] + I.n[1]; t++, c++) {
          int pw, n; proj_decode(I, t, pw, n);
          mbar_wait(of + 8 * g, c & 1);
          tma_store(&P.c[pw], stg + g * 16384, n * 128, (I.m * 2 + r) * 128 + g * 64);
          tma_store(&P.c[pw], stg + g * 16384 + 8192, n * 128 + 64, (I.m * 2 + r) * 128 + g * 64);
          bulk_commit();
          bulk_wait_read<0>();
          mbar_arrive(oe + 8 * g);
          if (t == 3 && !g) CT(0, 1)
          if (t == I.n[0] - 1) { bulk_wait<0>(); signal_after_bulk(S_PROJ + I.pa * (I.m + 1) * 2); }
        }
        bulk_wait<0>(); signal_after_bulk(S_PROJ + I.pa * (I.m + 1) * 2 + 1);
      }
      if (!g) CT(0, 2)
    }
  } else {
    reg_inc<240>();
    uint32_t A[36][4];
    float acc[64];
    uint32_t s = 0, ph = 0, c = 1;
    const uint32_t row = ((tid >> 5) & 3) * 16 + (tid & 15);
    const uint32_t roff = row * 128 + ((((tid >> 4) & 1) ^ (row & 7)) << 4);
    const uint32_t rel = mapa(empty, tid & 1);
    auto release = [&](uint32_t st) { asm volatile("{.reg .pred p; setp.lt.u32 p,%1,2; @p mbarrier.arrive.shared::cluster.b64 _,[%0];}" ::"r"(rel + 8 * st), "r"(tid & 127) : "memory"); };
    for (int it = blockIdx.x >> 1; it < P.nitems; it += gridDim.x >> 1) {
      const int pa = P.item[it].pa, nt = P.item[it].n[0] + P.item[it].n[1];
#pragma unroll
      for (int k = 0; k < 9; k++) {
        if (k < 8 || pa) {
          mbar_wait(full + 8 * s, ph);
#pragma unroll
          for (int kk = 0; kk < 4; kk++) ldsm4(A[4 * k + kk], base + s * 16384 + wg * 8192 + (roff ^ (kk * 32)));
          bar_sync(1 + wg, 128);
          release(s);
          if (++s == PST) { s = 0; ph ^= 1; }
        }
      }
      if (tid == 0) CT(0, 0)
      if (wg) bar_sync(3, 256);
      bool ok = false;
      for (int t = 0; t < nt; t++, c ^= 1) {
        uint32_t p1 = 0;
#pragma unroll
        for (int k = 0; k < 9; k++) {
          if (k < 8 || pa) {
            if (!ok) mbar_wait(full + 8 * s, ph);
            const uint64_t db = desc_mn(base + s * 16384, 8192);
            wg_fence();
#pragma unroll
            for (int kk = 0; kk < 4; kk++) wg_rs128<1>(acc, A[4 * k + kk], db + kk * 128, k | kk);
            wg_commit();
            const uint32_t cur = s;
            if (++s == PST) { s = 0; ph ^= 1; }
            ok = mbar_test(full + 8 * s, ph);
            if (k) { wg_wait<1>(); release(p1); }
            if (k == 4 && t == 0 && !wg) bar_arrive(3, 256);
            p1 = cur;
          }
        }
        mwait(oe + 8 * wg, c);
        wg_wait<0>();
        release(p1);
#pragma unroll
        for (int i = 0; i < 8; i++) {
          const float* a = acc + i * 8;
          stsm4(stg + wg * 16384 + (i >> 2) * 8192 + (roff ^ ((i & 3) * 32)), pack2(a[0], a[1]), pack2(a[2], a[3]), pack2(a[4], a[5]), pack2(a[6], a[7]));
        }
        fence_async();
        __syncwarp();
        if ((tid & 31) == 0) mbar_arrive(of + 8 * wg);
      }
    }
  }
}

struct OutMaps { CUtensorMap a, b, bh; };
constexpr int OSB = 40960;
template <int NST, bool MC> DEVI void out_produce(const OutMaps& M, uint32_t base, uint32_t full, int m, int n, int k0, int nk, int flag = -1) {
  const int r = MC ? blockIdx.x & 1 : 0;
  int s = 0, ph = 1;
#pragma unroll 1
  for (int k = 0; k < nk + (MC ? NST - 1 : 0); k++) {
    mbar_wait(full + 8 * (NST + s), ph);
    if (k < nk) {
      mbar_expect(full + 8 * s, OSB);
#pragma unroll 1
      for (int j = 0; j < 3; j++) {
        if (MC) tma_load_mc(base + s * OSB + 16384 + j * 8192 + r * 4096, &M.bh, n * 192 + j * 64, (k0 + k) * 64 + r * 32, full + 8 * s, 3);
        else tma_load(base + s * OSB + 16384 + j * 8192, &M.b, n * 192 + j * 64, (k0 + k) * 64, full + 8 * s);
      }
      if (flag >= 0 && k == 0) flag_wait(flag, 64, 15);
      if (flag >= 0 || k >= NST) tma_load(base + s * OSB, &M.a, (k0 + k) * 64, m * 128, full + 8 * s);
    }
    if (++s == NST) { s = 0; ph ^= 1; }
  }
}
template <int NST> DEVI void out_first(const OutMaps& M, uint32_t base, uint32_t full, int m, int k0, int nk, int flag) {
  flag_wait(flag, 64, 3);
#pragma unroll 1
  for (int k = 0; k < NST; k++) tma_load(base + k * OSB, &M.a, (k0 + k) * 64, m * 128, full + 8 * k);
}
template <int NST, bool MC> DEVI void out_consume(float* acc, uint32_t base, uint32_t full, int nk) {
  const uint32_t empty = full + 8 * NST;
  const int wg = threadIdx.x >> 7;
  int s = 0, ph = 0, prev = 0;
#pragma unroll 1
  for (int k = 0; k < nk; k++) {
    mbar_wait(full + 8 * s, ph);
    const uint64_t da = desc_k(base + s * OSB + wg * 8192), db = desc_mn(base + s * OSB + 16384, 8192);
    wg_fence();
#pragma unroll
    for (int kk = 0; kk < 4; kk++) wg_ss192<1>(acc, da + kk * 2, db + kk * 128, k | kk);
    wg_commit();
    if (k) { wg_wait<1>(); if (MC) arrive_pair(empty + 8 * prev); else if ((threadIdx.x & 127) == 0) mbar_arrive(empty + 8 * prev); }
    prev = s;
    if (++s == NST) { s = 0; ph ^= 1; }
  }
  wg_wait<0>();
}
struct OutParams { OutMaps p[2]; CUtensorMap c[2]; int m0, nb, id; };
#define OST 4
constexpr int SM_O = 5 * OSB + 256;
template <bool MC> __global__ void __launch_bounds__(384, 1) out_kernel(const __grid_constant__ OutParams P) {
  extern __shared__ __align__(1024) uint8_t smem_raw[];
  const uint32_t base = s2u(smem_raw), full = base + OST * OSB;
  const int tid = threadIdx.x, wg = tid >> 7;
  const int pb = (int)blockIdx.x < P.nb, t = pb ? blockIdx.x : 47 - (blockIdx.x - P.nb);
  const int m = (pb ? P.m0 : 0) + (MC ? t / 6 * 2 + (t & 1) : t / 3), n = MC ? (t >> 1) % 3 : t % 3;
  TL_START(P.id)
  pdl_trigger();
  if (tid == 0) {
    for (int i = 0; i < OST; i++) { mbar_init(full + 8 * i, 1); mbar_init(full + 8 * (OST + i), MC ? 4 : 2); }
    asm volatile("fence.mbarrier_init.release.cluster;" ::: "memory");
  }
  if (MC) cluster_sync_relaxed(); else __syncthreads();
  if (wg == 2) {
    if (tid == 256) out_produce<OST, MC>(P.p[pb], base, full, m, n, 0, 64);
    if (tid == 288) out_first<OST>(P.p[pb], base, full, m, 0, 64, (pb ? S_CTXB : S_CTXA) + m);
  } else {
    float acc[96];
    if (tid == 0) CT(P.id, 0)
    out_consume<OST, MC>(acc, base, full, 64);
    if (tid == 0) CT(P.id, 2)
    bar_sync(3, 256);
    const uint32_t row = ((tid >> 5) & 3) * 16 + (tid & 15);
    const uint32_t roff = row * 128 + ((((tid >> 4) & 1) ^ (row & 7)) << 4);
#pragma unroll
    for (int i = 0; i < 12; i++) {
      const float* a = acc + i * 8;
      stsm4(base + wg * 24576 + (i >> 2) * 8192 + (roff ^ ((i & 3) * 32)), pack2(a[0], a[1]), pack2(a[2], a[3]), pack2(a[4], a[5]), pack2(a[6], a[7]));
    }
    fence_async();
    bar_sync(1 + wg, 128);
    if ((tid & 127) == 0) {
      for (int c = 0; c < 3; c++) tma_store(&P.c[pb], base + wg * 24576 + c * 8192, n * 192 + c * 64, m * 128 + wg * 64);
      bulk_commit();
      bulk_wait<0>();
    }
    TL_END(P.id)
  }
}
struct FaParams { CUtensorMap q, k, v, o; unsigned nctas; uint8_t nproj[12]; uint16_t order[512]; };
constexpr int SM_F = 7 * 32768 + 256;
constexpr float FA_C = 0.08838834764831845f * 1.4426950408889634f;
DEVI int fa_qt(int w) { return w >> 5; }
DEVI int fa_hc(int w) { return (w & 31) * 128; }

DEVI void fa_exp(const float* S, uint32_t* Pn, float mc0, float mc1, float& s0, float& s1) {
  float a0 = 0.f, a1 = 0.f, b0 = 0.f, b1 = 0.f;
#pragma unroll
  for (int j = 0; j < 16; j++) {
    const float e0 = ex2(fmaf(S[4 * j], FA_C, -mc0)), e1 = ex2(fmaf(S[4 * j + 1], FA_C, -mc0));
    const float e2 = ex2(fmaf(S[4 * j + 2], FA_C, -mc1)), e3 = ex2(fmaf(S[4 * j + 3], FA_C, -mc1));
    a0 += e0; a1 += e1; b0 += e2; b1 += e3;
    Pn[2 * j] = pack2(e0, e1); Pn[2 * j + 1] = pack2(e2, e3);
  }
  s0 = a0 + a1; s1 = b0 + b1;
}

struct FaState { float mc0, mc1, l0, l1; int w, j, qi; uint32_t dq; bool first; };
enum { F_Q = 0, F_K = 2 * 32768, F_V = 4 * 32768, F_O = 6 * 32768, F_QF = 7 * 32768, F_QE = F_QF + 16, F_KF = F_QF + 32, F_KE = F_QF + 48, F_VF = F_QF + 64, F_VE = F_QF + 80,
       F_OF = F_QF + 96, F_OE = F_QF + 112, F_INFO = F_QF + 128 };

template <int SC> DEVI bool fa_step(FaState& T, float* O, float* S, const uint32_t* Pc, uint32_t* Pn, uint32_t base, int tid, int wg, uint32_t ph) {
  const bool el = (tid & 127) == 0, fin = T.j == 0;
  int wn = T.w, jn = T.j - 1;
  const bool okk = mbar_try(base + F_KF + 8 * (SC ^ 1), ph), okv = mbar_try(base + F_VF + 8 * SC, ph ^ SC);
  if (fin) {
    T.qi++; T.dq ^= 2048;
    mbar_wait(base + F_QF + 8 * (T.qi & 1), (T.qi >> 1) & 1);
    asm volatile("ld.shared.b32 %0,[%1];" : "=r"(wn) : "r"(base + F_INFO + (T.qi & 1) * 4) : "memory");
    wn = __shfl_sync(~0u, wn, 0);
    jn = fa_qt(wn);
  }
  if (!(okk && okv)) { mbar_wait(base + F_KF + 8 * (SC ^ 1), ph); mbar_wait(base + F_VF + 8 * SC, ph ^ SC); }
  const bool last = wn < 0;
  {
    const uint64_t dq = desc_k(0) | T.dq, dk = desc_k(base + F_K + (SC ^ 1) * 32768), dv = desc_mn(base + F_V + SC * 32768, 16384);
    bar_sync(3 + wg, 256);
    wg_fence();
#pragma unroll
    for (int kk = 0; kk < 8; kk++) wg_ss128<0>(S, dq + (kk & 3) * 2 + (kk >> 2) * 1024, dk + (kk & 3) * 2 + (kk >> 2) * 1024, kk);
    wg_commit();
#pragma unroll
    for (int kk = 0; kk < 8; kk++) wg_rs128<1>(O, Pc + 4 * kk, dv + kk * 128, kk || !T.first);
    wg_commit();
    bar_arrive(4 - wg, 256);
  }
  wg_wait<1>();
  asm volatile("{.reg .pred p,q; setp.ne.u32 p,%0,0; setp.eq.and.u32 q,%1,0,p; @p mbarrier.arrive.shared::cta.b64 _,[%2]; @q mbarrier.arrive.shared::cta.b64 _,[%3];}"
               ::"r"((uint32_t)el), "r"(jn), "r"(base + F_KE + 8 * (SC ^ 1)), "r"(base + F_QE + 8 * (T.qi & 1)) : "memory");
  const float lp0 = T.l0, lp1 = T.l1;
  float s0 = 0.f, s1 = 0.f, f0 = 1.f, f1 = 1.f;
  bool exact = fin;
  if (!fin) {
    fa_exp(S, Pn, T.mc0, T.mc1, s0, s1);
    exact = __any_sync(~0u, !(fmaxf(s0, s1) <= 1073741824.f));
  }
  if (exact && !last) {
    float a = -INFINITY, b = -INFINITY;
    if (fin) {
      const int row = (tid >> 5) * 16 + ((tid & 31) >> 2) - (tid & 3) * 2;
#pragma unroll
      for (int j = 0; j < 16; j++) {
        if (j * 8 > row) S[4 * j] = -INFINITY;
        if (j * 8 + 1 > row) S[4 * j + 1] = -INFINITY;
        if (j * 8 > row + 8) S[4 * j + 2] = -INFINITY;
        if (j * 8 + 1 > row + 8) S[4 * j + 3] = -INFINITY;
      }
      T.mc0 = T.mc1 = -INFINITY;
    }
#pragma unroll
    for (int j = 0; j < 16; j++) { a = fmaxf(a, fmaxf(S[4 * j], S[4 * j + 1])); b = fmaxf(b, fmaxf(S[4 * j + 2], S[4 * j + 3])); }
    a = fmaxf(a, __shfl_xor_sync(~0u, a, 1)); b = fmaxf(b, __shfl_xor_sync(~0u, b, 1));
    a = fmaxf(a, __shfl_xor_sync(~0u, a, 2)); b = fmaxf(b, __shfl_xor_sync(~0u, b, 2));
    a = fmaxf(a * FA_C, T.mc0); b = fmaxf(b * FA_C, T.mc1);
    f0 = ex2(T.mc0 - a); f1 = ex2(T.mc1 - b);
    T.mc0 = a; T.mc1 = b;
    T.l0 = fin ? 0.f : T.l0 * f0; T.l1 = fin ? 0.f : T.l1 * f1;
    fa_exp(S, Pn, a, b, s0, s1);
  }
  T.l0 += s0; T.l1 += s1;
  wg_wait<0>();
  if (el) mbar_arrive(base + F_VE + 8 * SC);
  if (exact) {
    if (fin) {
      f0 = lp0 + __shfl_xor_sync(~0u, lp0, 1); f1 = lp1 + __shfl_xor_sync(~0u, lp1, 1);
      f0 += __shfl_xor_sync(~0u, f0, 2); f1 += __shfl_xor_sync(~0u, f1, 2);
      f0 = 1.f / f0; f1 = 1.f / f1;
    }
#pragma unroll
    for (int i = 0; i < 16; i++) { O[4 * i] *= f0; O[4 * i + 1] *= f0; O[4 * i + 2] *= f1; O[4 * i + 3] *= f1; }
    if (fin && (T.qi || last)) {
      const uint32_t row = ((tid >> 5) & 3) * 16 + (tid & 15);
      const uint32_t o = base + F_O + wg * 16384 + row * 128 + ((((tid >> 4) & 1) ^ (row & 7)) << 4);
      if (T.qi) mbar_wait(base + F_OE + 8 * wg, T.qi & 1);
#pragma unroll
      for (int i = 0; i < 8; i++) {
        const float* a = O + i * 8;
        stsm4((o ^ ((i & 3) * 32)) + (i >> 2) * 8192, pack2(a[0], a[1]), pack2(a[2], a[3]), pack2(a[4], a[5]), pack2(a[6], a[7]));
      }
      if (el) asm volatile("st.shared.b32 [%0],%1;" ::"r"(base + F_INFO + 8 + wg * 4), "r"(!T.qi ? -1 : T.w | (last ? 1024 : 0)) : "memory");
      fence_async();
      __syncwarp();
      if ((tid & 31) == 0) mbar_arrive(base + F_OF + 8 * wg);
    }
  }
  T.w = wn; T.j = jn; T.first = fin;
  return last;
}

__global__ void __launch_bounds__(384, 1) fa_kernel(const __grid_constant__ FaParams P) {
  extern __shared__ __align__(1024) uint8_t smem_raw[];
  const uint32_t base = s2u(smem_raw);
  const uint32_t sQ = base, sK = base + 2 * 32768, sV = base + 4 * 32768, sO = base + 6 * 32768, bars = base + 7 * 32768;
  const uint32_t qf = bars, qe = bars + 16, kf = bars + 32, ke = bars + 48, vf = bars + 64, ve = bars + 80, of = bars + 96, oe = bars + 112;
  volatile int* info = (volatile int*)(smem_raw + 7 * 32768 + 128);
  const int tid = threadIdx.x, wg = tid >> 7;
  pdl_trigger();
  if (tid == 0) {
    for (int i = 0; i < 16; i++) mbar_init(bars + 8 * i, i >= 14 ? 1 : i >= 12 ? 4 : (i & 2) ? 2 : 1);
    info[4] = 0;
    asm volatile("fence.mbarrier_init.release.cluster;" ::: "memory");
  }
  __syncthreads();
  if (wg == 2) {
    reg_dec<24>();
    if (tid == 256) {
      int it = 0, qi = 0, vc = 0, vr = -1, j = 0, hc = 0;
      CT(gridDim.x > 20 ? 3 : 6, 0)
      auto load_v = [&]() {
        if (vr < 0) return;
        const int s = (it - 1) & 1;
        mbar_wait(ve + 8 * s, (((it - 1) >> 1) & 1) ^ 1 ^ s);
        mbar_expect(vf + 8 * s, 32768);
        tma_load(sV + s * 32768, &P.v, vc, vr, vf + 8 * s);
        tma_load(sV + s * 32768 + 16384, &P.v, vc + 64, vr, vf + 8 * s);
        vr = -1;
      };
      auto ready = [&](uint32_t m) { uint32_t v; asm volatile("ld.acquire.cta.shared.b32 %0,[%1];" : "=r"(v) : "r"(base + F_INFO + 16) : "memory"); return (v & m) == m; };
      for (it = -1;; it++) {
        if (it >= 0) {
          const int s = it & 1;
          mbar_wait(ke + 8 * s, ((it >> 1) & 1) ^ 1);
          if (j < 0) { mbar_arrive(kf + 8 * s); load_v(); break; }
          mbar_expect(kf + 8 * s, 32768);
          tma_load(sK + s * 32768, &P.k, hc, j * 128, kf + 8 * s);
          tma_load(sK + s * 32768 + 16384, &P.k, hc + 64, j * 128, kf + 8 * s);
        }
        int nc = hc, nr = it >= 0 ? j * 128 : -1;
        if (j-- == 0) {
          int w = atomicInc(&g_sync[S_QUEUE], 511 + P.nctas);
          w = w < 512 ? P.order[w] : -1;
          const uint32_t q = qi & 1, m = w < 0 ? 0x3ffff : (1u | (2u << (fa_qt(w) | 1))) << ((w >> 4) & 1);
          if (!ready(m) || !mbar_test(qe + 8 * q, ((qi >> 1) & 1) ^ 1)) {
            load_v(); it++; vc = nc; vr = nr; load_v(); it--; nr = -1;
            for (int n = 0; !ready(m) && n < WAIT_MAX; n++) __nanosleep(64);
            mbar_wait(qe + 8 * q, ((qi >> 1) & 1) ^ 1);
          }
          asm volatile("fence.proxy.async.global;" ::: "memory");
          info[q] = w;
          if (w < 0) mbar_arrive(qf + 8 * q);
          else {
            j = fa_qt(w); hc = fa_hc(w);
            mbar_expect(qf + 8 * q, 32768);
            tma_load(sQ + q * 32768, &P.q, hc, j * 128, qf + 8 * q);
            tma_load(sQ + q * 32768 + 16384, &P.q, hc + 64, j * 128, qf + 8 * q);
          }
          qi++;
        }
        load_v();
        vc = nc; vr = nr;
      }
      if (atomicInc(&g_sync[S_EXIT], P.nctas - 1) == P.nctas - 1)
        for (int i = 0; i < 18; i++) g_sync[S_PROJ + i] = 0;
    } else if (tid >= 352) {
      const int l = tid - 352;
      for (int n = 0; n < WAIT_MAX; n++) {
        unsigned v = 255;
        if (l < 18) asm volatile("ld.acquire.gpu.global.u32 %0, [%1];" : "=r"(v) : "l"(g_sync + S_PROJ + l) : "memory");
        const uint32_t m = __ballot_sync(~0u, v >= P.nproj[(l >> 1) % 9]);
        __syncwarp();
        if (l == 0) asm volatile("st.release.cta.shared.b32 [%0],%1;" ::"r"(base + F_INFO + 16), "r"(m) : "memory");
        if (m == ~0u) break;
        __nanosleep(300);
      }
    } else if (tid == 288 || tid == 320) {
      const int g = tid == 320;
        for (int n = 0;; n++) {
          mbar_wait(of + 8 * g, n & 1);
          const int v = info[2 + g], w = v & 1023, qt = fa_qt(w), hc = fa_hc(w);
          if (v < 0) break;
          tma_store(&P.o, sO + g * 16384, hc, qt * 128 + g * 64);
          tma_store(&P.o, sO + g * 16384 + 8192, hc + 64, qt * 128 + g * 64);
          bulk_commit();
          bulk_wait_read<0>();
          mbar_arrive(oe + 8 * g);
          bulk_wait<0>();
          signal_after_bulk(S_CTXA + qt);
          if (v & 1024) break;
        }
    }
  } else {
    reg_inc<240>();
    float O[64], S[64];
    uint32_t PA[32], PB[32];
#pragma unroll
    for (int i = 0; i < 32; i++) PA[i] = 0;
#pragma unroll
    for (int i = 0; i < 64; i++) O[i] = 0.f;
    const uint32_t ub = __shfl_sync(~0u, base, 0);
    const int uw = __shfl_sync(~0u, wg, 0);
    FaState T = {0.f, 0.f, 1.f, 1.f, 0, 0, -1, ((ub + 32768 + uw * 8192) >> 4) & 0x3fff, true};
    if (wg == 1) bar_arrive(3, 256);
    for (uint32_t ph = 0;; ph ^= 1) {
      if (fa_step<1>(T, O, S, PA, PB, ub, tid, uw, ph)) break;
      if (fa_step<0>(T, O, S, PB, PA, ub, tid, uw, ph)) break;
    }
    if (wg == 0) bar_sync(3, 256);
  }
}
#define PS 20
#define PT(i)
#define YD 200
#define NPF 4
#define NRES 6
#define RP 208
#define PD 2
#define VR "............rrrrrr.................."
#define VP "222222222222111111111111------------"
constexpr int vr_index(int k) { int n = 0; for (int i = 0; i < k; i++) n += VR[i] == 'r'; return n; }
constexpr int VB = vr_index(36);
template <int K> struct VIdx { static constexpr int v = vr_index(K); static constexpr char r = VR[K], p = VP[K]; };
#define XG 6
#define XW 2
#define WOD 4000
#define KA 26
constexpr int R_WV = 0, R_WO = 73728, R_H = 147456, R_OX = R_H + 46080, R_Q = R_OX + 4096, R_K = R_Q + 5120, R_SX = R_K + 5120, R_P = R_SX + 3200, R_U = R_P + 3200,
              R_BAR = R_H + 73728, R_PROF = R_BAR + 256, R_END = R_PROF + 3072;
constexpr int B_W0 = R_BAR, B_W1 = R_BAR + 8, B_XA = R_BAR + 16, B_XB = R_BAR + 24, B_XF = R_BAR + 32, B_Z0 = R_BAR + 40, B_Z1 = R_BAR + 48, B_R = R_BAR + 56,
              B_SM = R_BAR + 64, B_SX = R_BAR + 72, B_U = R_BAR + 80, B_V = R_BAR + 88, B_O = R_BAR + 96, B_W2 = R_BAR + 160, B_W3 = R_BAR + 168;
static_assert(R_U + 4096 <= R_BAR, "");
enum { N_P1 = 1, N_PM, N_PX, N_SUM, N_O, N_INIT, N_INIT1, N_INIT2, N_WO, N_S };
constexpr int YSLOT = 9 * 16 * 1024;
struct RecParams { CUtensorMap wq, wk, wv, wo, x, ctx; OutMaps o; const bf16 *mem0, *x_raw; bf16* out; };
constexpr int TAIL0 = 12;
constexpr int R_RED = 4 * OSB;

DEVI uint64_t mkdesc(uint32_t a, uint32_t lbo, uint32_t sbo, int sw) { return (uint64_t)((a >> 4) & 0x3fff) | ((uint64_t)(lbo >> 4) << 16) | ((uint64_t)(sbo >> 4) << 32) | ((uint64_t)sw << 62); }
DEVI void wg_rs32(float* d, const uint32_t* a, uint64_t db, int acc) {
  asm volatile("{.reg .pred p; setp.ne.b32 p,%21,0;\n wgmma.mma_async.sync.aligned.m64n32k16.f32.bf16.bf16 {%0,%1,%2,%3,%4,%5,%6,%7,%8,%9,%10,%11,%12,%13,%14,%15},{%16,%17,%18,%19},%20,p,1,1,0;}"
               : F8(d, 0), F8(d, 8) : "r"(a[0]), "r"(a[1]), "r"(a[2]), "r"(a[3]), "l"(db), "r"(acc));
}
DEVI void wg_rs40(float* d, const uint32_t* a, uint64_t db, int acc) {
  asm volatile("{.reg .pred p; setp.ne.b32 p,%25,0;\n wgmma.mma_async.sync.aligned.m64n40k16.f32.bf16.bf16 {%0,%1,%2,%3,%4,%5,%6,%7,%8,%9,%10,%11,%12,%13,%14,%15,%16,%17,%18,%19},{%20,%21,%22,%23},%24,p,1,1,0;}"
               : F8(d, 0), F8(d, 8), "+f"(d[16]), "+f"(d[17]), "+f"(d[18]), "+f"(d[19]) : "r"(a[0]), "r"(a[1]), "r"(a[2]), "r"(a[3]), "l"(db), "r"(acc));
}
template <int TB> DEVI void wg_ss40(float* d, uint64_t da, uint64_t db, int acc) {
  asm volatile("{.reg .pred p; setp.ne.b32 p,%22,0;\n wgmma.mma_async.sync.aligned.m64n40k16.f32.bf16.bf16 {%0,%1,%2,%3,%4,%5,%6,%7,%8,%9,%10,%11,%12,%13,%14,%15,%16,%17,%18,%19},%20,%21,p,1,1,1,%23;}"
               : F8(d, 0), F8(d, 8), "+f"(d[16]), "+f"(d[17]), "+f"(d[18]), "+f"(d[19]) : "l"(da), "l"(db), "r"(acc), "n"(TB));
}
DEVI void mma8(float* d, uint32_t a0, uint32_t a1, uint32_t b0) {
  asm volatile("mma.sync.aligned.m16n8k8.row.col.f32.bf16.bf16.f32 {%0,%1,%2,%3},{%4,%5},{%6},{%0,%1,%2,%3};" : "+f"(d[0]), "+f"(d[1]), "+f"(d[2]), "+f"(d[3]) : "r"(a0), "r"(a1), "r"(b0));
}
DEVI void stsm4t(uint32_t a, uint32_t r0, uint32_t r1, uint32_t r2, uint32_t r3) {
  asm volatile("stmatrix.sync.aligned.m8n8.x4.trans.shared.b16 [%0],{%1,%2,%3,%4};" ::"r"(a), "r"(r0), "r"(r1), "r"(r2), "r"(r3) : "memory");
}
DEVI uint32_t movm(uint32_t a) { uint32_t d; asm volatile("movmatrix.sync.aligned.m8n8.trans.b16 %0,%1;" : "=r"(d) : "r"(a)); return d; }
DEVI void sts1(uint32_t a, uint32_t v) { asm volatile("st.shared.b32 [%0],%1;" ::"r"(a), "r"(v) : "memory"); }
DEVI uint32_t lds1(uint32_t a) { uint32_t v; asm volatile("ld.shared.b32 %0,[%1];" : "=r"(v) : "r"(a) : "memory"); return v; }
DEVI void sta1(uint32_t d, uint32_t a, uint32_t bar) { asm volatile("st.async.weak.shared::cluster.mbarrier::complete_tx::bytes.b32 [%0],%1,[%2];" ::"r"(d), "r"(a), "r"(bar) : "memory"); }
DEVI void sta2(uint32_t d, uint32_t a, uint32_t b, uint32_t bar) { asm volatile("st.async.weak.shared::cluster.mbarrier::complete_tx::bytes.v2.b32 [%0],{%1,%2},[%3];" ::"r"(d), "r"(a), "r"(b), "r"(bar) : "memory"); }
DEVI uint32_t clk32() { uint64_t c; asm volatile("mov.u64 %0,%%clock64;" : "=l"(c)::"memory"); return (uint32_t)c; }
DEVI int opq(int x) { asm volatile("" : "+r"(x)); return x; }
DEVI int pin(int x) { return __shfl_sync(~0u, x, threadIdx.x & 31); }
DEVI void x_load(const RecParams& P, uint32_t sb, int c, int seg) {
  asm volatile("cp.async.bulk.tensor.2d.shared::cluster.global.mbarrier::complete_tx::bytes.multicast::cluster [%0],[%1,{%3,%4}],[%2],%5;"
               ::"r"(sb + R_H + c * 5120 + 1024), "l"(&P.x), "r"(sb + (c < XG ? B_XA : B_XB)), "r"(c * 64), "r"(seg * 32), "h"((uint16_t)0xffff) : "memory");
  if (seg + 2 < NSEG) asm volatile("cp.async.bulk.prefetch.tensor.2d.L2.global [%0,{%1,%2}];" ::"l"(&P.x), "r"(c * 64), "r"(seg * 32 + 64) : "memory");
}
DEVI uint32_t hadd2(uint32_t a, uint32_t b) { uint32_t r; asm("add.rn.bf16x2 %0,%1,%2;" : "=r"(r) : "r"(a), "r"(b)); return r; }
DEVI uint32_t hmax2(uint32_t a, uint32_t b) { uint32_t r; asm("max.bf16x2 %0,%1,%2;" : "=r"(r) : "r"(a), "r"(b)); return r; }
DEVI float rcp(float x) { float y; asm("rcp.approx.ftz.f32 %0,%1;" : "=f"(y) : "f"(x)); return y; }
constexpr float SCL = 0.08838834764831845f * 1.4426950408889634f;

DEVI void y_store(const float* a, uint32_t off, int s) {
  const uint32_t x = movm(pack2(a[0], a[1])), y = movm(pack2(a[2], a[3]));
  const uint32_t tag = ((s >> 1) & 1) ^ 1;
  asm volatile("st.relaxed.gpu.global.b64 [%0],%1;" ::"l"((uint8_t*)g_Y + (s & 1) * YSLOT + off), "l"((uint64_t)((x & ~1u) | tag) | ((uint64_t)y << 32)) : "memory");
}
DEVI void y_load(uint32_t* w, const uint8_t* p) {
#pragma unroll
  for (int i = 0; i < 4; i++) asm volatile("{.reg .b64 t; ld.relaxed.gpu.global.b64 t,[%2]; mov.b64 {%0,%1},t;}" : "=r"(w[2 * i]), "=r"(w[2 * i + 1]) : "l"(p + i * 256) : "memory");
}
DEVI bool y_missing(const uint32_t* w, uint32_t tag) {
  uint32_t r;
  asm volatile("{.reg .b32 a,b; .reg .pred p; lop3.b32 a,%1,%2,%5,0x7e; lop3.b32 b,%3,%4,%5,0x7e; lop3.b32 a,a,b,1,0xa8; setp.ne.u32 p,a,0; vote.sync.any.pred p,p,0xffffffff; selp.u32 %0,1,0,p;}"
               : "=r"(r) : "r"(w[0]), "r"(w[2]), "r"(w[4]), "r"(w[6]), "r"(tag));
  return r;
}
DEVI void y_reload(uint32_t* w, const uint8_t* p, uint32_t tag) {
#pragma unroll
  for (int i = 0; i < 4; i++)
    asm volatile("{.reg .b64 t; .reg .b32 a; .reg .pred q; lop3.b32 a,%0,%3,1,0x28; setp.ne.u32 q,a,0; mov.b64 t,{%0,%1}; @q ld.relaxed.gpu.global.b64 t,[%2]; mov.b64 {%0,%1},t;}"
                 : "+r"(w[2 * i]), "+r"(w[2 * i + 1]) : "l"(p + i * 256), "r"(tag) : "memory");
}
DEVI void y_sum(uint32_t* r, const uint32_t* w, uint32_t sel) {
  float d0[4] = {0, 0, 0, 0}, d1[4] = {0, 0, 0, 0};
  mma16(d0, w[0], w[1], w[2], w[3], sel, sel); mma16(d1, w[4], w[5], w[6], w[7], sel, sel);
  r[0] = pack2(d0[0] + d1[0], d0[1] + d1[1]); r[1] = pack2(d0[2] + d1[2], d0[3] + d1[3]);
}
DEVI void y_send(const uint32_t* r, uint32_t sb, uint32_t dst, uint32_t bar, int lane) {
#pragma unroll
  for (int i = 0; i < 4; i++) { const uint32_t rs = mapa(sb, (lane & 3) + i * 4); sta2(rs + dst, r[0], r[1], rs + bar); }
}
DEVI void wo_convert(uint32_t sb, int lane) {
  TL_END(11)
  mbar_wait(sb + B_W3, 0);
  TL_END(9)
#pragma unroll 1
  for (uint32_t a = sb + R_WO + ((threadIdx.x >> 5) & 3) * 4608, i = 0; i < 4; i++, a += 18432) {
    uint32_t r[9][4];
#pragma unroll
    for (int k = 0; k < 9; k++) ldsm4t(r[k], a + k * 32 + ((lane & 7) + (lane >> 4) * 8) * 288 + ((lane >> 3) & 1) * 16);
    __syncwarp();
#pragma unroll
    for (int k = 0; k < 9; k++) stsm4(a + k * 512 + ((lane >> 4) * 2 + ((lane >> 1) & 1)) * 128 + (((lane >> 2) & 3) * 2 + (lane & 1)) * 16, r[k][0], r[k][1], r[k][2], r[k][3]);
  }
  __syncwarp();
}
DEVI uint32_t y_offset(int cta, int tile, int lane) {
  const int T = (cta & 3) * 9 + tile;
  return (((T >> 2) * 8 + (lane >> 2)) * 2 + ((T >> 1) & 1)) * 1024 + (cta >> 4) * 256 + (T & 1) * 128 + ((cta >> 2) & 3) * 32 + (lane & 3) * 8;
}
template <int NR, int NP> DEVI void wo_tile(const uint32_t (*A0)[4], uint32_t sb, int tile, int lane, uint32_t yo, int s) {
  uint32_t u[8][4], A[16][4];
  const uint32_t wa = sb + R_WO + tile * 512 + lane * 16, ua = sb + R_U + lane * 16;
  float a[4] = {0, 0, 0, 0}, b[4] = {0, 0, 0, 0};
  auto fetch = [&](int i) { if (i < 16 - NR) ldsm4(A[i], wa + i * 4608); };
  auto uload = [&](int i) { if (i < 8) ldsm4t(u[i], ua + i * 512); };
#pragma unroll
  for (int i = 0; i < NP; i++) fetch(i);
  mwait(sb + B_V, s & 1);
  PT(6)
  uload(0); uload(1);
#pragma unroll
  for (int i = 0; i < 16; i++) {
    if (i == 4) {
      mwait(sb + B_U, s & 1);
      PT(7)
      uload(2); uload(3);
    }
    const uint32_t* f = i >= 16 - NR ? A0[i >= 16 - NR ? i - 16 + NR : 0] : A[i];
    mma16(i & 1 ? b : a, f[0], f[1], f[2], f[3], u[i >> 1][(i & 1) * 2], u[i >> 1][(i & 1) * 2 + 1]);
    fetch(i + NP);
    if (i >= 4 && (i & 1)) uload((i >> 1) + 2);
  }
#pragma unroll
  for (int i = 0; i < 4; i++) a[i] += b[i];
  y_store(a, yo, s);
}
template <bool X> DEVI void softmax8(const uint32_t* h, uint32_t a4, uint32_t a1) {
  uint32_t y[5];
  lds4(y, a4 + R_SX);
  y[4] = lds1(a1 + R_SX);
#pragma unroll
  for (int j = 0; j < 5; j++) y[j] = hadd2(h[j], y[j]);
  const uint32_t m2 = hmax2(hmax2(hmax2(y[0], y[1]), hmax2(y[2], y[3])), y[4]);
  const float mc = fmaxf(blo(m2), bhi(m2)) * SCL;
  const float m1 = __shfl_xor_sync(~0u, mc, 1), m3 = __shfl_xor_sync(~0u, mc, 2), m4 = __shfl_xor_sync(~0u, mc, 3);
  float e[10];
#pragma unroll
  for (int j = 0; j < 5; j++) { e[2 * j] = ex2(fmaf(blo(y[j]), SCL, -mc)); e[2 * j + 1] = ex2(fmaf(bhi(y[j]), SCL, -mc)); }
  const float c = ex2(mc - fmaxf(fmaxf(mc, m1), fmaxf(m3, m4)));
  const float l = c * ((((e[0] + e[1]) + (e[2] + e[3])) + ((e[4] + e[5]) + (e[6] + e[7]))) + (e[8] + e[9]));
  const float r = c * rcp((l + __shfl_xor_sync(~0u, l, 1)) + (__shfl_xor_sync(~0u, l, 2) + __shfl_xor_sync(~0u, l, 3)));
#pragma unroll
  for (int j = 0; j < 5; j++) y[j] = pack2(e[2 * j] * r, e[2 * j + 1] * r);
  if (!X) sts4(a4 + R_P, y[0], y[1], y[2], y[3]);
  else stsm4(a4 + R_P, y[0], y[1], y[2], y[3]);
  sts1(a1 + R_P, y[4]);
  if (X) fence_async();
}

DEVI void arm_step(uint32_t sb, int s) {
  mbar_expect(sb + B_SM, 640); mbar_expect(sb + B_SX, 2560);
  if (s < NSEG - 1) {
    mbar_expect(sb + B_U, 3072); mbar_expect(sb + B_Z0, 4096); mbar_expect(sb + B_Z1, 5120);
    mbar_expect(sb + B_XA, XG * 4096); mbar_expect(sb + B_XB, (9 - XG) * 4096);
  }
}
DEVI void rec_proj(const RecParams& P, const uint32_t sb, const int cta) {
  uint32_t W[36][4], A0[NRES ? NRES : 1][4];
  const int tid = pin(threadIdx.x);
  const uint32_t yo = pin(y_offset(cta, threadIdx.x >> 5, threadIdx.x & 31));
  const int warp = __shfl_sync(~0u, threadIdx.x >> 5, 0), role = warp >> 2;
  const uint32_t qk = sb + R_Q + warp * 1280;
  {
    const int lane = threadIdx.x & 31, w4 = (threadIdx.x >> 5) & 3;
    const uint32_t a = sb + role * R_H + ((lane & 7) + (lane >> 4) * 8) * 128 + (((w4 * 2 + ((lane >> 3) & 1)) ^ (lane & 7)) << 4);
    mbar_wait(sb + B_W0 + role * 8, 0);
    TL_END(8)
#pragma unroll
    for (int k = 0; k < 36; k++) ldsm4t(W[k], a + k * 2048);
    if (role) bar_arrive(N_INIT1, 256); else bar_sync(N_INIT, 128);
    cluster_sync_relaxed();
#pragma unroll
    for (int i = 0; i < NRES; i++) A0[i][0] = A0[i][1] = A0[i][2] = A0[i][3] = 0;
  }
  for (int s = -1; s < NSEG; s++) {
    if (s >= 0) {
      PT(0)
      {
        const int lane = opq(tid) & 31;
        const uint32_t hb = sb + R_H + (lane & 7) * 128 + (((lane >> 3) ^ (lane & 7)) << 4);
        float a[4] = {0, 0, 0, 0}, b[4] = {0, 0, 0, 0};
        mwait(sb + B_Z0, (s - 1) & 1);
        PT(1)
        uint32_t f[18][4];
#pragma unroll
        for (int c = -PD; c < 18; c++) {
          if (c + PD == 8) mwait(sb + B_Z1, (s - 1) & 1);
          if (c + PD < 18) ldsm4(f[c + PD], (hb ^ (((c + PD) & 1) * 64)) + ((c + PD) >> 1) * 5120);
          if (c >= 0) {
            mma16(a, W[2 * c][0], W[2 * c][1], W[2 * c][2], W[2 * c][3], f[c][0], f[c][1]);
            mma16(b, W[2 * c + 1][0], W[2 * c + 1][1], W[2 * c + 1][2], W[2 * c + 1][3], f[c][2], f[c][3]);
          }
        }
        sts1(qk + 512 + lane * 4, pack2(a[0] + b[0], a[1] + b[1]));
        sts1(qk + 1152 + lane * 4, pack2(a[2] + b[2], a[3] + b[3]));
        fence_async();
      }
      PT(2)
      const int lane = opq(tid) & 31;
      if (role) {
        bar_arrive(N_P1, 256);
        if (tid == 128) arm_step(sb, s);
        const uint32_t o4 = sb + (warp - 4) * 640 + lane * 16, o1 = sb + (warp - 4) * 640 + 512 + lane * 4;
        uint32_t h[5];
        bar_sync(N_PX, 192);
        lds4(h, o4 + R_P); h[4] = lds1(o1 + R_P);
        mwait(sb + B_SX, s & 1);
        PT(4)
        softmax8<true>(h, o4, o1);
        PT(5)
      } else {
        float S[20];
        const uint64_t da = mkdesc(sb + R_Q, 640, 128, 0), db = mkdesc(sb + R_K, 640, 128, 0);
        const uint32_t rs = mapa(sb, (cta & 15) ^ 1);
        const uint32_t o4 = warp * 1280 + lane * 16, o1 = warp * 1280 + 512 + lane * 4;
        bar_sync(N_P1, 256);
        wg_fence();
#pragma unroll
        for (int k = 0; k < 4; k++) wg_ss40<1>(S, da + k * 80, db + k * 80, k);
        wg_commit();
        bar_arrive(N_S, 256);
        wg_wait<0>();
        PT(3)
        uint32_t h[2][5];
        if (warp == 2) {
#pragma unroll
          for (int j = 0; j < 5; j++) h[0][j] = pack2(S[4 * j], S[4 * j + 1]);
          sta4(rs + R_SX + o4, h[0][0], h[0][1], h[0][2], h[0][3], rs + B_SM); sta1(rs + R_SX + o1, h[0][4], rs + B_SM);
          mwait(sb + B_SM, s & 1);
          PT(4)
          softmax8<false>(h[0], sb + o4, sb + o1);
          bar_arrive(N_PM, 160);
        } else if (warp < 2) {
          const int row = warp * 16 + (lane >> 2) - (lane & 3) * 2;
#pragma unroll
          for (int g = 0; g < 2; g++) {
#pragma unroll
            for (int j = 0; j < 5; j++) h[g][j] = pack2(j < 4 && j * 8 > row + g * 8 ? -INFINITY : S[4 * j + 2 * g], j < 4 && j * 8 + 1 > row + g * 8 ? -INFINITY : S[4 * j + 2 * g + 1]);
            sts4(sb + R_P + o4 + g * 640, h[g][0], h[g][1], h[g][2], h[g][3]); sts1(sb + R_P + o1 + g * 640, h[g][4]);
            sta4(rs + R_SX + o4 + g * 640, h[g][0], h[g][1], h[g][2], h[g][3], rs + B_SX);
            sta1(rs + R_SX + o1 + g * 640, h[g][4], rs + B_SX);
          }
          bar_arrive(N_PX, 192);
        } else {
          if (s) bar_sync(N_O, 160);
          if (tid == 96) {
            if (s) {
              bulk_wait<0>();
              tma_store(&P.ctx, sb + R_OX, cta * 64, s * 32 - 32); bulk_commit();
              if ((s & 3) == 1 && s > 1) signal_after_bulk(S_CTXB + (s >> 2) - 1);
              bulk_wait_read<0>();
            }
          }
        }
        __syncwarp();
        PT(5)
      }
      {
        if (s == 0) {
          bar_sync(N_INIT2, 384);
#pragma unroll
          for (int i = 0; i < NRES; i++) ldsm4(A0[i], sb + R_WO + warp * 512 + lane * 16 + (16 - NRES + i) * 4608);
        }
        if (s == NSEG - 1) break;
        wo_tile<NRES, NPF>(A0, sb, warp, lane, yo, s);

        PT(8)
        bar_sync(N_WO, 384);
      }
    }
    {
      float acc[16];
      const uint64_t db = mkdesc(sb + R_H + 1024, 16, 1024, 1);
      mwait(sb + B_XA, (s + 1) & 1);
      PT(9)
      wg_fence();
#pragma unroll
      for (int k = 0; k < XG * 4; k++) wg_rs32(acc, W[k], db + (k >> 2) * 320 + (k & 3) * 2, k);
      wg_commit();
      mwait(sb + B_XB, (s + 1) & 1);
      wg_fence();
#pragma unroll
      for (int k = XG * 4; k < KA; k++) wg_rs32(acc, W[k], db + (k >> 2) * 320 + (k & 3) * 2, 1);
      wg_commit();
      wg_wait<0>();
      PT(10)
      bar_sync(N_SUM, 384);
      wg_fence();
#pragma unroll
      for (int k = KA; k < 36; k++) wg_rs32(acc, W[k], db + (k >> 2) * 320 + (k & 3) * 2, 1);
      wg_commit();
      const uint32_t o = qk + (opq(tid) & 31) * 16;
      wg_wait<0>();
      PT(11)
      stsm4(o, pack2(acc[0], acc[1]), pack2(acc[4], acc[5]), pack2(acc[8], acc[9]), pack2(acc[12], acc[13]));
      stsm4(o + 640, pack2(acc[2], acc[3]), pack2(acc[6], acc[7]), pack2(acc[10], acc[11]), pack2(acc[14], acc[15]));
    }
  }
  bar_arrive(N_WO, 384);
  for (int i = 0; i < (warp ? 1 : 2); i++)
    asm volatile("st.relaxed.gpu.global.b64 [%0],%1;" ::"l"((uint8_t*)g_Y + YSLOT + yo + i * 2 * 16384), "l"(0ull) : "memory");
  TL_END(6)
  if (tid == 0) CT(1, 0)
  if (warp == 3) {
    if (tid == 96) { bulk_wait<0>(); asm volatile("fence.proxy.async.global;" ::: "memory"); }
    __syncwarp();
    bar_arrive(N_O, 160);
  }
  asm volatile("barrier.cluster.arrive.relaxed.aligned;" ::: "memory");
  float acc[96];
  const int rk = opq(cta) & 15, n = rk / 5, q = rk - n * 5;
  out_consume<4, false>(acc, sb, sb + B_O, rk == 15 ? 0 : q == 4 ? 12 : 13);
  if (tid == 0) CT(7, 1)
  if (tid == 0) CT(1, 1)
  asm volatile("barrier.cluster.wait.aligned;" ::: "memory");
  bar_sync(N_P1, 256);
  {
#pragma unroll
    for (int u = 0; u < 12; u++) {
      const int d = u % 5;
      const float* a = acc + u * 8;
      const uint32_t x = pack2(a[0], a[1]), y = pack2(a[2], a[3]), z = pack2(a[4], a[5]), w = pack2(a[6], a[7]);
      const uint32_t rs = mapa(sb, rk == 15 ? 15 : n * 5 + d);
      if (d == q) sts4(sb + R_RED - 12288 + (u / 5) * 4096 + tid * 16, x, y, z, w);
      else sta4(rs + R_RED + (q < d ? q : q - 1) * 12288 + (u / 5) * 4096 + tid * 16, x, y, z, w, rs + B_R);
    }
    mbar_wait(sb + B_R, 0);
    if (tid == 0) CT(1, 2)
    const int lane = tid & 31;
    const uint32_t st = sb + warp * 1024 + (lane & 15) * 48 + (lane >> 4) * 16, ld = sb + warp * 1024 + (lane >> 1) * 48 + (lane & 1) * 16;
    bf16* out = P.out + (size_t)((TAIL0 + (cta >> 4)) * 128 + warp * 16 + (lane >> 1)) * (2 * DM) + DM + n * 192 + q * 16 + (lane & 1) * 8;
#pragma unroll 1
    for (int i = 0; i < (q < 2 ? 3 : 2); i++) {
      uint32_t v[5][4], r[4];
#pragma unroll
      for (int p = 0; p < 5; p++) lds4(v[p], sb + R_RED + (p - 1) * 12288 + i * 4096 + tid * 16);
#pragma unroll
      for (int j = 0; j < 4; j++)
        r[j] = pack2((blo(v[0][j]) + blo(v[1][j])) + (blo(v[2][j]) + blo(v[3][j])) + blo(v[4][j]), (bhi(v[0][j]) + bhi(v[1][j])) + (bhi(v[2][j]) + bhi(v[3][j])) + bhi(v[4][j]));
      stsm4(st + i * 8192, r[0], r[1], r[2], r[3]);
      __syncwarp();
      lds4(r, ld + i * 8192);
      asm volatile("{.reg .pred p; setp.ne.s32 p,%5,15; @p st.global.v4.b32 [%0],{%1,%2,%3,%4};}" ::"l"(out + i * 80), "r"(r[0]), "r"(r[1]), "r"(r[2]), "r"(r[3]), "r"(rk) : "memory");
    }
  }
}

template <int K> DEVI void v_resident(uint32_t (*F)[4], uint32_t wv) {
  if constexpr (K < 36) { if (VIdx<K>::r == 'r') ldsm4t(F[VIdx<K>::v], wv + K * 2048); v_resident<K + 1>(F, wv); }
}
template <int K> DEVI void v_pass(float* acc, const uint32_t (*F)[4], uint64_t da, uint64_t db, uint32_t xf, uint32_t t, uint32_t nrel) {
  if constexpr (K < 36) {
    wg_fence();
    if (VIdx<K>::r == 'r') wg_rs40(acc, F[VIdx<K>::v], db + (K >> 2) * 320 + (K & 3) * 2, K);
    else wg_ss40<0>(acc, da + K * 128, db + (K >> 2) * 320 + (K & 3) * 2, K);
    wg_commit();
    if constexpr (VIdx<K>::p != '-') wg_wait<VIdx<K>::p - '0'>();
    if (K == XG * 4 - 1 + XW) { wg_wait<XW>(); asm volatile("{.reg .pred p; .reg .b32 a; setp.lt.u32 p,%1,%2; @p mapa.shared::cluster.u32 a,%0,%1; @p mbarrier.arrive.shared::cluster.b64 _,[a];}" ::"r"(xf), "r"(t), "r"(nrel) : "memory"); }
    v_pass<K + 1>(acc, F, da, db, xf, t, nrel);
  }
}
DEVI void rec_aux(const RecParams& P, const uint32_t sb, const int cta) {
  const int tid = pin(threadIdx.x);
  {
    uint4 v[5];
#pragma unroll
    for (int j = 0; j < 5; j++) if (j * 128 + tid - 256 < 576) v[j] = ((const uint4*)P.mem0)[j * 128 + tid - 256];
    if (tid == 288) {
      const uint32_t t0 = clk32();
      while (clk32() - t0 < (uint32_t)WOD) {}
#pragma unroll 1
      for (int i = 0; i < 4; i++) tma_load(sb + R_WO + i * 18432, &P.wo, (cta & 3) * 144, (cta ^ i) * 64, sb + B_W3);
      for (int i = 0; i < 3; i++) asm volatile("cp.async.bulk.prefetch.tensor.2d.L2.global [%0,{%1,%2}];" ::"l"(&P.wv), "r"(cta * 64), "r"(i * 192) : "memory");
    }
    __syncwarp();
    bar_sync(N_INIT1, 256);
#pragma unroll
    for (int j = 0; j < 5; j++) {
      const int i = j * 128 + tid - 256, t = i / 72, c = i - t * 72;
      if (i < 576) sts4(sb + R_H + (c >> 3) * 5120 + t * 128 + (((c & 7) ^ t) << 4), v[j].x, v[j].y, v[j].z, v[j].w);
    }
    fence_async();
    bar_arrive(N_SUM, 384);
    cluster_sync_relaxed();
    if (tid == 288) {
      if ((cta & 15) < 9) x_load(P, sb, cta & 15, 0);
#pragma unroll 1
      for (int i = 0; i < 3; i++) tma_load(sb + R_WV + i * 24576, &P.wv, cta * 64, i * 192, sb + B_W2);
    }
    __syncwarp();
    TL_END(12)
    wo_convert(sb, threadIdx.x & 31);
    bar_sync(N_O, 128);
    bar_arrive(N_INIT2, 384);
    TL_END(10)
  }
  const int rk = cta & 15, w4 = __shfl_sync(~0u, (threadIdx.x >> 5) & 3, 0);
  const uint32_t yg = pin((((threadIdx.x >> 5) & 3) * 16 + rk) * 1024 + ((threadIdx.x >> 4) & 1) * 128 + (threadIdx.x & 3) * 32 + ((threadIdx.x >> 2) & 3) * 8);
  uint32_t F[VB][4];
  mbar_wait(sb + B_W2, 0);
  TL_END(7)
  v_resident<0>(F, sb + R_WV + ((tid & 7) + ((tid >> 4) & 1) * 8) * 128 + (((w4 * 2 + ((tid >> 3) & 1)) ^ (tid & 7)) << 4));
  LT(0)
  for (int s = 0; s < NSEG; s++) {
    const bool last = s == NSEG - 1;
    uint32_t va[12], p[5];
    int lane = opq(tid) & 31;
    {
      float acc[20];
      const uint64_t da = mkdesc(sb + R_WV, 0, 1024, 1), db = mkdesc(sb + R_H, 16, 1024, 1);
      PT(0)
      bar_sync(N_S, 256);
      asm volatile("fence.proxy.async::generic.acquire.sync_restrict::shared::cluster.cluster;" ::: "memory");
      v_pass<0>(acc, F, da, db, sb + B_XF, tid - 256, last ? 0 : XG);
      PT(13)
      bar_sync(N_PM, 160);
      lds4(p, sb + R_P + 2560 + lane * 16); p[4] = lds1(sb + R_P + 3072 + lane * 4);
      wg_wait<0>();
      PT(1)
#pragma unroll
      for (int i = 0; i < 10; i++) va[i < 2 ? i + 8 : i - 2] = pack2(acc[2 * i], acc[2 * i + 1]);
      va[10] = va[11] = 0;
    }
    lane = opq(tid) & 31;
    if (!last) {
      const uint32_t uo = R_U + w4 * 256 + lane * 4;
      float a[4] = {0, 0, 0, 0}, b[4] = {0, 0, 0, 0}, c[4] = {0, 0, 0, 0};
      mma16(a, va[0], va[1], va[2], va[3], p[0], p[1]); mma16(b, va[4], va[5], va[6], va[7], p[2], p[3]); mma8(c, va[8], va[9], p[4]);
      const uint32_t u0 = pack2(a[0] + b[0] + c[0], a[1] + b[1] + c[1]), u1 = pack2(a[2] + b[2] + c[2], a[3] + b[3] + c[3]);
      sts1(sb + uo, u0); sts1(sb + uo + 128, u1);
      __syncwarp();
      if (lane == 0) mbar_arrive(sb + B_V);
#pragma unroll
      for (int q = 1; q < 4; q++) { const uint32_t rs = mapa(sb, rk ^ q); sta1(rs + uo + q * 1024, u0, rs + B_U); sta1(rs + uo + q * 1024 + 128, u1, rs + B_U); }
      asm volatile("{.reg .pred p; .reg .b32 a; setp.lt.u32 p,%1,%3; @p mapa.shared::cluster.u32 a,%0,%2; @p mbarrier.arrive.shared::cluster.b64 _,[a];}" ::"r"(sb + B_XF), "r"(tid - 256 - XG), "r"(tid - 256), "n"(9 - XG) : "memory");
      PT(4)
      if (w4 == 3) {
        wo_tile<0, 4>(nullptr, sb, 8, lane, y_offset(cta, 8, lane), s);
      } else if (tid == 288 && rk < 9) { mbar_wait(sb + B_XF, s & 1); x_load(P, sb, rk, s + 1); }
      PT(2)
    }
    lane = opq(tid) & 31;
    uint32_t ox[8], tu;
    {
      float o[16];
      const uint64_t dp = mkdesc(sb + R_P, 128, 640, 0);
      bar_sync(N_WO, 384);
      wg_fence();
      wg_rs32(o, va, dp, 0); wg_rs32(o, va + 4, dp + 16, 1); wg_rs32(o, va + 8, mkdesc(sb + R_P + 512, 0, 640, 0), 1);
      wg_commit();
      tu = clk32();
      wg_wait<0>();
      PT(3)
#pragma unroll
      for (int i = 0; i < 8; i++) ox[i] = pack2(o[2 * i], o[2 * i + 1]);
    }
    if (!last) {
      const uint8_t* y = (const uint8_t*)g_Y + (s & 1) * YSLOT + yg;
      uint32_t w0[8], w1[8], w2[8];
      while (clk32() - tu < (uint32_t)YD) {}
      y_load(w0, y); y_load(w1, y + 4 * 16384);
      if (w4 == 0) y_load(w2, y + 8 * 16384);
      else {
#pragma unroll
        for (int i = 0; i < 8; i++) w2[i] = ((s >> 1) & 1) ^ 1;
      }
      PT(5)
      const uint32_t dst = R_H + w4 * 5120 + (rk >> 1) * 128 + ((((rk & 1) * 4 + (lane >> 3)) ^ (rk >> 1)) << 4) + (lane & 4) * 2;
      const uint32_t tag = ((s >> 1) & 1) ^ 1, sel = (lane & 4) ? 0x3f800000u : 0x3f80u;
      uint32_t r0[2], r1[2], r2[2];
#pragma unroll 1
      for (int it = 0; (y_missing(w0, tag) | y_missing(w1, tag) | y_missing(w2, tag)) && it < (1 << 20); it++) {
        y_reload(w0, y, tag); y_reload(w1, y + 4 * 16384, tag); y_reload(w2, y + 8 * 16384, tag);
      }
      PT(7)
      y_sum(r0, w0, sel); y_sum(r1, w1, sel); y_sum(r2, w2, sel);
      y_send(r0, sb, dst, B_Z0, lane);
      bar_arrive(N_SUM, 384);
      y_send(r1, sb, dst + 4 * 5120, B_Z1, lane);
      if (w4 == 0) y_send(r2, sb, dst + 8 * 5120, B_Z1, lane);
      PT(9)
    }
#pragma unroll
    for (int h = 0; h < 2; h++) stsm4t(sb + R_OX + lane * 128 + (((w4 * 2 + h) ^ (lane & 7)) << 4), ox[h], ox[2 + h], ox[4 + h], ox[6 + h]);
    if (last) break;
    fence_async();
    bar_arrive(N_O, 160);
    PT(11)
  }
  fence_async();
  bar_sync(N_O, 160);
  if (tid == 256) {
    tma_store(&P.ctx, sb + R_OX, cta * 64, SEQ - 32); bulk_commit(); bulk_wait<0>(); CT(2, 0) signal_after_bulk(S_CTXB + 15); CT(2, 1)
  }
  __syncwarp();
  LT(1)
  asm volatile("barrier.cluster.arrive.relaxed.aligned;" ::: "memory");
  if (tid == 256) {
    const int m = TAIL0 + (cta >> 4), n = rk / 5, q = rk - n * 5;
    mbar_expect(sb + B_R, rk == 15 ? 9 * 4096 : q < 2 ? 12 * 4096 : 8 * 4096);
    if (rk < 15) out_produce<4, false>(P.o, sb, sb + B_O, m, n, q * 13, q == 4 ? 12 : 13, S_CTXB + m);
  }
  __syncwarp();
  asm volatile("barrier.cluster.wait.aligned;" ::: "memory");
}

__global__ void __launch_bounds__(384, 1) rec_kernel(const __grid_constant__ RecParams P) {
  extern __shared__ __align__(1024) uint8_t smem_raw[];
  const uint32_t sb = s2u(smem_raw);
  const int tid = threadIdx.x, cta = blockIdx.x;
  TL_START(1)
  pdl_trigger();
  if (tid == 0) {
    for (int i = 0; i < 22; i++) mbar_init(sb + R_BAR + 8 * i, 8 * i == B_XF - R_BAR ? 16 : 8 * i == B_V - R_BAR ? 4 : i >= 16 && i < 20 ? 2 : 1);
    asm volatile("fence.mbarrier_init.release.cluster;" ::: "memory");
    asm volatile("cp.async.bulk.prefetch.L2.global [%0],%1;" ::"l"(P.x_raw + cta * DM), "r"(DM * 2) : "memory");
    mbar_expect(sb + B_W0, 73728); mbar_expect(sb + B_W1, 73728); mbar_expect(sb + B_W2, 73728); mbar_expect(sb + B_W3, 73728);
#pragma unroll 1
    for (int i = 0; i < 3; i++) { tma_load(sb + R_WV + i * 24576, &P.wq, cta * 64, i * 192, sb + B_W0); tma_load(sb + R_H + i * 24576, &P.wk, cta * 64, i * 192, sb + B_W1); }
    mbar_expect(sb + B_XA, XG * 4096); mbar_expect(sb + B_XB, (9 - XG) * 4096);
  }
  __syncthreads();
  if (tid >= 256) { reg_dec<504 - 2 * RP>(); rec_aux(P, sb, cta); }
  else { reg_inc<RP>(); rec_proj(P, sb, cta); }
  TL_END(1)
  if (tid == 0) CT(7, 2)
  cluster_sync_relaxed();
}
typedef CUresult (*EncFn)(CUtensorMap*, CUtensorMapDataType, cuuint32_t, void*, const cuuint64_t*, const cuuint64_t*, const cuuint32_t*, const cuuint32_t*,
                          CUtensorMapInterleave, CUtensorMapSwizzle, CUtensorMapL2promotion, CUtensorMapFloatOOBfill);
static EncFn g_enc;
static CUtensorMap mk(const void* p, uint64_t cols, uint64_t rows, uint64_t pitch_elems, uint32_t box_rows, uint32_t box_cols = 64) {
  CUtensorMap m;
  cuuint64_t dim[2] = {cols, rows}, str[1] = {pitch_elems * 2};
  cuuint32_t box[2] = {box_cols, box_rows}, es[2] = {1, 1};
  g_enc(&m, CU_TENSOR_MAP_DATA_TYPE_BFLOAT16, 2, (void*)p, dim, str, box, es, CU_TENSOR_MAP_INTERLEAVE_NONE, box_cols == 64 ? CU_TENSOR_MAP_SWIZZLE_128B : CU_TENSOR_MAP_SWIZZLE_NONE,
        CU_TENSOR_MAP_L2_PROMOTION_L2_256B, CU_TENSOR_MAP_FLOAT_OOB_FILL_NONE);
  return m;
}
template <class T> static void* sym(T& s) { void* p; cudaGetSymbolAddress(&p, s); return p; }

#define FE 6
#define STG 10
#define FHC 22
#define FSL 4
#define NOE 6
#define OMC true
template <class K, class A> static void launch(K k, int grid, int smem, int cluster, bool pdl, const A& arg) {
  cudaLaunchConfig_t c = {};
  cudaLaunchAttribute at[2];
  int n = 0;
  if (cluster > 1) { at[n].id = cudaLaunchAttributeClusterDimension; at[n].val.clusterDim.x = cluster; at[n].val.clusterDim.y = at[n].val.clusterDim.z = 1; n++; }
  if (pdl) { at[n].id = cudaLaunchAttributeProgrammaticStreamSerialization; at[n].val.programmaticStreamSerializationAllowed = 1; n++; }
  c.gridDim = grid; c.blockDim = 384; c.dynamicSmemBytes = smem; c.stream = cudaStreamPerThread; c.attrs = at; c.numAttrs = n;
  cudaLaunchKernelEx(&c, k, arg);
}

extern "C" void kernel_launch(void* const* d_in, const int* in_sizes, int n_in, void* d_out, int out_size) {
  static int nb;
  if (!g_enc) {
    cudaDriverEntryPointQueryResult qr;
    cudaGetDriverEntryPoint("cuTensorMapEncodeTiled", (void**)&g_enc, cudaEnableDefault, &qr);
    cudaDeviceGetAttribute(&nb, cudaDevAttrMultiProcessorCount, 0);
    nb = nb - 64 < 16 ? 16 : nb - 64 > 128 ? 128 : (nb - 64) & ~1;
    cudaFuncSetAttribute(proj_kernel, cudaFuncAttributeMaxDynamicSharedMemorySize, SM_P);
    cudaFuncSetAttribute(out_kernel<false>, cudaFuncAttributeMaxDynamicSharedMemorySize, SM_O);
    cudaFuncSetAttribute(out_kernel<true>, cudaFuncAttributeMaxDynamicSharedMemorySize, SM_O);
    cudaFuncSetAttribute(fa_kernel, cudaFuncAttributeMaxDynamicSharedMemorySize, SM_F);
    cudaFuncSetAttribute(rec_kernel, cudaFuncAttributeMaxDynamicSharedMemorySize, R_END);
    cudaFuncSetAttribute(rec_kernel, cudaFuncAttributeNonPortableClusterSizeAllowed, 1);
  }
  const bf16 *Ax = (const bf16*)d_in[0], *Ac = (const bf16*)d_in[1], *Awq = (const bf16*)d_in[2], *Awk = (const bf16*)d_in[3], *Awv = (const bf16*)d_in[4],
             *Awo = (const bf16*)d_in[5], *Bx = (const bf16*)d_in[6], *Bm = (const bf16*)d_in[7], *Bwq = (const bf16*)d_in[8], *Bwk = (const bf16*)d_in[9],
             *Bwv = (const bf16*)d_in[10], *Bwo = (const bf16*)d_in[11];
  bf16* out = (bf16*)d_out;
  ProjParams p;
  p.a[0] = mk(Ac, 512, SEQ, 512, 128); p.a[1] = mk(Ax, DM, SEQ, DM, 128);
  p.w[0] = mk(Awk, HD, 512, HD, 64); p.w[1] = mk(Awv, HD, 512, HD, 64); p.w[2] = mk(Awq, HD, DM, HD, 64);
  p.c[0] = mk(sym(g_kA), HD, SEQ, HD, 64); p.c[1] = mk(sym(g_vA), HD, SEQ, HD, 64); p.c[2] = mk(sym(g_qA), HD, SEQ, HD, 64);
  {
    int parts[16];
    for (int i = 0; i < 16; i++) parts[i] = 1;
    for (int e = 0; e < nb / 2 - 16; e++) parts[e % 24 < 16 ? e % 8 : 15 - (e % 24 - 16)]++;
    p.nitems = 0;
    for (int i = 15; i >= 0; i--)
      for (int j = 0, nc = i < 8 ? 32 : 16, a = parts[i]; j < a; j++) {
        ProjItem& I = p.item[p.nitems++];
        I.pa = i >> 3; I.m = i & 7;
        I.c0[0] = j * nc / a; I.n[0] = (j + 1) * nc / a - I.c0[0];
        I.c0[1] = (j * nc + a - 1) / a; I.n[1] = ((j + 1) * nc + a - 1) / a - I.c0[1];
        if (i < 8 && a == 3) { const int d = STG * (i + 4) / 11, b1 = 11 - d, b2 = 22 - d + (i - 4) * STG / 16; I.c0[1] = j == 0 ? 0 : j == 1 ? b1 : b2; I.n[1] = (j == 0 ? b1 : j == 1 ? b2 : 32) - I.c0[1]; }
      }
  }
  OutParams o;
  for (int i = 0; i < 2; i++) {
    o.p[i].a = mk(i ? sym(g_ctxB) : sym(g_qA), HD, SEQ, HD, 128); o.p[i].b = mk(i ? Bwo : Awo, DM, HD, DM, 64); o.p[i].bh = mk(i ? Bwo : Awo, DM, HD, DM, 32);
    o.c[i] = mk(out + i * DM, DM, SEQ, 2 * DM, 64);
  }
  FaParams f;
  f.q = mk(sym(g_qA), HD, SEQ, HD, 128); f.k = mk(sym(g_kA), HD, SEQ, HD, 128); f.v = mk(sym(g_vA), HD, SEQ, HD, 128); f.o = mk(sym(g_qA), HD, SEQ, HD, 64);
  f.nctas = nb;
  for (int i = 0; i < 9; i++) f.nproj[i] = 0;
  for (int i = 0; i < p.nitems; i++) f.nproj[p.item[i].pa * (p.item[i].m + 1)] += 4;
  for (int key = -90, n = 0; n < 512; key++)
    for (int h = 0; h < 32; h++)
      for (int qt = 0; qt < 16; qt++)
        if ((h < FHC ? h : FHC) * FSL - qt * 2 - (qt >= 12 && h < FE ? 60 : 0) == key) f.order[n++] = qt * 32 + h;
  RecParams r;
  r.wq = mk(Bwq, HD, DM, HD, 192); r.wk = mk(Bwk, HD, DM, HD, 192); r.wv = mk(Bwv, HD, DM, HD, 192); r.wo = mk(Bwo, DM, HD, DM, 64, 144);
  r.x_raw = Bx;
  r.x = mk(Bx, DM, SEQ, DM, 32); r.ctx = mk(sym(g_ctxB), HD, SEQ, HD, 32); r.mem0 = Bm; r.o = o.p[1]; r.out = out;

  launch(rec_kernel, 64, R_END, 16, false, r);
  launch(proj_kernel, nb, SM_P, 2, true, p);
  launch(fa_kernel, nb - NOE * 3, SM_F, 1, true, f);
  o.m0 = 0; o.nb = NOE * 3; o.id = 4;
  launch(out_kernel<false>, o.nb, SM_O, 1, true, o);
  launch(fa_kernel, NOE * 3, SM_F, 1, true, f);
  o.m0 = NOE; o.nb = (TAIL0 - NOE) * 3; o.id = 5;
  launch(out_kernel<OMC>, o.nb + 48, SM_O, OMC ? 2 : 1, true, o);
}
```

```cpp
#include <cuda_runtime.h>
#include <cuda_bf16.h>
#include <cuda.h>
#include <stdint.h>

typedef __nv_bfloat16 bf16;
#define DEVI __device__ __forceinline__
#define WAIT_FAIL(code) break
#define WAIT_MAX (1 << 22)

constexpr int SEQ = 2048, HD = 4096, DM = 576, NSEG = 64;

__device__ __align__(1024) bf16 g_qA[SEQ * HD], g_kA[SEQ * HD], g_vA[SEQ * HD];
__device__ __align__(1024) bf16 g_ctxB[SEQ * HD];
__device__ __align__(1024) uint4 g_Y[2 * 9 * 16 * 64];
enum { S_QUEUE = 0, S_EXIT = 1, S_PROJ = 32, S_CTXA = 64, S_CTXB = 96 };
__device__ unsigned g_sync[128];
#define LT(i)
#define CT(k, i) {}
#define TL_START(i)
#define TL_END(i)

DEVI uint32_t s2u(const void* p) { return (uint32_t)__cvta_generic_to_shared(p); }
DEVI void mbar_init(uint32_t b, uint32_t c) { asm volatile("mbarrier.init.shared::cta.b64 [%0],%1;" ::"r"(b), "r"(c)); }
DEVI void mbar_expect(uint32_t b, uint32_t n) { asm volatile("mbarrier.arrive.expect_tx.shared::cta.b64 _,[%0],%1;" ::"r"(b), "r"(n) : "memory"); }
DEVI void mbar_arrive(uint32_t b) { asm volatile("mbarrier.arrive.shared::cta.b64 _,[%0];" ::"r"(b) : "memory"); }
DEVI void mbar_wait(uint32_t b, uint32_t ph) {
  uint32_t ok; int it = 0;
  do {
    asm volatile("{.reg .pred p; mbarrier.try_wait.parity.shared::cta.b64 p,[%1],%2; selp.u32 %0,1,0,p;}" : "=r"(ok) : "r"(b), "r"(ph) : "memory");
    if (!ok && ++it > WAIT_MAX) WAIT_FAIL(b & 0xffffff);
  } while (!ok);
}
DEVI bool mbar_try(uint32_t b, uint32_t ph) {
  uint32_t ok;
  asm volatile("{.reg .pred p; mbarrier.try_wait.parity.shared::cta.b64 p,[%1],%2; selp.u32 %0,1,0,p;}" : "=r"(ok) : "r"(b), "r"(ph) : "memory");
  return ok;
}
DEVI bool mbar_test(uint32_t b, uint32_t ph) {
  uint32_t ok;
  asm volatile("{.reg .pred p; mbarrier.test_wait.parity.shared::cta.b64 p,[%1],%2; selp.u32 %0,1,0,p;}" : "=r"(ok) : "r"(b), "r"(ph) : "memory");
  return ok;
}
DEVI void mwait(uint32_t b, uint32_t ph) { if (__builtin_expect(!mbar_try(b, ph), 0)) mbar_wait(b, ph); }
DEVI void tma_load(uint32_t dst, const CUtensorMap* tm, int c0, int c1, uint32_t bar) {
  asm volatile("cp.async.bulk.tensor.2d.shared::cluster.global.mbarrier::complete_tx::bytes [%0],[%1,{%3,%4}],[%2];" ::"r"(dst), "l"(tm), "r"(bar), "r"(c0), "r"(c1) : "memory");
}
DEVI void tma_store(const CUtensorMap* tm, uint32_t src, int c0, int c1) {
  asm volatile("cp.async.bulk.tensor.2d.global.shared::cta.bulk_group [%0,{%2,%3}],[%1];" ::"l"(tm), "r"(src), "r"(c0), "r"(c1) : "memory");
}
DEVI void bulk_commit() { asm volatile("cp.async.bulk.commit_group;" ::: "memory"); }
template <int N> DEVI void bulk_wait_read() { asm volatile("cp.async.bulk.wait_group.read %0;" ::"n"(N) : "memory"); }
template <int N> DEVI void bulk_wait() { asm volatile("cp.async.bulk.wait_group %0;" ::"n"(N) : "memory"); }
DEVI void fence_async() { asm volatile("fence.proxy.async.shared::cta;" ::: "memory"); }
DEVI void bar_sync(int id, int n) { asm volatile("bar.sync %0,%1;" ::"r"(id), "r"(n) : "memory"); }
DEVI void bar_arrive(int id, int n) { asm volatile("bar.arrive %0,%1;" ::"r"(id), "r"(n) : "memory"); }
template <int R> DEVI void reg_inc() { asm volatile("setmaxnreg.inc.sync.aligned.u32 %0;" ::"n"(R)); }
template <int R> DEVI void reg_dec() { asm volatile("setmaxnreg.dec.sync.aligned.u32 %0;" ::"n"(R)); }
DEVI void wg_fence() { asm volatile("wgmma.fence.sync.aligned;" ::: "memory"); }
DEVI void wg_commit() { asm volatile("wgmma.commit_group.sync.aligned;" ::: "memory"); }
template <int N> DEVI void wg_wait() { asm volatile("wgmma.wait_group.sync.aligned %0;" ::"n"(N) : "memory"); }
DEVI uint64_t desc_k(uint32_t a) { return (uint64_t)((a >> 4) & 0x3fff) | (1ull << 16) | (64ull << 32) | (1ull << 62); }
DEVI uint64_t desc_mn(uint32_t a, uint32_t lbo) { return (uint64_t)((a >> 4) & 0x3fff) | ((uint64_t)(lbo >> 4) << 16) | (64ull << 32) | (1ull << 62); }
DEVI uint64_t mkdesc(uint32_t a, uint32_t lbo, uint32_t sbo, int sw) { return (uint64_t)((a >> 4) & 0x3fff) | ((uint64_t)(lbo >> 4) << 16) | ((uint64_t)(sbo >> 4) << 32) | ((uint64_t)sw << 62); }
DEVI uint32_t pack2(float lo, float hi) { uint32_t r; asm("cvt.rn.bf16x2.f32 %0,%1,%2;" : "=r"(r) : "f"(hi), "f"(lo)); return r; }
DEVI float ex2(float x) { float y; asm("ex2.approx.ftz.f32 %0,%1;" : "=f"(y) : "f"(x)); return y; }
DEVI void stsm4(uint32_t a, uint32_t r0, uint32_t r1, uint32_t r2, uint32_t r3) {
  asm volatile("stmatrix.sync.aligned.m8n8.x4.shared.b16 [%0],{%1,%2,%3,%4};" ::"r"(a), "r"(r0), "r"(r1), "r"(r2), "r"(r3) : "memory");
}
DEVI void ldsm4(uint32_t* r, uint32_t a) {
  asm volatile("ldmatrix.sync.aligned.m8n8.x4.shared.b16 {%0,%1,%2,%3},[%4];" : "=r"(r[0]), "=r"(r[1]), "=r"(r[2]), "=r"(r[3]) : "r"(a) : "memory");
}
DEVI void ldsm4t(uint32_t* r, uint32_t a) {
  asm volatile("ldmatrix.sync.aligned.m8n8.x4.trans.shared.b16 {%0,%1,%2,%3},[%4];" : "=r"(r[0]), "=r"(r[1]), "=r"(r[2]), "=r"(r[3]) : "r"(a) : "memory");
}
DEVI void mma16(float* d, uint32_t a0, uint32_t a1, uint32_t a2, uint32_t a3, uint32_t b0, uint32_t b1) {
  asm volatile("mma.sync.aligned.m16n8k16.row.col.f32.bf16.bf16.f32 {%0,%1,%2,%3},{%4,%5,%6,%7},{%8,%9},{%0,%1,%2,%3};"
               : "+f"(d[0]), "+f"(d[1]), "+f"(d[2]), "+f"(d[3]) : "r"(a0), "r"(a1), "r"(a2), "r"(a3), "r"(b0), "r"(b1));
}

DEVI void pdl_trigger() { asm volatile("griddepcontrol.launch_dependents;" ::: "memory"); }
DEVI void signal_after_bulk(int f) {
  asm volatile("fence.proxy.async.global;" ::: "memory");
  asm volatile("red.release.gpu.global.add.u32 [%0], 1;" ::"l"(g_sync + f) : "memory");
}
DEVI void flag_wait(int f, unsigned n, unsigned waiters) {
  for (int it = 0;; it++) {
    if (it > WAIT_MAX) WAIT_FAIL(f);
    unsigned v; asm volatile("ld.acquire.gpu.global.u32 %0, [%1];" : "=r"(v) : "l"(g_sync + f) : "memory");
    if (v >= n) break;
    __nanosleep(64);
  }
  if (waiters) asm volatile("red.relaxed.gpu.global.inc.u32 [%0], %1;" ::"l"(g_sync + f), "r"(n + waiters - 1) : "memory");
  asm volatile("fence.proxy.async.global;" ::: "memory");
}
DEVI uint32_t mapa(uint32_t a, uint32_t r) { uint32_t o; asm("mapa.shared::cluster.u32 %0,%1,%2;" : "=r"(o) : "r"(a), "r"(r)); return o; }
DEVI void tma_load_mc(uint32_t dst, const CUtensorMap* tm, int c0, int c1, uint32_t bar, uint16_t mask) {
  asm volatile("cp.async.bulk.tensor.2d.shared::cluster.global.mbarrier::complete_tx::bytes.multicast::cluster [%0],[%1,{%3,%4}],[%2],%5;" ::"r"(dst), "l"(tm), "r"(bar), "r"(c0), "r"(c1), "h"(mask) : "memory");
}
DEVI void arrive_pair(uint32_t b) { if ((threadIdx.x & 127) < 2) asm volatile("mbarrier.arrive.shared::cluster.b64 _,[%0];" ::"r"(mapa(b, threadIdx.x & 1)) : "memory"); }
DEVI void cluster_sync_relaxed() { asm volatile("barrier.cluster.arrive.relaxed.aligned; barrier.cluster.wait.aligned;" ::: "memory"); }
DEVI void cluster_sync() { asm volatile("barrier.cluster.arrive.aligned; barrier.cluster.wait.aligned;" ::: "memory"); }
DEVI void sts4(uint32_t a, uint32_t x, uint32_t y, uint32_t z, uint32_t w) { asm volatile("st.shared.v4.b32 [%0],{%1,%2,%3,%4};" ::"r"(a), "r"(x), "r"(y), "r"(z), "r"(w) : "memory"); }
DEVI void lds4(uint32_t* r, uint32_t a) { asm volatile("ld.shared.v4.b32 {%0,%1,%2,%3},[%4];" : "=r"(r[0]), "=r"(r[1]), "=r"(r[2]), "=r"(r[3]) : "r"(a) : "memory"); }
DEVI void sta4(uint32_t d, uint32_t a, uint32_t b, uint32_t c, uint32_t e, uint32_t bar) {
  asm volatile("st.async.weak.shared::cluster.mbarrier::complete_tx::bytes.v4.b32 [%0],{%1,%2,%3,%4},[%5];" ::"r"(d), "r"(a), "r"(b), "r"(c), "r"(e), "r"(bar) : "memory");
}
DEVI float blo(uint32_t u) { return __uint_as_float(u << 16); }
DEVI float bhi(uint32_t u) { return __uint_as_float(u & 0xffff0000u); }

#define F8(a, o) "+f"(a[o]), "+f"(a[o + 1]), "+f"(a[o + 2]), "+f"(a[o + 3]), "+f"(a[o + 4]), "+f"(a[o + 5]), "+f"(a[o + 6]), "+f"(a[o + 7])
#define F32(a, o) F8(a, o), F8(a, o + 8), F8(a, o + 16), F8(a, o + 24)
template<int TB> DEVI void wg_ss128(float* d, uint64_t da, uint64_t db, int acc){
 asm volatile("{.reg .pred p; setp.ne.b32 p,%66,0;\n wgmma.mma_async.sync.aligned.m64n128k16.f32.bf16.bf16 {%0,%1,%2,%3,%4,%5,%6,%7,%8,%9,%10,%11,%12,%13,%14,%15,%16,%17,%18,%19,%20,%21,%22,%23,%24,%25,%26,%27,%28,%29,%30,%31,%32,%33,%34,%35,%36,%37,%38,%39,%40,%41,%42,%43,%44,%45,%46,%47,%48,%49,%50,%51,%52,%53,%54,%55,%56,%57,%58,%59,%60,%61,%62,%63},%64,%65,p,1,1,0,%67;}"
 : F32(d,0),F32(d,32) : "l"(da),"l"(db),"r"(acc),"n"(TB));}
template<int TB> DEVI void wg_ss192(float* d, uint64_t da, uint64_t db, int acc){
 asm volatile("{.reg .pred p; setp.ne.b32 p,%98,0;\n wgmma.mma_async.sync.aligned.m64n192k16.f32.bf16.bf16 {%0,%1,%2,%3,%4,%5,%6,%7,%8,%9,%10,%11,%12,%13,%14,%15,%16,%17,%18,%19,%20,%21,%22,%23,%24,%25,%26,%27,%28,%29,%30,%31,%32,%33,%34,%35,%36,%37,%38,%39,%40,%41,%42,%43,%44,%45,%46,%47,%48,%49,%50,%51,%52,%53,%54,%55,%56,%57,%58,%59,%60,%61,%62,%63,%64,%65,%66,%67,%68,%69,%70,%71,%72,%73,%74,%75,%76,%77,%78,%79,%80,%81,%82,%83,%84,%85,%86,%87,%88,%89,%90,%91,%92,%93,%94,%95},%96,%97,p,1,1,0,%99;}"
 : F32(d,0),F32(d,32),F32(d,64) : "l"(da),"l"(db),"r"(acc),"n"(TB));}
template<int TB> DEVI void wg_rs128(float* d, const uint32_t* a, uint64_t db, int acc){
 asm volatile("{.reg .pred p; setp.ne.b32 p,%69,0;\n wgmma.mma_async.sync.aligned.m64n128k16.f32.bf16.bf16 {%0,%1,%2,%3,%4,%5,%6,%7,%8,%9,%10,%11,%12,%13,%14,%15,%16,%17,%18,%19,%20,%21,%22,%23,%24,%25,%26,%27,%28,%29,%30,%31,%32,%33,%34,%35,%36,%37,%38,%39,%40,%41,%42,%43,%44,%45,%46,%47,%48,%49,%50,%51,%52,%53,%54,%55,%56,%57,%58,%59,%60,%61,%62,%63},{%64,%65,%66,%67},%68,p,1,1,%70;}"
 : F32(d,0),F32(d,32) : "r"(a[0]),"r"(a[1]),"r"(a[2]),"r"(a[3]),"l"(db),"r"(acc),"n"(TB));}
DEVI void wg_ss96t(float* d, uint64_t da, uint64_t db, int acc){
 asm volatile("{.reg .pred p; setp.ne.b32 p,%50,0;\n wgmma.mma_async.sync.aligned.m64n96k16.f32.bf16.bf16 {%0,%1,%2,%3,%4,%5,%6,%7,%8,%9,%10,%11,%12,%13,%14,%15,%16,%17,%18,%19,%20,%21,%22,%23,%24,%25,%26,%27,%28,%29,%30,%31,%32,%33,%34,%35,%36,%37,%38,%39,%40,%41,%42,%43,%44,%45,%46,%47},%48,%49,p,1,1,0,1;}"
 : F32(d,0),F8(d,32),F8(d,40) : "l"(da),"l"(db),"r"(acc));}
struct ProjItem { uint8_t pa, m, c0[2], n[2], s0, leave; };
struct ProjParams { CUtensorMap a[2], w[3], c[3]; ProjItem item[64]; };
constexpr int PST = 12, P_STG = PST * 16384, P_FULL = P_STG + 32768 + 256, P_EMPTY = P_FULL + 8 * PST, P_OF = P_EMPTY + 8 * PST, P_OE = P_OF + 16, P_END = P_OE + 16;
DEVI void proj_decode(const ProjItem& I, int t, int& pw, int& n) {
  const int g = t >= I.n[0], c = g ? I.c0[1] + t - I.n[0] : I.c0[0] + t;
  pw = I.pa ? 2 : c >> 4; n = (c & 15) + g * 16;
}
DEVI void proj_init(const ProjItem& I, uint32_t base) {
  for (int i = 0; i < PST; i++) { mbar_init(base + P_FULL + 8 * i, 1); mbar_init(base + P_EMPTY + 8 * i, 4); }
  for (int i = 0; i < 2; i++) { mbar_init(base + P_OF + 8 * i, 4); mbar_init(base + P_OE + 8 * i, 1); }
  mbar_init(base + P_END, 1);
  for (int i = 0; i < I.s0; i++) {
    mbar_arrive(base + P_FULL + 8 * i);
    asm volatile("mbarrier.arrive.shared::cta.b64 _,[%0],4;" ::"r"(base + P_EMPTY + 8 * i) : "memory");
  }
}
DEVI int proj_produce(const ProjParams& P, const ProjItem& I, uint32_t base) {
  const int nk = 8 + I.pa, r = blockIdx.x & 1;
  int s = I.s0, ph = 1;
  for (int t = -1; t < I.n[0] + I.n[1]; t++) {
    int pw, n; proj_decode(I, t, pw, n);
    if (t == I.n[0] + I.n[1] - 1) mbar_arrive(base + P_END);
    for (int k = 0; k < nk; k++) {
      if (t >= 0) mbar_wait(base + P_EMPTY + 8 * s, ph);
      mbar_expect(base + P_FULL + 8 * s, 16384);
      if (t < 0) tma_load(base + s * 16384, &P.a[I.pa], k * 64, (I.m * 2 + r) * 128, base + P_FULL + 8 * s);
      else tma_load_mc(base + s * 16384 + r * 8192, &P.w[pw], n * 128 + r * 64, k * 64, base + P_FULL + 8 * s, 3);
      if (++s == PST) { s = 0; ph ^= 1; }
    }
  }
  return ph;
}
DEVI void proj_store(const ProjParams& P, const ProjItem& I, uint32_t base, int g) {
  const int r0 = (I.m * 2 + (blockIdx.x & 1)) * 128 + g * 64;
  for (int t = 0; t < I.n[0] + I.n[1]; t++) {
    int pw, n; proj_decode(I, t, pw, n);
    mbar_wait(base + P_OF + 8 * g, t & 1);
    tma_store(&P.c[pw], base + P_STG + g * 16384, n * 128, r0);
    tma_store(&P.c[pw], base + P_STG + g * 16384 + 8192, n * 128 + 64, r0);
    bulk_commit();
    bulk_wait_read<0>();
    mbar_arrive(base + P_OE + 8 * g);
    if (t == 3 && !g) CT(0, 1)
    if (t == I.n[0] - 1) { bulk_wait<0>(); signal_after_bulk(S_PROJ + I.pa * (I.m + 1) * 2); }
  }
  bulk_wait<0>(); signal_after_bulk(S_PROJ + I.pa * (I.m + 1) * 2 + 1);
  if (!g) CT(0, 2)
}
DEVI void proj_consume(const ProjItem& I, uint32_t base, int tid, int wg) {
  const uint32_t full = base + P_FULL;
  uint32_t A[36][4];
  float acc[64];
  uint32_t s = I.s0, ph = 0, c = 1;
  const uint32_t row = ((tid >> 5) & 3) * 16 + (tid & 15);
  const uint32_t roff = row * 128 + ((((tid >> 4) & 1) ^ (row & 7)) << 4);
  const uint32_t rel = mapa(base + P_EMPTY, tid & 1);
  auto release = [&](uint32_t st) { asm volatile("{.reg .pred p; setp.lt.u32 p,%1,2; @p mbarrier.arrive.shared::cluster.b64 _,[%0];}" ::"r"(rel + 8 * st), "r"(tid & 127) : "memory"); };
  const int pa = I.pa, nt = I.n[0] + I.n[1];
#pragma unroll
  for (int k = 0; k < 9; k++) {
    if (k < 8 || pa) {
      mbar_wait(full + 8 * s, ph);
#pragma unroll
      for (int kk = 0; kk < 4; kk++) ldsm4(A[4 * k + kk], base + s * 16384 + wg * 8192 + (roff ^ (kk * 32)));
      bar_sync(1 + wg, 128);
      release(s);
      if (++s == PST) { s = 0; ph ^= 1; }
    }
  }
  if (tid == 0) CT(0, 0)
  if (wg) bar_sync(5, 256);
  bool ok = false;
  for (int t = 0; t < nt; t++, c ^= 1) {
    uint32_t p1 = 0;
#pragma unroll
    for (int k = 0; k < 9; k++) {
      if (k < 8 || pa) {
        if (!ok) mbar_wait(full + 8 * s, ph);
        const uint64_t db = desc_mn(base + s * 16384, 8192);
        wg_fence();
#pragma unroll
        for (int kk = 0; kk < 4; kk++) wg_rs128<1>(acc, A[4 * k + kk], db + kk * 128, k | kk);
        wg_commit();
        const uint32_t cur = s;
        if (++s == PST) { s = 0; ph ^= 1; }
        ok = mbar_test(full + 8 * s, ph);
        if (k) { wg_wait<1>(); release(p1); }
        if (k == 4 && t == 0 && !wg) bar_arrive(5, 256);
        p1 = cur;
      }
    }
    mwait(base + P_OE + 8 * wg, c);
    wg_wait<0>();
    release(p1);
#pragma unroll
    for (int i = 0; i < 8; i++) {
      const float* a = acc + i * 8;
      stsm4(base + P_STG + wg * 16384 + (i >> 2) * 8192 + (roff ^ ((i & 3) * 32)), pack2(a[0], a[1]), pack2(a[2], a[3]), pack2(a[4], a[5]), pack2(a[6], a[7]));
    }
    fence_async();
    __syncwarp();
    if ((tid & 31) == 0) mbar_arrive(base + P_OF + 8 * wg);
  }
}

struct OutMaps { CUtensorMap a, b, c; };
template <int NST, bool MC, int G> DEVI void out_produce(const OutMaps& M, uint32_t base, uint32_t full, int m, int n, int k0, int nk, int flag) {
  constexpr int SB = 16384 + 384 * G;
  const int r = MC ? blockIdx.x & 1 : 0;
  int s = 0, ph = 1;
#pragma unroll 1
  for (int k = 0; k < nk + (MC ? NST - 1 : 0); k++) {
    mbar_wait(full + 8 * (NST + s), ph);
    if (k < nk) {
      mbar_expect(full + 8 * s, SB);
#pragma unroll 1
      for (int j = 0; j < 3; j++) {
        if (MC) tma_load_mc(base + s * SB + 16384 + j * 128 * G + r * 64 * G, &M.b, (n * 3 + j) * G, (k0 + k) * 64 + r * 32, full + 8 * s, 3);
        else tma_load(base + s * SB + 16384 + j * 128 * G, &M.b, (n * 3 + j) * G, (k0 + k) * 64, full + 8 * s);
      }
      if (flag >= 0 && k == 0) flag_wait(flag, 64, 30);
      if (flag < 0 && k == 32) mbar_wait(full + 16 * NST, 0);
      if (flag >= 0 || k >= NST) tma_load(base + s * SB, &M.a, (k0 + k) * 64, m * 128, full + 8 * s);
    }
    if (++s == NST) { s = 0; ph ^= 1; }
  }
}
template <int NST, int G> DEVI void out_first(const OutMaps& M, uint32_t base, uint32_t full, int m, int flag, int cnt) {
  flag_wait(flag, cnt, 192 / G);
#pragma unroll 1
  for (int k = 0; k < NST; k++) tma_load(base + k * (16384 + 384 * G), &M.a, k * 64, m * 128, full + 8 * k);
  if (cnt == 32) flag_wait(flag + 16, 32, 3);
  mbar_arrive(full + 16 * NST);
}
template <int NST, bool MC, int G> DEVI void out_consume(float* acc, uint32_t base, uint32_t full, int nk) {
  constexpr int SB = 16384 + 384 * G;
  const uint32_t empty = full + 8 * NST;
  const int wg = threadIdx.x >> 7;
  int s = 0, ph = 0, prev = 0;
#pragma unroll 1
  for (int k = 0; k < nk; k++) {
    mbar_wait(full + 8 * s, ph);
    const uint64_t da = desc_k(base + s * SB + wg * 8192), db = mkdesc(base + s * SB + 16384, 128 * G, 16 * G, G == 64 ? 1 : 2);
    wg_fence();
#pragma unroll
    for (int kk = 0; kk < 4; kk++) {
      if (G == 64) wg_ss192<1>(acc, da + kk * 2, db + kk * 128, k | kk);
      else wg_ss96t(acc, da + kk * 2, db + kk * 64, k | kk);
    }
    wg_commit();
    if (k) { wg_wait<1>(); if (MC) arrive_pair(empty + 8 * prev); else if ((threadIdx.x & 127) == 0) mbar_arrive(empty + 8 * prev); }
    prev = s;
    if (++s == NST) { s = 0; ph ^= 1; }
  }
  wg_wait<0>();
}
struct OutParams { OutMaps p[2]; int n, id; uint8_t tile[96]; };
#define WR 1
constexpr int SM_O = 172032 + 256;
template <bool MC, int G> __global__ void __launch_bounds__(384, 1) out_kernel(const __grid_constant__ OutParams P) {
  constexpr int NST = G == 64 ? 4 : 6;
  extern __shared__ __align__(1024) uint8_t smem_raw[];
  const uint32_t base = s2u(smem_raw), full = base + 172032;
  const int tid = threadIdx.x, wg = tid >> 7;
  const int t = P.tile[blockIdx.x], pb = t >> 7, m = (t >> 3) & 15, n = t & 7;
  TL_START(P.id)
  pdl_trigger();
  if (tid == 0) {
    for (int i = 0; i < NST; i++) { mbar_init(full + 8 * i, 1); mbar_init(full + 8 * (NST + i), MC ? 4 : 2); }
    mbar_init(full + 16 * NST, 1);
    asm volatile("fence.mbarrier_init.release.cluster;" ::: "memory");
  }
  if (MC) cluster_sync_relaxed(); else __syncthreads();
  if (wg == 2) {
    if (tid == 256) out_produce<NST, MC, G>(P.p[pb], base, full, m, n, 0, 64, -1);
    if (tid == 288) out_first<NST, G>(P.p[pb], base, full, m, (pb ? S_CTXB : S_CTXA) + m, pb ? 64 : 32);
  } else {
    float acc[G * 3 / 2];
    if (tid == 0) CT(P.id, 0)
    out_consume<NST, MC, G>(acc, base, full, 64);
    if (tid == 0) CT(P.id, 2)
    bar_sync(3, 256);
    const uint32_t row = ((tid >> 5) & 3) * 16 + (tid & 15);
    const uint32_t roff = row * 2 * G + ((((tid >> 4) & 1) ^ (G == 64 ? row & 7 : (row >> 1) & 3)) << 4);
#pragma unroll
    for (int i = 0; i < G * 3 / 16; i++) {
      const float* a = acc + i * 8;
      stsm4(base + wg * 384 * G + i / (G / 16) * 128 * G + (roff ^ (i % (G / 16) * 32)), pack2(a[0], a[1]), pack2(a[2], a[3]), pack2(a[4], a[5]), pack2(a[6], a[7]));
    }
    fence_async();
    bar_sync(1 + wg, 128);
    if ((tid & 127) == 0) {
      for (int c = 0; c < 3; c++) tma_store(&P.p[pb].c, base + wg * 384 * G + c * 128 * G, (n * 3 + c) * G, m * 128 + wg * 64);
      bulk_commit();
      if (WR) bulk_wait_read<0>(); else bulk_wait<0>();
    }
    TL_END(P.id)
  }
}
struct FaParams { ProjParams p; CUtensorMap q, k, v, o; unsigned proj, nctas; uint8_t nproj[12]; uint16_t order[512]; };
constexpr int SM_F = 7 * 32768 + 512;
constexpr float FA_C = 0.08838834764831845f * 1.4426950408889634f;
DEVI int fa_qt(int w) { return w >> 5; }
DEVI int fa_hc(int w) { return (w & 31) * 128; }

DEVI void fa_exp(const float* S, uint32_t* Pn, float mc0, float mc1, float& s0, float& s1) {
  float a0 = 0.f, a1 = 0.f, b0 = 0.f, b1 = 0.f;
#pragma unroll
  for (int j = 0; j < 16; j++) {
    const float e0 = ex2(fmaf(S[4 * j], FA_C, -mc0)), e1 = ex2(fmaf(S[4 * j + 1], FA_C, -mc0));
    const float e2 = ex2(fmaf(S[4 * j + 2], FA_C, -mc1)), e3 = ex2(fmaf(S[4 * j + 3], FA_C, -mc1));
    a0 += e0; a1 += e1; b0 += e2; b1 += e3;
    Pn[2 * j] = pack2(e0, e1); Pn[2 * j + 1] = pack2(e2, e3);
  }
  s0 = a0 + a1; s1 = b0 + b1;
}

struct FaState { float mc0, mc1, l0, l1; int w, j, qi; uint32_t dq; bool first; };
enum { F_Q = 0, F_K = 2 * 32768, F_V = 4 * 32768, F_O = 6 * 32768, F_QF = 7 * 32768, F_QE = F_QF + 16, F_KF = F_QF + 32, F_KE = F_QF + 48, F_VF = F_QF + 64, F_VE = F_QF + 80,
       F_OF = F_QF + 96, F_OE = F_QF + 112, F_INFO = F_QF + 128 };

template <int SC> DEVI bool fa_step(FaState& T, float* O, float* S, const uint32_t* Pc, uint32_t* Pn, uint32_t base, int tid, int wg, uint32_t ph) {
  const bool el = (tid & 127) == 0, fin = T.j == 0;
  int wn = T.w, jn = T.j - 1;
  const bool okk = mbar_try(base + F_KF + 8 * (SC ^ 1), ph), okv = mbar_try(base + F_VF + 8 * SC, ph ^ SC);
  if (fin) {
    T.qi++; T.dq ^= 2048;
    mbar_wait(base + F_QF + 8 * (T.qi & 1), (T.qi >> 1) & 1);
    asm volatile("ld.shared.b32 %0,[%1];" : "=r"(wn) : "r"(base + F_INFO + (T.qi & 1) * 4) : "memory");
    wn = __shfl_sync(~0u, wn, 0);
    jn = fa_qt(wn);
  }
  if (!(okk && okv)) { mbar_wait(base + F_KF + 8 * (SC ^ 1), ph); mbar_wait(base + F_VF + 8 * SC, ph ^ SC); }
  const bool last = wn < 0;
  {
    const uint64_t dq = desc_k(0) | T.dq, dk = desc_k(base + F_K + (SC ^ 1) * 32768), dv = desc_mn(base + F_V + SC * 32768, 16384);
    bar_sync(3 + wg, 256);
    wg_fence();
#pragma unroll
    for (int kk = 0; kk < 8; kk++) wg_ss128<0>(S, dq + (kk & 3) * 2 + (kk >> 2) * 1024, dk + (kk & 3) * 2 + (kk >> 2) * 1024, kk);
    wg_commit();
#pragma unroll
    for (int kk = 0; kk < 8; kk++) wg_rs128<1>(O, Pc + 4 * kk, dv + kk * 128, kk || !T.first);
    wg_commit();
    bar_arrive(4 - wg, 256);
  }
  wg_wait<1>();
  asm volatile("{.reg .pred p,q; setp.ne.u32 p,%0,0; setp.eq.and.u32 q,%1,0,p; @p mbarrier.arrive.shared::cta.b64 _,[%2]; @q mbarrier.arrive.shared::cta.b64 _,[%3];}"
               ::"r"((uint32_t)el), "r"(jn), "r"(base + F_KE + 8 * (SC ^ 1)), "r"(base + F_QE + 8 * (T.qi & 1)) : "memory");
  const float lp0 = T.l0, lp1 = T.l1;
  float s0 = 0.f, s1 = 0.f, f0 = 1.f, f1 = 1.f;
  bool exact = fin;
  if (!fin) {
    fa_exp(S, Pn, T.mc0, T.mc1, s0, s1);
    exact = __any_sync(~0u, !(fmaxf(s0, s1) <= 1073741824.f));
  }
  if (exact && !last) {
    float a = -INFINITY, b = -INFINITY;
    if (fin) {
      const int row = (tid >> 5) * 16 + ((tid & 31) >> 2) - (tid & 3) * 2;
#pragma unroll
      for (int j = 0; j < 16; j++) {
        if (j * 8 > row) S[4 * j] = -INFINITY;
        if (j * 8 + 1 > row) S[4 * j + 1] = -INFINITY;
        if (j * 8 > row + 8) S[4 * j + 2] = -INFINITY;
        if (j * 8 + 1 > row + 8) S[4 * j + 3] = -INFINITY;
      }
      T.mc0 = T.mc1 = -INFINITY;
    }
#pragma unroll
    for (int j = 0; j < 16; j++) { a = fmaxf(a, fmaxf(S[4 * j], S[4 * j + 1])); b = fmaxf(b, fmaxf(S[4 * j + 2], S[4 * j + 3])); }
    a = fmaxf(a, __shfl_xor_sync(~0u, a, 1)); b = fmaxf(b, __shfl_xor_sync(~0u, b, 1));
    a = fmaxf(a, __shfl_xor_sync(~0u, a, 2)); b = fmaxf(b, __shfl_xor_sync(~0u, b, 2));
    a = fmaxf(a * FA_C, T.mc0); b = fmaxf(b * FA_C, T.mc1);
    f0 = ex2(T.mc0 - a); f1 = ex2(T.mc1 - b);
    T.mc0 = a; T.mc1 = b;
    T.l0 = fin ? 0.f : T.l0 * f0; T.l1 = fin ? 0.f : T.l1 * f1;
    fa_exp(S, Pn, a, b, s0, s1);
  }
  T.l0 += s0; T.l1 += s1;
  wg_wait<0>();
  if (el) mbar_arrive(base + F_VE + 8 * SC);
  if (exact) {
    if (fin) {
      f0 = lp0 + __shfl_xor_sync(~0u, lp0, 1); f1 = lp1 + __shfl_xor_sync(~0u, lp1, 1);
      f0 += __shfl_xor_sync(~0u, f0, 2); f1 += __shfl_xor_sync(~0u, f1, 2);
      f0 = 1.f / f0; f1 = 1.f / f1;
    }
#pragma unroll
    for (int i = 0; i < 16; i++) { O[4 * i] *= f0; O[4 * i + 1] *= f0; O[4 * i + 2] *= f1; O[4 * i + 3] *= f1; }
    if (fin && (T.qi || last)) {
      const uint32_t row = ((tid >> 5) & 3) * 16 + (tid & 15);
      const uint32_t o = base + F_O + wg * 16384 + row * 128 + ((((tid >> 4) & 1) ^ (row & 7)) << 4);
      if (T.qi) mbar_wait(base + F_OE + 8 * wg, (T.qi & 1) ^ 1);
#pragma unroll
      for (int i = 0; i < 8; i++) {
        const float* a = O + i * 8;
        stsm4((o ^ ((i & 3) * 32)) + (i >> 2) * 8192, pack2(a[0], a[1]), pack2(a[2], a[3]), pack2(a[4], a[5]), pack2(a[6], a[7]));
      }
      if (el) asm volatile("st.shared.b32 [%0],%1;" ::"r"(base + F_INFO + 8 + wg * 4), "r"(!T.qi ? -1 : T.w | (last ? 1024 : 0)) : "memory");
      fence_async();
      __syncwarp();
      if ((tid & 31) == 0) mbar_arrive(base + F_OF + 8 * wg);
    }
  }
  T.w = wn; T.j = jn; T.first = fin;
  return last;
}

__global__ void __launch_bounds__(384, 1) fa_kernel(const __grid_constant__ FaParams P) {
  extern __shared__ __align__(1024) uint8_t smem_raw[];
  const uint32_t base = __shfl_sync(~0u, s2u(smem_raw), 0);
  const uint32_t sQ = base, sK = base + 2 * 32768, sV = base + 4 * 32768, sO = base + 6 * 32768, bars = base + 7 * 32768;
  const uint32_t qf = bars, qe = bars + 16, kf = bars + 32, ke = bars + 48, vf = bars + 64, ve = bars + 80, of = bars + 96, oe = bars + 112;
  volatile int* info = (volatile int*)(smem_raw + 7 * 32768 + 128);
  const int tid = threadIdx.x, wg = tid >> 7;
  const ProjItem& I = P.p.item[blockIdx.x >> 1];
  const bool leave = P.proj && I.leave;
  pdl_trigger();
  if (tid == 0) {
    if (P.proj) proj_init(I, base);
    for (int i = 0; i < 16; i++) mbar_init(bars + 8 * i, i >= 14 ? 1 : i >= 12 ? 4 : (i & 2) ? 2 : 1);
    info[4] = 0;
    asm volatile("fence.mbarrier_init.release.cluster;" ::: "memory");
  }
  __syncthreads();
  if (P.proj) cluster_sync_relaxed();
  if (wg == 2) {
    reg_dec<24>();
    if (tid == 256) {
      int it = 0, qi = 0, vc = 0, vr = -1, j = 0, hc = 0;
      int pph = P.proj ? proj_produce(P.p, I, base) : -1;
      auto drain = [&](int s0) { if (pph >= 0) for (int i = s0; i < s0 + 6; i++) mbar_wait(base + P_EMPTY + 8 * i, pph); };
      if (leave) { drain(0); drain(6); return; }
      CT(P.proj ? 3 : 6, 0)
      auto load_v = [&]() {
        if (vr < 0) return;
        const int s = (it - 1) & 1;
        drain(6); pph = -1;
        mbar_wait(ve + 8 * s, (((it - 1) >> 1) & 1) ^ 1 ^ s);
        mbar_expect(vf + 8 * s, 32768);
        tma_load(sV + s * 32768, &P.v, vc, vr, vf + 8 * s);
        tma_load(sV + s * 32768 + 16384, &P.v, vc + 64, vr, vf + 8 * s);
        vr = -1;
      };
      auto ready = [&](uint32_t m) { uint32_t v; asm volatile("ld.acquire.cta.shared.b32 %0,[%1];" : "=r"(v) : "r"(base + F_INFO + 16) : "memory"); return (v & m) == m; };
      for (it = -1;; it++) {
        if (it >= 0) {
          const int s = it & 1;
          if (it || j < 0) { drain(6); pph = -1; }
          mbar_wait(ke + 8 * s, ((it >> 1) & 1) ^ 1);
          if (j < 0) { mbar_arrive(kf + 8 * s); load_v(); break; }
          mbar_expect(kf + 8 * s, 32768);
          tma_load(sK + s * 32768, &P.k, hc, j * 128, kf + 8 * s);
          tma_load(sK + s * 32768 + 16384, &P.k, hc + 64, j * 128, kf + 8 * s);
        }
        int nc = hc, nr = it >= 0 ? j * 128 : -1;
        if (j-- == 0) {
          int w = atomicInc(&g_sync[S_QUEUE], 511 + P.nctas);
          w = w < 512 ? P.order[w] : -1;
          const uint32_t q = qi & 1, m = w < 0 ? 0x3ffff : (1u | (2u << (fa_qt(w) | 1))) << ((w >> 4) & 1);
          if (!ready(m) || !mbar_test(qe + 8 * q, ((qi >> 1) & 1) ^ 1)) {
            load_v(); it++; vc = nc; vr = nr; load_v(); it--; nr = -1;
            for (int n = 0; !ready(m) && n < WAIT_MAX; n++) __nanosleep(64);
            mbar_wait(qe + 8 * q, ((qi >> 1) & 1) ^ 1);
          }
          asm volatile("fence.proxy.async.global;" ::: "memory");
          if (it < 0) drain(0);
          info[q] = w;
          if (w < 0) mbar_arrive(qf + 8 * q);
          else {
            j = fa_qt(w); hc = fa_hc(w);
            mbar_expect(qf + 8 * q, 32768);
            tma_load(sQ + q * 32768, &P.q, hc, j * 128, qf + 8 * q);
            tma_load(sQ + q * 32768 + 16384, &P.q, hc + 64, j * 128, qf + 8 * q);
          }
          qi++;
        }
        load_v();
        vc = nc; vr = nr;
      }
      if (atomicInc(&g_sync[S_EXIT], P.nctas - 1) == P.nctas - 1)
        for (int i = 0; i < 18; i++) g_sync[S_PROJ + i] = 0;
    } else if (tid >= 352) {
      const int l = tid - 352;
      if (P.proj) mbar_wait(base + P_END, 0);
#pragma unroll 1
      for (int n = 0; n < WAIT_MAX && !leave; n++) {
        unsigned v = 255;
        if (l < 18) asm volatile("ld.acquire.gpu.global.u32 %0, [%1];" : "=r"(v) : "l"(g_sync + S_PROJ + l) : "memory");
        const uint32_t m = __ballot_sync(~0u, v >= P.nproj[(l >> 1) % 9]);
        __syncwarp();
        if (l == 0) asm volatile("st.release.cta.shared.b32 [%0],%1;" ::"r"(base + F_INFO + 16), "r"(m) : "memory");
        if (m == ~0u) break;
        __nanosleep(300);
      }
    } else if (tid == 288 || tid == 320) {
      const int g = tid == 320;
      if (P.proj) proj_store(P.p, I, base, g);
      if (leave) return;
      mbar_arrive(oe + 8 * g);
        for (int n = 0;; n++) {
          mbar_wait(of + 8 * g, n & 1);
          const int v = info[2 + g], w = v & 1023, qt = fa_qt(w), hc = fa_hc(w);
          if (v < 0) break;
          tma_store(&P.o, sO + g * 16384, hc, qt * 128 + g * 64);
          tma_store(&P.o, sO + g * 16384 + 8192, hc + 64, qt * 128 + g * 64);
          bulk_commit();
          bulk_wait_read<0>();
          mbar_arrive(oe + 8 * g);
          bulk_wait<0>();
          signal_after_bulk(S_CTXA + (w & 16) + qt);
          if (v & 1024) break;
        }
    }
  } else {
    reg_inc<240>();
    const uint32_t ub = base;
    const int uw = __shfl_sync(~0u, wg, 0);
    if (wg == 1 && !leave) bar_arrive(3, 256);
    if (P.proj) proj_consume(I, ub, tid, uw);
    if (leave) return;
    float O[64], S[64];
    uint32_t PA[32], PB[32];
#pragma unroll
    for (int i = 0; i < 32; i++) PA[i] = 0;
#pragma unroll
    for (int i = 0; i < 64; i++) O[i] = 0.f;
    FaState T = {0.f, 0.f, 1.f, 1.f, 0, 0, -1, ((ub + 32768 + uw * 8192) >> 4) & 0x3fff, true};
    for (uint32_t ph = 0;; ph ^= 1) {
      if (fa_step<1>(T, O, S, PA, PB, ub, tid, uw, ph)) break;
      if (fa_step<0>(T, O, S, PB, PA, ub, tid, uw, ph)) break;
    }
    if (wg == 0) bar_sync(3, 256);
  }
}
#define PS 20
#define PT(i)
#define YD 200
#define NPF 4
#define NRES 6
#define RP 208
#define PD 2
#define VR "............rrrrrr.................."
#define VP "222222222222111111111111------------"
constexpr int vr_index(int k) { int n = 0; for (int i = 0; i < k; i++) n += VR[i] == 'r'; return n; }
constexpr int VB = vr_index(36);
template <int K> struct VIdx { static constexpr int v = vr_index(K); static constexpr char r = VR[K], p = VP[K]; };
#define XG 6
#define XW 2
#define WOD 4000
#define ES 0
#define KA 26
constexpr int R_WV = 0, R_WO = 73728, R_H = 147456, R_OX = R_H + 46080, R_Q = R_OX + 4096, R_K = R_Q + 5120, R_SX = R_K + 5120, R_P = R_SX + 3200, R_U = R_P + 3200,
              R_BAR = R_H + 73728, R_PROF = R_BAR + 256, R_END = R_PROF + 3072;
constexpr int B_W0 = R_BAR, B_W1 = R_BAR + 8, B_XA = R_BAR + 16, B_XB = R_BAR + 24, B_XF = R_BAR + 32, B_Z0 = R_BAR + 40, B_Z1 = R_BAR + 48, B_R = R_BAR + 56,
              B_SM = R_BAR + 64, B_SX = R_BAR + 72, B_U = R_BAR + 80, B_V = R_BAR + 88, B_W2 = R_BAR + 96, B_W3 = R_BAR + 104, B_O = R_BAR + 112;
static_assert(R_U + 4096 <= R_BAR, "");
enum { N_P1 = 1, N_PM, N_PX, N_SUM, N_O, N_INIT, N_INIT1, N_INIT2, N_WO, N_S };
constexpr int YSLOT = 9 * 16 * 1024;
struct RecParams { CUtensorMap wq, wk, wv, wo, x, ctx; OutMaps o; const bf16 *mem0, *x_raw; bf16* out; };
constexpr int TAIL0 = 14;
constexpr int TST = 6, R_RED = TST * 28672;

DEVI void wg_rs32(float* d, const uint32_t* a, uint64_t db, int acc) {
  asm volatile("{.reg .pred p; setp.ne.b32 p,%21,0;\n wgmma.mma_async.sync.aligned.m64n32k16.f32.bf16.bf16 {%0,%1,%2,%3,%4,%5,%6,%7,%8,%9,%10,%11,%12,%13,%14,%15},{%16,%17,%18,%19},%20,p,1,1,0;}"
               : F8(d, 0), F8(d, 8) : "r"(a[0]), "r"(a[1]), "r"(a[2]), "r"(a[3]), "l"(db), "r"(acc));
}
DEVI void wg_rs40(float* d, const uint32_t* a, uint64_t db, int acc) {
  asm volatile("{.reg .pred p; setp.ne.b32 p,%25,0;\n wgmma.mma_async.sync.aligned.m64n40k16.f32.bf16.bf16 {%0,%1,%2,%3,%4,%5,%6,%7,%8,%9,%10,%11,%12,%13,%14,%15,%16,%17,%18,%19},{%20,%21,%22,%23},%24,p,1,1,0;}"
               : F8(d, 0), F8(d, 8), "+f"(d[16]), "+f"(d[17]), "+f"(d[18]), "+f"(d[19]) : "r"(a[0]), "r"(a[1]), "r"(a[2]), "r"(a[3]), "l"(db), "r"(acc));
}
template <int TB> DEVI void wg_ss40(float* d, uint64_t da, uint64_t db, int acc) {
  asm volatile("{.reg .pred p; setp.ne.b32 p,%22,0;\n wgmma.mma_async.sync.aligned.m64n40k16.f32.bf16.bf16 {%0,%1,%2,%3,%4,%5,%6,%7,%8,%9,%10,%11,%12,%13,%14,%15,%16,%17,%18,%19},%20,%21,p,1,1,1,%23;}"
               : F8(d, 0), F8(d, 8), "+f"(d[16]), "+f"(d[17]), "+f"(d[18]), "+f"(d[19]) : "l"(da), "l"(db), "r"(acc), "n"(TB));
}
DEVI void mma8(float* d, uint32_t a0, uint32_t a1, uint32_t b0) {
  asm volatile("mma.sync.aligned.m16n8k8.row.col.f32.bf16.bf16.f32 {%0,%1,%2,%3},{%4,%5},{%6},{%0,%1,%2,%3};" : "+f"(d[0]), "+f"(d[1]), "+f"(d[2]), "+f"(d[3]) : "r"(a0), "r"(a1), "r"(b0));
}
DEVI void stsm4t(uint32_t a, uint32_t r0, uint32_t r1, uint32_t r2, uint32_t r3) {
  asm volatile("stmatrix.sync.aligned.m8n8.x4.trans.shared.b16 [%0],{%1,%2,%3,%4};" ::"r"(a), "r"(r0), "r"(r1), "r"(r2), "r"(r3) : "memory");
}
DEVI uint32_t movm(uint32_t a) { uint32_t d; asm volatile("movmatrix.sync.aligned.m8n8.trans.b16 %0,%1;" : "=r"(d) : "r"(a)); return d; }
DEVI void sts1(uint32_t a, uint32_t v) { asm volatile("st.shared.b32 [%0],%1;" ::"r"(a), "r"(v) : "memory"); }
DEVI uint32_t lds1(uint32_t a) { uint32_t v; asm volatile("ld.shared.b32 %0,[%1];" : "=r"(v) : "r"(a) : "memory"); return v; }
DEVI void sta1(uint32_t d, uint32_t a, uint32_t bar) { asm volatile("st.async.weak.shared::cluster.mbarrier::complete_tx::bytes.b32 [%0],%1,[%2];" ::"r"(d), "r"(a), "r"(bar) : "memory"); }
DEVI void sta2(uint32_t d, uint32_t a, uint32_t b, uint32_t bar) { asm volatile("st.async.weak.shared::cluster.mbarrier::complete_tx::bytes.v2.b32 [%0],{%1,%2},[%3];" ::"r"(d), "r"(a), "r"(b), "r"(bar) : "memory"); }
DEVI uint32_t clk32() { uint64_t c; asm volatile("mov.u64 %0,%%clock64;" : "=l"(c)::"memory"); return (uint32_t)c; }
DEVI int opq(int x) { asm volatile("" : "+r"(x)); return x; }
DEVI int pin(int x) { return __shfl_sync(~0u, x, threadIdx.x & 31); }
DEVI void x_load(const RecParams& P, uint32_t sb, int c, int seg) {
  asm volatile("cp.async.bulk.tensor.2d.shared::cluster.global.mbarrier::complete_tx::bytes.multicast::cluster [%0],[%1,{%3,%4}],[%2],%5;"
               ::"r"(sb + R_H + c * 5120 + 1024), "l"(&P.x), "r"(sb + (c < XG ? B_XA : B_XB)), "r"(c * 64), "r"(seg * 32), "h"((uint16_t)0xffff) : "memory");
  if (seg + 2 < NSEG) asm volatile("cp.async.bulk.prefetch.tensor.2d.L2.global [%0,{%1,%2}];" ::"l"(&P.x), "r"(c * 64), "r"(seg * 32 + 64) : "memory");
}
DEVI uint32_t hadd2(uint32_t a, uint32_t b) { uint32_t r; asm("add.rn.bf16x2 %0,%1,%2;" : "=r"(r) : "r"(a), "r"(b)); return r; }
DEVI uint32_t hmax2(uint32_t a, uint32_t b) { uint32_t r; asm("max.bf16x2 %0,%1,%2;" : "=r"(r) : "r"(a), "r"(b)); return r; }
DEVI float rcp(float x) { float y; asm("rcp.approx.ftz.f32 %0,%1;" : "=f"(y) : "f"(x)); return y; }
constexpr float SCL = 0.08838834764831845f * 1.4426950408889634f;

DEVI void y_store(const float* a, uint32_t off, int s) {
  const uint32_t x = movm(pack2(a[0], a[1])), y = movm(pack2(a[2], a[3]));
  const uint32_t tag = ((s >> 1) & 1) ^ 1;
  asm volatile("st.relaxed.gpu.global.b64 [%0],%1;" ::"l"((uint8_t*)g_Y + (s & 1) * YSLOT + off), "l"((uint64_t)((x & ~1u) | tag) | ((uint64_t)y << 32)) : "memory");
}
DEVI void y_load(uint32_t* w, const uint8_t* p) {
#pragma unroll
  for (int i = 0; i < 4; i++) asm volatile("{.reg .b64 t; ld.relaxed.gpu.global.b64 t,[%2]; mov.b64 {%0,%1},t;}" : "=r"(w[2 * i]), "=r"(w[2 * i + 1]) : "l"(p + i * 256) : "memory");
}
DEVI bool y_missing(const uint32_t* w, uint32_t tag) {
  uint32_t r;
  asm volatile("{.reg .b32 a,b; .reg .pred p; lop3.b32 a,%1,%2,%5,0x7e; lop3.b32 b,%3,%4,%5,0x7e; lop3.b32 a,a,b,1,0xa8; setp.ne.u32 p,a,0; vote.sync.any.pred p,p,0xffffffff; selp.u32 %0,1,0,p;}"
               : "=r"(r) : "r"(w[0]), "r"(w[2]), "r"(w[4]), "r"(w[6]), "r"(tag));
  return r;
}
DEVI void y_reload(uint32_t* w, const uint8_t* p, uint32_t tag) {
#pragma unroll
  for (int i = 0; i < 4; i++)
    asm volatile("{.reg .b64 t; .reg .b32 a; .reg .pred q; lop3.b32 a,%0,%3,1,0x28; setp.ne.u32 q,a,0; mov.b64 t,{%0,%1}; @q ld.relaxed.gpu.global.b64 t,[%2]; mov.b64 {%0,%1},t;}"
                 : "+r"(w[2 * i]), "+r"(w[2 * i + 1]) : "l"(p + i * 256), "r"(tag) : "memory");
}
DEVI void y_sum(uint32_t* r, const uint32_t* w, uint32_t sel) {
  float d0[4] = {0, 0, 0, 0}, d1[4] = {0, 0, 0, 0};
  mma16(d0, w[0], w[1], w[2], w[3], sel, sel); mma16(d1, w[4], w[5], w[6], w[7], sel, sel);
  r[0] = pack2(d0[0] + d1[0], d0[1] + d1[1]); r[1] = pack2(d0[2] + d1[2], d0[3] + d1[3]);
}
DEVI void y_send(const uint32_t* r, uint32_t sb, uint32_t dst, uint32_t bar, int lane) {
#pragma unroll
  for (int i = 0; i < 4; i++) { const uint32_t rs = mapa(sb, (lane & 3) + i * 4); sta2(rs + dst, r[0], r[1], rs + bar); }
}
DEVI void wo_convert(uint32_t sb, int lane) {
  TL_END(11)
  mbar_wait(sb + B_W3, 0);
  TL_END(9)
#pragma unroll 1
  for (uint32_t a = sb + R_WO + ((threadIdx.x >> 5) & 3) * 4608, i = 0; i < 4; i++, a += 18432) {
    uint32_t r[9][4];
#pragma unroll
    for (int k = 0; k < 9; k++) ldsm4t(r[k], a + k * 32 + ((lane & 7) + (lane >> 4) * 8) * 288 + ((lane >> 3) & 1) * 16);
    __syncwarp();
#pragma unroll
    for (int k = 0; k < 9; k++) stsm4(a + k * 512 + ((lane >> 4) * 2 + ((lane >> 1) & 1)) * 128 + (((lane >> 2) & 3) * 2 + (lane & 1)) * 16, r[k][0], r[k][1], r[k][2], r[k][3]);
  }
  __syncwarp();
}
DEVI uint32_t y_offset(int cta, int tile, int lane) {
  const int T = (cta & 3) * 9 + tile;
  return (((T >> 2) * 8 + (lane >> 2)) * 2 + ((T >> 1) & 1)) * 1024 + (cta >> 4) * 256 + (T & 1) * 128 + ((cta >> 2) & 3) * 32 + (lane & 3) * 8;
}
template <int NR, int NP> DEVI void wo_tile(const uint32_t (*A0)[4], uint32_t sb, int tile, int lane, uint32_t yo, int s) {
  uint32_t u[8][4], A[16][4];
  const uint32_t wa = sb + R_WO + tile * 512 + lane * 16, ua = sb + R_U + lane * 16;
  float a[4] = {0, 0, 0, 0}, b[4] = {0, 0, 0, 0};
  auto fetch = [&](int i) { if (i < 16 - NR) ldsm4(A[i], wa + i * 4608); };
  auto uload = [&](int i) { if (i < 8) ldsm4t(u[i], ua + i * 512); };
#pragma unroll
  for (int i = 0; i < NP; i++) fetch(i);
  mwait(sb + B_V, s & 1);
  PT(6)
  uload(0); uload(1);
#pragma unroll
  for (int i = 0; i < 16; i++) {
    if (i == 4) {
      mwait(sb + B_U, s & 1);
      PT(7)
      uload(2); uload(3);
    }
    const uint32_t* f = i >= 16 - NR ? A0[i >= 16 - NR ? i - 16 + NR : 0] : A[i];
    mma16(i & 1 ? b : a, f[0], f[1], f[2], f[3], u[i >> 1][(i & 1) * 2], u[i >> 1][(i & 1) * 2 + 1]);
    fetch(i + NP);
    if (i >= 4 && (i & 1)) uload((i >> 1) + 2);
  }
#pragma unroll
  for (int i = 0; i < 4; i++) a[i] += b[i];
  y_store(a, yo, s);
}
template <bool X> DEVI void softmax8(const uint32_t* h, uint32_t a4, uint32_t a1) {
  uint32_t y[5];
  lds4(y, a4 + R_SX);
  y[4] = lds1(a1 + R_SX);
#pragma unroll
  for (int j = 0; j < 5; j++) y[j] = hadd2(h[j], y[j]);
  const uint32_t m2 = hmax2(hmax2(hmax2(y[0], y[1]), hmax2(y[2], y[3])), y[4]);
  const float mc = fmaxf(blo(m2), bhi(m2)) * SCL;
  const float m1 = __shfl_xor_sync(~0u, mc, 1), m3 = __shfl_xor_sync(~0u, mc, 2), m4 = __shfl_xor_sync(~0u, mc, 3);
  float e[10];
#pragma unroll
  for (int j = 0; j < 5; j++) { e[2 * j] = ex2(fmaf(blo(y[j]), SCL, -mc)); e[2 * j + 1] = ex2(fmaf(bhi(y[j]), SCL, -mc)); }
  const float c = ex2(mc - fmaxf(fmaxf(mc, m1), fmaxf(m3, m4)));
  const float l = c * ((((e[0] + e[1]) + (e[2] + e[3])) + ((e[4] + e[5]) + (e[6] + e[7]))) + (e[8] + e[9]));
  const float r = c * rcp((l + __shfl_xor_sync(~0u, l, 1)) + (__shfl_xor_sync(~0u, l, 2) + __shfl_xor_sync(~0u, l, 3)));
#pragma unroll
  for (int j = 0; j < 5; j++) y[j] = pack2(e[2 * j] * r, e[2 * j + 1] * r);
  if (!X) sts4(a4 + R_P, y[0], y[1], y[2], y[3]);
  else stsm4(a4 + R_P, y[0], y[1], y[2], y[3]);
  sts1(a1 + R_P, y[4]);
  if (X) fence_async();
}

DEVI void arm_step(uint32_t sb, int s) {
  mbar_expect(sb + B_SM, 640); mbar_expect(sb + B_SX, 2560);
  if (s < NSEG - 1) {
    mbar_expect(sb + B_U, 3072); mbar_expect(sb + B_Z0, 4096); mbar_expect(sb + B_Z1, 5120);
    mbar_expect(sb + B_XA, XG * 4096); mbar_expect(sb + B_XB, (9 - XG) * 4096);
  }
}
DEVI void rec_proj(const RecParams& P, const uint32_t sb, const int cta) {
  uint32_t W[36][4], A0[NRES ? NRES : 1][4];
  const int tid = pin(threadIdx.x);
  const uint32_t yo = pin(y_offset(cta, threadIdx.x >> 5, threadIdx.x & 31));
  const int warp = __shfl_sync(~0u, threadIdx.x >> 5, 0), role = warp >> 2;
  const uint32_t qk = sb + R_Q + warp * 1280;
  {
    const int lane = threadIdx.x & 31, w4 = (threadIdx.x >> 5) & 3;
    const uint32_t a = sb + role * R_H + ((lane & 7) + (lane >> 4) * 8) * 128 + (((w4 * 2 + ((lane >> 3) & 1)) ^ (lane & 7)) << 4);
    mbar_wait(sb + B_W0 + role * 8, 0);
    TL_END(8)
#pragma unroll
    for (int k = 0; k < 36; k++) ldsm4t(W[k], a + k * 2048);
    if (role) bar_arrive(N_INIT1, 256); else bar_sync(N_INIT, 128);
    cluster_sync_relaxed();
#pragma unroll
    for (int i = 0; i < NRES; i++) A0[i][0] = A0[i][1] = A0[i][2] = A0[i][3] = 0;
  }
  for (int s = -1; s < NSEG; s++) {
    if (s >= 0) {
      PT(0)
      {
        const int lane = opq(tid) & 31;
        const uint32_t hb = sb + R_H + (lane & 7) * 128 + (((lane >> 3) ^ (lane & 7)) << 4);
        float a[4] = {0, 0, 0, 0}, b[4] = {0, 0, 0, 0};
        mwait(sb + B_Z0, (s - 1) & 1);
        PT(1)
        uint32_t f[18][4];
#pragma unroll
        for (int c = -PD; c < 18; c++) {
          if (c + PD == 8) mwait(sb + B_Z1, (s - 1) & 1);
          if (c + PD < 18) ldsm4(f[c + PD], (hb ^ (((c + PD) & 1) * 64)) + ((c + PD) >> 1) * 5120);
          if (c >= 0) {
            mma16(a, W[2 * c][0], W[2 * c][1], W[2 * c][2], W[2 * c][3], f[c][0], f[c][1]);
            mma16(b, W[2 * c + 1][0], W[2 * c + 1][1], W[2 * c + 1][2], W[2 * c + 1][3], f[c][2], f[c][3]);
          }
        }
        sts1(qk + 512 + lane * 4, pack2(a[0] + b[0], a[1] + b[1]));
        sts1(qk + 1152 + lane * 4, pack2(a[2] + b[2], a[3] + b[3]));
        fence_async();
      }
      PT(2)
      const int lane = opq(tid) & 31;
      if (role) {
        bar_arrive(N_P1, 256);
        if (tid == 128) arm_step(sb, s);
        const uint32_t o4 = sb + (warp - 4) * 640 + lane * 16, o1 = sb + (warp - 4) * 640 + 512 + lane * 4;
        uint32_t h[5];
        bar_sync(N_PX, 192);
        lds4(h, o4 + R_P); h[4] = lds1(o1 + R_P);
        mwait(sb + B_SX, s & 1);
        PT(4)
        softmax8<true>(h, o4, o1);
        PT(5)
      } else {
        float S[20];
        const uint64_t da = mkdesc(sb + R_Q, 640, 128, 0), db = mkdesc(sb + R_K, 640, 128, 0);
        const uint32_t rs = mapa(sb, (cta & 15) ^ 1);
        const uint32_t o4 = warp * 1280 + lane * 16, o1 = warp * 1280 + 512 + lane * 4;
        bar_sync(N_P1, 256);
        wg_fence();
#pragma unroll
        for (int k = 0; k < 4; k++) wg_ss40<1>(S, da + k * 80, db + k * 80, k);
        wg_commit();
        bar_arrive(N_S, 256);
        wg_wait<0>();
        PT(3)
        uint32_t h[2][5];
        if (warp == 2) {
#pragma unroll
          for (int j = 0; j < 5; j++) h[0][j] = pack2(S[4 * j], S[4 * j + 1]);
          sta4(rs + R_SX + o4, h[0][0], h[0][1], h[0][2], h[0][3], rs + B_SM); sta1(rs + R_SX + o1, h[0][4], rs + B_SM);
          mwait(sb + B_SM, s & 1);
          PT(4)
          softmax8<false>(h[0], sb + o4, sb + o1);
          bar_arrive(N_PM, 160);
        } else if (warp < 2) {
          const int row = warp * 16 + (lane >> 2) - (lane & 3) * 2;
#pragma unroll
          for (int g = 0; g < 2; g++) {
#pragma unroll
            for (int j = 0; j < 5; j++) h[g][j] = pack2(j < 4 && j * 8 > row + g * 8 ? -INFINITY : S[4 * j + 2 * g], j < 4 && j * 8 + 1 > row + g * 8 ? -INFINITY : S[4 * j + 2 * g + 1]);
            sts4(sb + R_P + o4 + g * 640, h[g][0], h[g][1], h[g][2], h[g][3]); sts1(sb + R_P + o1 + g * 640, h[g][4]);
            sta4(rs + R_SX + o4 + g * 640, h[g][0], h[g][1], h[g][2], h[g][3], rs + B_SX);
            sta1(rs + R_SX + o1 + g * 640, h[g][4], rs + B_SX);
          }
          bar_arrive(N_PX, 192);
        } else {
          if (s) bar_sync(N_O, 160);
          if (tid == 96) {
            if (s) {
              bulk_wait<0>();
              tma_store(&P.ctx, sb + R_OX, cta * 64, s * 32 - 32); bulk_commit();
              if (ES && s == TAIL0 * 4) { bulk_wait<0>(); signal_after_bulk(S_CTXB + TAIL0 - 1); }
              else if ((s & 3) == 1 && s > 1 && (!ES || s != TAIL0 * 4 + 1)) signal_after_bulk(S_CTXB + (s >> 2) - 1);
              bulk_wait_read<0>();
            }
          }
        }
        __syncwarp();
        PT(5)
      }
      {
        if (s == 0) {
          bar_sync(N_INIT2, 384);
#pragma unroll
          for (int i = 0; i < NRES; i++) ldsm4(A0[i], sb + R_WO + warp * 512 + lane * 16 + (16 - NRES + i) * 4608);
        }
        if (s == NSEG - 1) break;
        wo_tile<NRES, NPF>(A0, sb, warp, lane, yo, s);

        PT(8)
        bar_sync(N_WO, 384);
      }
    }
    {
      float acc[16];
      const uint64_t db = mkdesc(sb + R_H + 1024, 16, 1024, 1);
      mwait(sb + B_XA, (s + 1) & 1);
      PT(9)
      wg_fence();
#pragma unroll
      for (int k = 0; k < XG * 4; k++) wg_rs32(acc, W[k], db + (k >> 2) * 320 + (k & 3) * 2, k);
      wg_commit();
      mwait(sb + B_XB, (s + 1) & 1);
      wg_fence();
#pragma unroll
      for (int k = XG * 4; k < KA; k++) wg_rs32(acc, W[k], db + (k >> 2) * 320 + (k & 3) * 2, 1);
      wg_commit();
      wg_wait<0>();
      PT(10)
      bar_sync(N_SUM, 384);
      wg_fence();
#pragma unroll
      for (int k = KA; k < 36; k++) wg_rs32(acc, W[k], db + (k >> 2) * 320 + (k & 3) * 2, 1);
      wg_commit();
      const uint32_t o = qk + (opq(tid) & 31) * 16;
      wg_wait<0>();
      PT(11)
      stsm4(o, pack2(acc[0], acc[1]), pack2(acc[4], acc[5]), pack2(acc[8], acc[9]), pack2(acc[12], acc[13]));
      stsm4(o + 640, pack2(acc[2], acc[3]), pack2(acc[6], acc[7]), pack2(acc[10], acc[11]), pack2(acc[14], acc[15]));
    }
  }
  bar_arrive(N_WO, 384);
  for (int i = 0; i < (warp ? 1 : 2); i++)
    asm volatile("st.relaxed.gpu.global.b64 [%0],%1;" ::"l"((uint8_t*)g_Y + YSLOT + yo + i * 2 * 16384), "l"(0ull) : "memory");
  TL_END(6)
  if (tid == 0) CT(1, 0)
  if (warp == 3) {
    if (tid == 96) { bulk_wait<0>(); asm volatile("fence.proxy.async.global;" ::: "memory"); }
    __syncwarp();
    bar_arrive(N_O, 160);
  }
  asm volatile("barrier.cluster.arrive.relaxed.aligned;" ::: "memory");
  float acc[48];
  const int rk = opq(cta) & 15, n = rk / 5, q = rk - n * 5;
  out_consume<TST, false, 32>(acc, sb, sb + B_O, rk == 15 ? 0 : q == 4 ? 12 : 13);
  if (tid == 0) CT(7, 1)
  if (tid == 0) CT(1, 1)
  asm volatile("barrier.cluster.wait.aligned;" ::: "memory");
  bar_sync(N_P1, 256);
  {
#pragma unroll
    for (int u = 0; u < 6; u++) {
      const int d = u % 5;
      const float* a = acc + u * 8;
      const uint32_t x = pack2(a[0], a[1]), y = pack2(a[2], a[3]), z = pack2(a[4], a[5]), w = pack2(a[6], a[7]);
      const uint32_t rs = mapa(sb, rk == 15 ? 15 : n * 5 + d);
      if (d == q) sts4(sb + R_RED - 8192 + (u / 5) * 4096 + tid * 16, x, y, z, w);
      else sta4(rs + R_RED + (q < d ? q : q - 1) * 8192 + (u / 5) * 4096 + tid * 16, x, y, z, w, rs + B_R);
    }
    mbar_wait(sb + B_R, 0);
    if (tid == 0) CT(1, 2)
    const int lane = tid & 31;
    const uint32_t st = sb + warp * 1024 + (lane & 15) * 48 + (lane >> 4) * 16, ld = sb + warp * 1024 + (lane >> 1) * 48 + (lane & 1) * 16;
    bf16* out = P.out + (size_t)((TAIL0 + (cta >> 5)) * 128 + warp * 16 + (lane >> 1)) * (2 * DM) + DM + ((cta >> 4) & 1) * 288 + n * 96 + q * 16 + (lane & 1) * 8;
#pragma unroll 1
    for (int i = 0; i < (q ? 1 : 2); i++) {
      uint32_t v[5][4], r[4];
#pragma unroll
      for (int p = 0; p < 5; p++) lds4(v[p], sb + R_RED + (p - 1) * 8192 + i * 4096 + tid * 16);
#pragma unroll
      for (int j = 0; j < 4; j++)
        r[j] = pack2((blo(v[0][j]) + blo(v[1][j])) + (blo(v[2][j]) + blo(v[3][j])) + blo(v[4][j]), (bhi(v[0][j]) + bhi(v[1][j])) + (bhi(v[2][j]) + bhi(v[3][j])) + bhi(v[4][j]));
      stsm4(st + i * 8192, r[0], r[1], r[2], r[3]);
      __syncwarp();
      lds4(r, ld + i * 8192);
      asm volatile("{.reg .pred p; setp.ne.s32 p,%5,15; @p st.global.v4.b32 [%0],{%1,%2,%3,%4};}" ::"l"(out + i * 80), "r"(r[0]), "r"(r[1]), "r"(r[2]), "r"(r[3]), "r"(rk) : "memory");
    }
  }
}

template <int K> DEVI void v_resident(uint32_t (*F)[4], uint32_t wv) {
  if constexpr (K < 36) { if (VIdx<K>::r == 'r') ldsm4t(F[VIdx<K>::v], wv + K * 2048); v_resident<K + 1>(F, wv); }
}
template <int K> DEVI void v_pass(float* acc, const uint32_t (*F)[4], uint64_t da, uint64_t db, uint32_t xf, uint32_t t, uint32_t nrel) {
  if constexpr (K < 36) {
    wg_fence();
    if (VIdx<K>::r == 'r') wg_rs40(acc, F[VIdx<K>::v], db + (K >> 2) * 320 + (K & 3) * 2, K);
    else wg_ss40<0>(acc, da + K * 128, db + (K >> 2) * 320 + (K & 3) * 2, K);
    wg_commit();
    if constexpr (VIdx<K>::p != '-') wg_wait<VIdx<K>::p - '0'>();
    if (K == XG * 4 - 1 + XW) { wg_wait<XW>(); asm volatile("{.reg .pred p; .reg .b32 a; setp.lt.u32 p,%1,%2; @p mapa.shared::cluster.u32 a,%0,%1; @p mbarrier.arrive.shared::cluster.b64 _,[a];}" ::"r"(xf), "r"(t), "r"(nrel) : "memory"); }
    v_pass<K + 1>(acc, F, da, db, xf, t, nrel);
  }
}
DEVI void rec_aux(const RecParams& P, const uint32_t sb, const int cta) {
  const int tid = pin(threadIdx.x);
  {
    uint4 v[5];
#pragma unroll
    for (int j = 0; j < 5; j++) if (j * 128 + tid - 256 < 576) v[j] = ((const uint4*)P.mem0)[j * 128 + tid - 256];
    if (tid == 288) {
      const uint32_t t0 = clk32();
      while (clk32() - t0 < (uint32_t)WOD) {}
#pragma unroll 1
      for (int i = 0; i < 4; i++) tma_load(sb + R_WO + i * 18432, &P.wo, (cta & 3) * 144, (cta ^ i) * 64, sb + B_W3);
      for (int i = 0; i < 3; i++) asm volatile("cp.async.bulk.prefetch.tensor.2d.L2.global [%0,{%1,%2}];" ::"l"(&P.wv), "r"(cta * 64), "r"(i * 192) : "memory");
    }
    __syncwarp();
    bar_sync(N_INIT1, 256);
#pragma unroll
    for (int j = 0; j < 5; j++) {
      const int i = j * 128 + tid - 256, t = i / 72, c = i - t * 72;
      if (i < 576) sts4(sb + R_H + (c >> 3) * 5120 + t * 128 + (((c & 7) ^ t) << 4), v[j].x, v[j].y, v[j].z, v[j].w);
    }
    fence_async();
    bar_arrive(N_SUM, 384);
    cluster_sync_relaxed();
    if (tid == 288) {
      if ((cta & 15) < 9) x_load(P, sb, cta & 15, 0);
#pragma unroll 1
      for (int i = 0; i < 3; i++) tma_load(sb + R_WV + i * 24576, &P.wv, cta * 64, i * 192, sb + B_W2);
    }
    __syncwarp();
    TL_END(12)
    wo_convert(sb, threadIdx.x & 31);
    bar_sync(N_O, 128);
    bar_arrive(N_INIT2, 384);
    TL_END(10)
  }
  const int rk = cta & 15, w4 = __shfl_sync(~0u, (threadIdx.x >> 5) & 3, 0);
  const uint32_t yg = pin((((threadIdx.x >> 5) & 3) * 16 + rk) * 1024 + ((threadIdx.x >> 4) & 1) * 128 + (threadIdx.x & 3) * 32 + ((threadIdx.x >> 2) & 3) * 8);
  uint32_t F[VB][4];
  mbar_wait(sb + B_W2, 0);
  TL_END(7)
  v_resident<0>(F, sb + R_WV + ((tid & 7) + ((tid >> 4) & 1) * 8) * 128 + (((w4 * 2 + ((tid >> 3) & 1)) ^ (tid & 7)) << 4));
  LT(0)
  for (int s = 0; s < NSEG; s++) {
    const bool last = s == NSEG - 1;
    uint32_t va[12], p[5];
    int lane = opq(tid) & 31;
    {
      float acc[20];
      const uint64_t da = mkdesc(sb + R_WV, 0, 1024, 1), db = mkdesc(sb + R_H, 16, 1024, 1);
      PT(0)
      bar_sync(N_S, 256);
      asm volatile("fence.proxy.async::generic.acquire.sync_restrict::shared::cluster.cluster;" ::: "memory");
      v_pass<0>(acc, F, da, db, sb + B_XF, tid - 256, last ? 0 : XG);
      PT(13)
      bar_sync(N_PM, 160);
      lds4(p, sb + R_P + 2560 + lane * 16); p[4] = lds1(sb + R_P + 3072 + lane * 4);
      wg_wait<0>();
      PT(1)
#pragma unroll
      for (int i = 0; i < 10; i++) va[i < 2 ? i + 8 : i - 2] = pack2(acc[2 * i], acc[2 * i + 1]);
      va[10] = va[11] = 0;
    }
    lane = opq(tid) & 31;
    if (!last) {
      const uint32_t uo = R_U + w4 * 256 + lane * 4;
      float a[4] = {0, 0, 0, 0}, b[4] = {0, 0, 0, 0}, c[4] = {0, 0, 0, 0};
      mma16(a, va[0], va[1], va[2], va[3], p[0], p[1]); mma16(b, va[4], va[5], va[6], va[7], p[2], p[3]); mma8(c, va[8], va[9], p[4]);
      const uint32_t u0 = pack2(a[0] + b[0] + c[0], a[1] + b[1] + c[1]), u1 = pack2(a[2] + b[2] + c[2], a[3] + b[3] + c[3]);
      sts1(sb + uo, u0); sts1(sb + uo + 128, u1);
      __syncwarp();
      if (lane == 0) mbar_arrive(sb + B_V);
#pragma unroll
      for (int q = 1; q < 4; q++) { const uint32_t rs = mapa(sb, rk ^ q); sta1(rs + uo + q * 1024, u0, rs + B_U); sta1(rs + uo + q * 1024 + 128, u1, rs + B_U); }
      asm volatile("{.reg .pred p; .reg .b32 a; setp.lt.u32 p,%1,%3; @p mapa.shared::cluster.u32 a,%0,%2; @p mbarrier.arrive.shared::cluster.b64 _,[a];}" ::"r"(sb + B_XF), "r"(tid - 256 - XG), "r"(tid - 256), "n"(9 - XG) : "memory");
      PT(4)
      if (w4 == 3) {
        wo_tile<0, 4>(nullptr, sb, 8, lane, y_offset(cta, 8, lane), s);
      } else if (tid == 288 && rk < 9) { mbar_wait(sb + B_XF, s & 1); x_load(P, sb, rk, s + 1); }
      PT(2)
    }
    lane = opq(tid) & 31;
    uint32_t ox[8], tu;
    {
      float o[16];
      const uint64_t dp = mkdesc(sb + R_P, 128, 640, 0);
      bar_sync(N_WO, 384);
      wg_fence();
      wg_rs32(o, va, dp, 0); wg_rs32(o, va + 4, dp + 16, 1); wg_rs32(o, va + 8, mkdesc(sb + R_P + 512, 0, 640, 0), 1);
      wg_commit();
      tu = clk32();
      wg_wait<0>();
      PT(3)
#pragma unroll
      for (int i = 0; i < 8; i++) ox[i] = pack2(o[2 * i], o[2 * i + 1]);
    }
    if (!last) {
      const uint8_t* y = (const uint8_t*)g_Y + (s & 1) * YSLOT + yg;
      uint32_t w0[8], w1[8], w2[8];
      while (clk32() - tu < (uint32_t)YD) {}
      y_load(w0, y); y_load(w1, y + 4 * 16384);
      if (w4 == 0) y_load(w2, y + 8 * 16384);
      else {
#pragma unroll
        for (int i = 0; i < 8; i++) w2[i] = ((s >> 1) & 1) ^ 1;
      }
      PT(5)
      const uint32_t dst = R_H + w4 * 5120 + (rk >> 1) * 128 + ((((rk & 1) * 4 + (lane >> 3)) ^ (rk >> 1)) << 4) + (lane & 4) * 2;
      const uint32_t tag = ((s >> 1) & 1) ^ 1, sel = (lane & 4) ? 0x3f800000u : 0x3f80u;
      uint32_t r0[2], r1[2], r2[2];
#pragma unroll 1
      for (int it = 0; (y_missing(w0, tag) | y_missing(w1, tag) | y_missing(w2, tag)) && it < (1 << 20); it++) {
        y_reload(w0, y, tag); y_reload(w1, y + 4 * 16384, tag); y_reload(w2, y + 8 * 16384, tag);
      }
      PT(7)
      y_sum(r0, w0, sel); y_sum(r1, w1, sel); y_sum(r2, w2, sel);
      y_send(r0, sb, dst, B_Z0, lane);
      bar_arrive(N_SUM, 384);
      y_send(r1, sb, dst + 4 * 5120, B_Z1, lane);
      if (w4 == 0) y_send(r2, sb, dst + 8 * 5120, B_Z1, lane);
      PT(9)
    }
#pragma unroll
    for (int h = 0; h < 2; h++) stsm4t(sb + R_OX + lane * 128 + (((w4 * 2 + h) ^ (lane & 7)) << 4), ox[h], ox[2 + h], ox[4 + h], ox[6 + h]);
    if (last) break;
    fence_async();
    bar_arrive(N_O, 160);
    PT(11)
  }
  fence_async();
  bar_sync(N_O, 160);
  if (tid == 256) {
    tma_store(&P.ctx, sb + R_OX, cta * 64, SEQ - 32); bulk_commit(); bulk_wait<0>(); signal_after_bulk(S_CTXB + 15);
  }
  __syncwarp();
  LT(1)
  asm volatile("barrier.cluster.arrive.relaxed.aligned;" ::: "memory");
  if (tid == 256) {
    const int m = TAIL0 + (cta >> 5), n = rk / 5, q = rk - n * 5;
    mbar_expect(sb + B_R, q || rk == 15 ? 4 * 4096 : 8 * 4096);
    if (rk < 15) out_produce<TST, false, 32>(P.o, sb, sb + B_O, m, ((cta >> 4) & 1) * 3 + n, q * 13, q == 4 ? 12 : 13, S_CTXB + m);
  }
  __syncwarp();
  asm volatile("barrier.cluster.wait.aligned;" ::: "memory");
}

__global__ void __launch_bounds__(384, 1) rec_kernel(const __grid_constant__ RecParams P) {
  extern __shared__ __align__(1024) uint8_t smem_raw[];
  const uint32_t sb = s2u(smem_raw);
  const int tid = threadIdx.x, cta = blockIdx.x;
  TL_START(1)
  pdl_trigger();
  if (tid == 0) {
    for (int i = 0; i < 14 + 2 * TST; i++) mbar_init(sb + R_BAR + 8 * i, 8 * i == B_XF - R_BAR ? 16 : 8 * i == B_V - R_BAR ? 4 : i >= 14 + TST ? 2 : 1);
    asm volatile("fence.mbarrier_init.release.cluster;" ::: "memory");
    asm volatile("cp.async.bulk.prefetch.L2.global [%0],%1;" ::"l"(P.x_raw + cta * DM), "r"(DM * 2) : "memory");
    mbar_expect(sb + B_W0, 73728); mbar_expect(sb + B_W1, 73728); mbar_expect(sb + B_W2, 73728); mbar_expect(sb + B_W3, 73728);
#pragma unroll 1
    for (int i = 0; i < 3; i++) { tma_load(sb + R_WV + i * 24576, &P.wq, cta * 64, i * 192, sb + B_W0); tma_load(sb + R_H + i * 24576, &P.wk, cta * 64, i * 192, sb + B_W1); }
    mbar_expect(sb + B_XA, XG * 4096); mbar_expect(sb + B_XB, (9 - XG) * 4096);
  }
  __syncthreads();
  if (tid >= 256) { reg_dec<504 - 2 * RP>(); rec_aux(P, sb, cta); }
  else { reg_inc<RP>(); rec_proj(P, sb, cta); }
  TL_END(1)
  if (tid == 0) CT(7, 2)
  cluster_sync_relaxed();
}
typedef CUresult (*EncFn)(CUtensorMap*, CUtensorMapDataType, cuuint32_t, void*, const cuuint64_t*, const cuuint64_t*, const cuuint32_t*, const cuuint32_t*,
                          CUtensorMapInterleave, CUtensorMapSwizzle, CUtensorMapL2promotion, CUtensorMapFloatOOBfill);
static EncFn g_enc;
static CUtensorMap mk(const void* p, uint64_t cols, uint64_t rows, uint64_t pitch_elems, uint32_t box_rows, uint32_t box_cols = 64) {
  CUtensorMap m;
  cuuint64_t dim[2] = {cols, rows}, str[1] = {pitch_elems * 2};
  cuuint32_t box[2] = {box_cols, box_rows}, es[2] = {1, 1};
  g_enc(&m, CU_TENSOR_MAP_DATA_TYPE_BFLOAT16, 2, (void*)p, dim, str, box, es, CU_TENSOR_MAP_INTERLEAVE_NONE, box_cols == 64 ? CU_TENSOR_MAP_SWIZZLE_128B : box_cols == 32 ? CU_TENSOR_MAP_SWIZZLE_64B : CU_TENSOR_MAP_SWIZZLE_NONE,
        CU_TENSOR_MAP_L2_PROMOTION_L2_256B, CU_TENSOR_MAP_FLOAT_OOB_FILL_NONE);
  return m;
}
template <class T> static void* sym(T& s) { void* p; cudaGetSymbolAddress(&p, s); return p; }

#define FE 6
#define STG 10
#define FHC 24
#define FSL 5
#define NOE 9
#define NX 1
#define NF2 18
template <class K, class A> static void launch(K k, int grid, int smem, int cluster, bool pdl, const A& arg) {
  cudaLaunchConfig_t c = {};
  cudaLaunchAttribute at[2];
  int n = 0;
  if (cluster > 1) { at[n].id = cudaLaunchAttributeClusterDimension; at[n].val.clusterDim.x = cluster; at[n].val.clusterDim.y = at[n].val.clusterDim.z = 1; n++; }
  if (pdl) { at[n].id = cudaLaunchAttributeProgrammaticStreamSerialization; at[n].val.programmaticStreamSerializationAllowed = 1; n++; }
  c.gridDim = grid; c.blockDim = 384; c.dynamicSmemBytes = smem; c.stream = cudaStreamPerThread; c.attrs = at; c.numAttrs = n;
  cudaLaunchKernelEx(&c, k, arg);
}

extern "C" void kernel_launch(void* const* d_in, const int* in_sizes, int n_in, void* d_out, int out_size) {
  static int nb;
  if (!g_enc) {
    cudaDriverEntryPointQueryResult qr;
    cudaGetDriverEntryPoint("cuTensorMapEncodeTiled", (void**)&g_enc, cudaEnableDefault, &qr);
    cudaDeviceGetAttribute(&nb, cudaDevAttrMultiProcessorCount, 0);
    nb = nb - 64 < 32 ? 32 : nb - 64 > 128 ? 128 : (nb - 64) & ~1;
    cudaFuncSetAttribute(out_kernel<false, 64>, cudaFuncAttributeMaxDynamicSharedMemorySize, SM_O);
    cudaFuncSetAttribute(out_kernel<true, 64>, cudaFuncAttributeMaxDynamicSharedMemorySize, SM_O);
    cudaFuncSetAttribute(out_kernel<false, 32>, cudaFuncAttributeMaxDynamicSharedMemorySize, SM_O);
    cudaFuncSetAttribute(fa_kernel, cudaFuncAttributeMaxDynamicSharedMemorySize, SM_F);
    cudaFuncSetAttribute(rec_kernel, cudaFuncAttributeMaxDynamicSharedMemorySize, R_END);
    cudaFuncSetAttribute(rec_kernel, cudaFuncAttributeNonPortableClusterSizeAllowed, 1);
  }
  const bf16 *Ax = (const bf16*)d_in[0], *Ac = (const bf16*)d_in[1], *Awq = (const bf16*)d_in[2], *Awk = (const bf16*)d_in[3], *Awv = (const bf16*)d_in[4],
             *Awo = (const bf16*)d_in[5], *Bx = (const bf16*)d_in[6], *Bm = (const bf16*)d_in[7], *Bwq = (const bf16*)d_in[8], *Bwk = (const bf16*)d_in[9],
             *Bwv = (const bf16*)d_in[10], *Bwo = (const bf16*)d_in[11];
  bf16* out = (bf16*)d_out;
  FaParams f;
  ProjParams& p = f.p;
  int nitems = 0;
  p.a[0] = mk(Ac, 512, SEQ, 512, 128); p.a[1] = mk(Ax, DM, SEQ, DM, 128);
  p.w[0] = mk(Awk, HD, 512, HD, 64); p.w[1] = mk(Awv, HD, 512, HD, 64); p.w[2] = mk(Awq, HD, DM, HD, 64);
  p.c[0] = mk(sym(g_kA), HD, SEQ, HD, 64); p.c[1] = mk(sym(g_vA), HD, SEQ, HD, 64); p.c[2] = mk(sym(g_qA), HD, SEQ, HD, 64);
  {
    int parts[16];
    for (int i = 0; i < 16; i++) parts[i] = 1;
    for (int e = 0; e < nb / 2 - 16; e++) parts[e % 24 < 16 ? e % 8 : 15 - (e % 24 - 16)]++;
    for (int i = 15; i >= 0; i--)
      for (int j = 0, nc = i < 8 ? 32 : 16, a = parts[i]; j < a; j++) {
        ProjItem& I = p.item[nitems++];
        I.pa = i >> 3; I.m = i & 7;
        I.c0[0] = j * nc / a; I.n[0] = (j + 1) * nc / a - I.c0[0];
        I.c0[1] = (j * nc + a - 1) / a; I.n[1] = ((j + 1) * nc + a - 1) / a - I.c0[1];
        if (i < 8 && a == 3) { const int d = STG * (i + 4) / 11, b1 = 11 - d, b2 = 22 - d + (i - 4) * STG / 16; I.c0[1] = j == 0 ? 0 : j == 1 ? b1 : b2; I.n[1] = (j == 0 ? b1 : j == 1 ? b2 : 32) - I.c0[1]; }
      }
  }
  for (int i = 0; i < nitems; i++) {
    auto len = [&](int j) { return (8 + p.item[j].pa) * (1 + p.item[j].n[0] + p.item[j].n[1]); };
    int longer = 0;
    for (int j = 0; j < nitems; j++) longer += len(j) > len(i) || (len(j) == len(i) && j < i);
    p.item[i].leave = longer < NF2 / 2;
    p.item[i].s0 = (PST - len(i) % PST) % PST;
  }
  OutParams o, om, oh;
  for (int i = 0; i < 2; i++) {
    o.p[i].a = mk(i ? sym(g_ctxB) : sym(g_qA), HD, SEQ, HD, 128); o.p[i].b = mk(i ? Bwo : Awo, DM, HD, DM, 64); o.p[i].c = mk(out + i * DM, DM, SEQ, 2 * DM, 64);
    om.p[i] = o.p[i]; om.p[i].b = mk(i ? Bwo : Awo, DM, HD, DM, 32);
    oh.p[i] = o.p[i]; oh.p[i].b = mk(i ? Bwo : Awo, DM, HD, DM, 64, 32); oh.p[i].c = mk(out + i * DM, DM, SEQ, 2 * DM, 64, 32);
  }
  f.q = mk(sym(g_qA), HD, SEQ, HD, 128); f.k = mk(sym(g_kA), HD, SEQ, HD, 128); f.v = mk(sym(g_vA), HD, SEQ, HD, 128); f.o = mk(sym(g_qA), HD, SEQ, HD, 64);
  f.nctas = nb;
  for (int i = 0; i < 9; i++) f.nproj[i] = 0;
  for (int i = 0; i < nitems; i++) f.nproj[p.item[i].pa * (p.item[i].m + 1)] += 4;
  for (int key = -90, n = 0; n < 512; key++)
    for (int h = 0; h < 32; h++)
      for (int qt = 0; qt < 16; qt++)
        if ((h < FHC ? h : FHC) * FSL - qt * 2 - (qt >= 12 && h < FE ? 60 : 0) == key) f.order[n++] = qt * 32 + h;
  RecParams r;
  r.wq = mk(Bwq, HD, DM, HD, 192); r.wk = mk(Bwk, HD, DM, HD, 192); r.wv = mk(Bwv, HD, DM, HD, 192); r.wo = mk(Bwo, DM, HD, DM, 64, 144);
  r.x_raw = Bx;
  r.x = mk(Bx, DM, SEQ, DM, 32); r.ctx = mk(sym(g_ctxB), HD, SEQ, HD, 32); r.mem0 = Bm; r.o = oh.p[1]; r.out = out;

  o.n = om.n = oh.n = 0; o.id = 4; om.id = 5; oh.id = 2;
  for (int m = 0; m < NOE; m++)
    for (int n = 0; n < 3; n++) {
      if (m >= NOE - 2 && n >= 3 - NX) continue;
      o.tile[o.n++] = 128 + m * 8 + n;
    }
  for (int m = NOE - 2; m < TAIL0 - 1; m += 2)
    for (int n = m < NOE ? 3 - NX : 0; n < 3; n++) { om.tile[om.n++] = 128 + m * 8 + n; om.tile[om.n++] = 128 + m * 8 + 8 + n; }
  for (int m = 14; m >= 0; m -= 2)
    for (int n = 0; n < 3; n++) { om.tile[om.n++] = m * 8 + n; om.tile[om.n++] = m * 8 + 8 + n; }
  for (int n = 0; n < 6; n++) oh.tile[oh.n++] = 128 + (TAIL0 - 1) * 8 + n;
  launch(rec_kernel, 64, R_END, 16, false, r);
  f.proj = 1;
  launch(fa_kernel, nb, SM_F, 2, true, f);
  launch(out_kernel<false, 64>, o.n, SM_O, 1, true, o);
  f.proj = 0;
  launch(fa_kernel, NF2, SM_F, 1, true, f);
  launch(out_kernel<true, 64>, om.n, SM_O, 2, true, om);
  launch(out_kernel<false, 32>, oh.n, SM_O, 1, true, oh);
}
```

```cpp
#include <cuda_runtime.h>
#include <cuda_bf16.h>
#include <cuda.h>
#include <stdint.h>

typedef __nv_bfloat16 bf16;
#define DEVI __device__ __forceinline__
#define WAIT_FAIL(code) break
#define WAIT_MAX (1 << 22)

constexpr int SEQ = 2048, HD = 4096, DM = 576, NSEG = 64;

__device__ __align__(1024) bf16 g_qA[SEQ * HD], g_kA[SEQ * HD], g_vA[SEQ * HD];
__device__ __align__(1024) bf16 g_ctxB[SEQ * HD];
__device__ __align__(1024) uint4 g_Y[2 * 9 * 16 * 64];
enum { S_QUEUE = 0, S_EXIT = 1, S_LIST = 8, S_PROJ = 32, S_CTXA = 64, S_CTXB = 96 };
__device__ unsigned g_sync[128];
__device__ __align__(16) uint8_t g_group[256];
#define LT(i)
#define CT(k, i) {}
#define TL_START(i)
#define TL_END(i)

DEVI uint32_t s2u(const void* p) { return (uint32_t)__cvta_generic_to_shared(p); }
DEVI void mbar_init(uint32_t b, uint32_t c) { asm volatile("mbarrier.init.shared::cta.b64 [%0],%1;" ::"r"(b), "r"(c)); }
DEVI void mbar_expect(uint32_t b, uint32_t n) { asm volatile("mbarrier.arrive.expect_tx.shared::cta.b64 _,[%0],%1;" ::"r"(b), "r"(n) : "memory"); }
DEVI void mbar_arrive(uint32_t b) { asm volatile("mbarrier.arrive.shared::cta.b64 _,[%0];" ::"r"(b) : "memory"); }
DEVI void mbar_wait(uint32_t b, uint32_t ph) {
  uint32_t ok; int it = 0;
  do {
    asm volatile("{.reg .pred p; mbarrier.try_wait.parity.shared::cta.b64 p,[%1],%2; selp.u32 %0,1,0,p;}" : "=r"(ok) : "r"(b), "r"(ph) : "memory");
    if (!ok && ++it > WAIT_MAX) WAIT_FAIL(b & 0xffffff);
  } while (!ok);
}
DEVI bool mbar_try(uint32_t b, uint32_t ph) {
  uint32_t ok;
  asm volatile("{.reg .pred p; mbarrier.try_wait.parity.shared::cta.b64 p,[%1],%2; selp.u32 %0,1,0,p;}" : "=r"(ok) : "r"(b), "r"(ph) : "memory");
  return ok;
}
DEVI bool mbar_test(uint32_t b, uint32_t ph) {
  uint32_t ok;
  asm volatile("{.reg .pred p; mbarrier.test_wait.parity.shared::cta.b64 p,[%1],%2; selp.u32 %0,1,0,p;}" : "=r"(ok) : "r"(b), "r"(ph) : "memory");
  return ok;
}
DEVI void mwait(uint32_t b, uint32_t ph) { if (__builtin_expect(!mbar_try(b, ph), 0)) mbar_wait(b, ph); }
DEVI void tma_load(uint32_t dst, const CUtensorMap* tm, int c0, int c1, uint32_t bar) {
  asm volatile("cp.async.bulk.tensor.2d.shared::cluster.global.mbarrier::complete_tx::bytes [%0],[%1,{%3,%4}],[%2];" ::"r"(dst), "l"(tm), "r"(bar), "r"(c0), "r"(c1) : "memory");
}
DEVI void tma_store(const CUtensorMap* tm, uint32_t src, int c0, int c1) {
  asm volatile("cp.async.bulk.tensor.2d.global.shared::cta.bulk_group [%0,{%2,%3}],[%1];" ::"l"(tm), "r"(src), "r"(c0), "r"(c1) : "memory");
}
DEVI void bulk_commit() { asm volatile("cp.async.bulk.commit_group;" ::: "memory"); }
template <int N> DEVI void bulk_wait_read() { asm volatile("cp.async.bulk.wait_group.read %0;" ::"n"(N) : "memory"); }
template <int N> DEVI void bulk_wait() { asm volatile("cp.async.bulk.wait_group %0;" ::"n"(N) : "memory"); }
DEVI void fence_async() { asm volatile("fence.proxy.async.shared::cta;" ::: "memory"); }
DEVI void bar_sync(int id, int n) { asm volatile("bar.sync %0,%1;" ::"r"(id), "r"(n) : "memory"); }
DEVI void bar_arrive(int id, int n) { asm volatile("bar.arrive %0,%1;" ::"r"(id), "r"(n) : "memory"); }
template <int R> DEVI void reg_inc() { asm volatile("setmaxnreg.inc.sync.aligned.u32 %0;" ::"n"(R)); }
template <int R> DEVI void reg_dec() { asm volatile("setmaxnreg.dec.sync.aligned.u32 %0;" ::"n"(R)); }
DEVI void wg_fence() { asm volatile("wgmma.fence.sync.aligned;" ::: "memory"); }
DEVI void wg_commit() { asm volatile("wgmma.commit_group.sync.aligned;" ::: "memory"); }
template <int N> DEVI void wg_wait() { asm volatile("wgmma.wait_group.sync.aligned %0;" ::"n"(N) : "memory"); }
DEVI uint64_t desc_k(uint32_t a) { return (uint64_t)((a >> 4) & 0x3fff) | (1ull << 16) | (64ull << 32) | (1ull << 62); }
DEVI uint64_t desc_mn(uint32_t a, uint32_t lbo) { return (uint64_t)((a >> 4) & 0x3fff) | ((uint64_t)(lbo >> 4) << 16) | (64ull << 32) | (1ull << 62); }
DEVI uint64_t mkdesc(uint32_t a, uint32_t lbo, uint32_t sbo, int sw) { return (uint64_t)((a >> 4) & 0x3fff) | ((uint64_t)(lbo >> 4) << 16) | ((uint64_t)(sbo >> 4) << 32) | ((uint64_t)sw << 62); }
DEVI uint32_t pack2(float lo, float hi) { uint32_t r; asm("cvt.rn.bf16x2.f32 %0,%1,%2;" : "=r"(r) : "f"(hi), "f"(lo)); return r; }
DEVI float ex2(float x) { float y; asm("ex2.approx.ftz.f32 %0,%1;" : "=f"(y) : "f"(x)); return y; }
DEVI void stsm4(uint32_t a, uint32_t r0, uint32_t r1, uint32_t r2, uint32_t r3) {
  asm volatile("stmatrix.sync.aligned.m8n8.x4.shared.b16 [%0],{%1,%2,%3,%4};" ::"r"(a), "r"(r0), "r"(r1), "r"(r2), "r"(r3) : "memory");
}
DEVI void ldsm4(uint32_t* r, uint32_t a) {
  asm volatile("ldmatrix.sync.aligned.m8n8.x4.shared.b16 {%0,%1,%2,%3},[%4];" : "=r"(r[0]), "=r"(r[1]), "=r"(r[2]), "=r"(r[3]) : "r"(a) : "memory");
}
DEVI void ldsm4t(uint32_t* r, uint32_t a) {
  asm volatile("ldmatrix.sync.aligned.m8n8.x4.trans.shared.b16 {%0,%1,%2,%3},[%4];" : "=r"(r[0]), "=r"(r[1]), "=r"(r[2]), "=r"(r[3]) : "r"(a) : "memory");
}
DEVI void mma16(float* d, uint32_t a0, uint32_t a1, uint32_t a2, uint32_t a3, uint32_t b0, uint32_t b1) {
  asm volatile("mma.sync.aligned.m16n8k16.row.col.f32.bf16.bf16.f32 {%0,%1,%2,%3},{%4,%5,%6,%7},{%8,%9},{%0,%1,%2,%3};"
               : "+f"(d[0]), "+f"(d[1]), "+f"(d[2]), "+f"(d[3]) : "r"(a0), "r"(a1), "r"(a2), "r"(a3), "r"(b0), "r"(b1));
}

DEVI void pdl_trigger() { asm volatile("griddepcontrol.launch_dependents;" ::: "memory"); }
DEVI void signal_after_bulk(int f) {
  asm volatile("fence.proxy.async.global;" ::: "memory");
  asm volatile("red.release.gpu.global.add.u32 [%0], 1;" ::"l"(g_sync + f) : "memory");
}
DEVI void flag_wait(int f, unsigned n, unsigned waiters) {
  for (int it = 0;; it++) {
    if (it > WAIT_MAX) WAIT_FAIL(f);
    unsigned v; asm volatile("ld.acquire.gpu.global.u32 %0, [%1];" : "=r"(v) : "l"(g_sync + f) : "memory");
    if (v >= n) break;
    __nanosleep(64);
  }
  if (waiters) asm volatile("red.relaxed.gpu.global.inc.u32 [%0], %1;" ::"l"(g_sync + f), "r"(n + waiters - 1) : "memory");
  asm volatile("fence.proxy.async.global;" ::: "memory");
}
DEVI uint32_t mapa(uint32_t a, uint32_t r) { uint32_t o; asm("mapa.shared::cluster.u32 %0,%1,%2;" : "=r"(o) : "r"(a), "r"(r)); return o; }
DEVI void tma_load_mc(uint32_t dst, const CUtensorMap* tm, int c0, int c1, uint32_t bar, uint16_t mask) {
  asm volatile("cp.async.bulk.tensor.2d.shared::cluster.global.mbarrier::complete_tx::bytes.multicast::cluster [%0],[%1,{%3,%4}],[%2],%5;" ::"r"(dst), "l"(tm), "r"(bar), "r"(c0), "r"(c1), "h"(mask) : "memory");
}
DEVI void arrive_pair(uint32_t b) { if ((threadIdx.x & 127) < 2) asm volatile("mbarrier.arrive.shared::cluster.b64 _,[%0];" ::"r"(mapa(b, threadIdx.x & 1)) : "memory"); }
DEVI void cluster_sync_relaxed() { asm volatile("barrier.cluster.arrive.relaxed.aligned; barrier.cluster.wait.aligned;" ::: "memory"); }
DEVI void cluster_sync() { asm volatile("barrier.cluster.arrive.aligned; barrier.cluster.wait.aligned;" ::: "memory"); }
DEVI void sts4(uint32_t a, uint32_t x, uint32_t y, uint32_t z, uint32_t w) { asm volatile("st.shared.v4.b32 [%0],{%1,%2,%3,%4};" ::"r"(a), "r"(x), "r"(y), "r"(z), "r"(w) : "memory"); }
DEVI void lds4(uint32_t* r, uint32_t a) { asm volatile("ld.shared.v4.b32 {%0,%1,%2,%3},[%4];" : "=r"(r[0]), "=r"(r[1]), "=r"(r[2]), "=r"(r[3]) : "r"(a) : "memory"); }
DEVI void sta4(uint32_t d, uint32_t a, uint32_t b, uint32_t c, uint32_t e, uint32_t bar) {
  asm volatile("st.async.weak.shared::cluster.mbarrier::complete_tx::bytes.v4.b32 [%0],{%1,%2,%3,%4},[%5];" ::"r"(d), "r"(a), "r"(b), "r"(c), "r"(e), "r"(bar) : "memory");
}
DEVI float blo(uint32_t u) { return __uint_as_float(u << 16); }
DEVI float bhi(uint32_t u) { return __uint_as_float(u & 0xffff0000u); }

#define F8(a, o) "+f"(a[o]), "+f"(a[o + 1]), "+f"(a[o + 2]), "+f"(a[o + 3]), "+f"(a[o + 4]), "+f"(a[o + 5]), "+f"(a[o + 6]), "+f"(a[o + 7])
#define F32(a, o) F8(a, o), F8(a, o + 8), F8(a, o + 16), F8(a, o + 24)
template<int TB> DEVI void wg_ss128(float* d, uint64_t da, uint64_t db, int acc){
 asm volatile("{.reg .pred p; setp.ne.b32 p,%66,0;\n wgmma.mma_async.sync.aligned.m64n128k16.f32.bf16.bf16 {%0,%1,%2,%3,%4,%5,%6,%7,%8,%9,%10,%11,%12,%13,%14,%15,%16,%17,%18,%19,%20,%21,%22,%23,%24,%25,%26,%27,%28,%29,%30,%31,%32,%33,%34,%35,%36,%37,%38,%39,%40,%41,%42,%43,%44,%45,%46,%47,%48,%49,%50,%51,%52,%53,%54,%55,%56,%57,%58,%59,%60,%61,%62,%63},%64,%65,p,1,1,0,%67;}"
 : F32(d,0),F32(d,32) : "l"(da),"l"(db),"r"(acc),"n"(TB));}
template<int TB> DEVI void wg_ss192(float* d, uint64_t da, uint64_t db, int acc){
 asm volatile("{.reg .pred p; setp.ne.b32 p,%98,0;\n wgmma.mma_async.sync.aligned.m64n192k16.f32.bf16.bf16 {%0,%1,%2,%3,%4,%5,%6,%7,%8,%9,%10,%11,%12,%13,%14,%15,%16,%17,%18,%19,%20,%21,%22,%23,%24,%25,%26,%27,%28,%29,%30,%31,%32,%33,%34,%35,%36,%37,%38,%39,%40,%41,%42,%43,%44,%45,%46,%47,%48,%49,%50,%51,%52,%53,%54,%55,%56,%57,%58,%59,%60,%61,%62,%63,%64,%65,%66,%67,%68,%69,%70,%71,%72,%73,%74,%75,%76,%77,%78,%79,%80,%81,%82,%83,%84,%85,%86,%87,%88,%89,%90,%91,%92,%93,%94,%95},%96,%97,p,1,1,0,%99;}"
 : F32(d,0),F32(d,32),F32(d,64) : "l"(da),"l"(db),"r"(acc),"n"(TB));}
template<int TB> DEVI void wg_rs128(float* d, const uint32_t* a, uint64_t db, int acc){
 asm volatile("{.reg .pred p; setp.ne.b32 p,%69,0;\n wgmma.mma_async.sync.aligned.m64n128k16.f32.bf16.bf16 {%0,%1,%2,%3,%4,%5,%6,%7,%8,%9,%10,%11,%12,%13,%14,%15,%16,%17,%18,%19,%20,%21,%22,%23,%24,%25,%26,%27,%28,%29,%30,%31,%32,%33,%34,%35,%36,%37,%38,%39,%40,%41,%42,%43,%44,%45,%46,%47,%48,%49,%50,%51,%52,%53,%54,%55,%56,%57,%58,%59,%60,%61,%62,%63},{%64,%65,%66,%67},%68,p,1,1,%70;}"
 : F32(d,0),F32(d,32) : "r"(a[0]),"r"(a[1]),"r"(a[2]),"r"(a[3]),"l"(db),"r"(acc),"n"(TB));}
DEVI void wg_ss96t(float* d, uint64_t da, uint64_t db, int acc){
 asm volatile("{.reg .pred p; setp.ne.b32 p,%50,0;\n wgmma.mma_async.sync.aligned.m64n96k16.f32.bf16.bf16 {%0,%1,%2,%3,%4,%5,%6,%7,%8,%9,%10,%11,%12,%13,%14,%15,%16,%17,%18,%19,%20,%21,%22,%23,%24,%25,%26,%27,%28,%29,%30,%31,%32,%33,%34,%35,%36,%37,%38,%39,%40,%41,%42,%43,%44,%45,%46,%47},%48,%49,p,1,1,0,1;}"
 : F32(d,0),F8(d,32),F8(d,40) : "l"(da),"l"(db),"r"(acc));}
struct ProjItem { uint8_t pa, m, c0[2], n[2], s0, leave; };
struct ProjParams { CUtensorMap a[2], w[3], c[3]; ProjItem item[48]; };
constexpr int PST = 12, P_STG = PST * 16384, P_FULL = P_STG + 32768 + 256, P_EMPTY = P_FULL + 8 * PST, P_OF = P_EMPTY + 8 * PST, P_OE = P_OF + 16, P_END = P_OE + 16;
DEVI void proj_decode(const ProjItem& I, int t, int& pw, int& n) {
  const int g = t >= I.n[0], c = g ? I.c0[1] + t - I.n[0] : I.c0[0] + t;
  pw = I.pa ? 2 : c >> 4; n = (c & 15) + g * 16;
}
DEVI void proj_init(const ProjItem& I, uint32_t base) {
  for (int i = 0; i < PST; i++) { mbar_init(base + P_FULL + 8 * i, 1); mbar_init(base + P_EMPTY + 8 * i, 4); }
  for (int i = 0; i < 2; i++) { mbar_init(base + P_OF + 8 * i, 4); mbar_init(base + P_OE + 8 * i, 1); }
  mbar_init(base + P_END, 1);
  for (int i = 0; i < I.s0; i++) {
    mbar_arrive(base + P_FULL + 8 * i);
    asm volatile("mbarrier.arrive.shared::cta.b64 _,[%0],4;" ::"r"(base + P_EMPTY + 8 * i) : "memory");
  }
}
DEVI int proj_produce(const ProjParams& P, const ProjItem& I, uint32_t base) {
  const int nk = 8 + I.pa, r = blockIdx.x & 1;
  int s = I.s0, ph = 1;
  for (int t = -1; t < I.n[0] + I.n[1]; t++) {
    int pw, n; proj_decode(I, t, pw, n);
    if (t == I.n[0] + I.n[1] - 1) mbar_arrive(base + P_END);
    for (int k = 0; k < nk; k++) {
      if (t >= 0) mbar_wait(base + P_EMPTY + 8 * s, ph);
      mbar_expect(base + P_FULL + 8 * s, 16384);
      if (t < 0) tma_load(base + s * 16384, &P.a[I.pa], k * 64, (I.m * 2 + r) * 128, base + P_FULL + 8 * s);
      else tma_load_mc(base + s * 16384 + r * 8192, &P.w[pw], n * 128 + r * 64, k * 64, base + P_FULL + 8 * s, 3);
      if (++s == PST) { s = 0; ph ^= 1; }
    }
  }
  return ph;
}
DEVI void proj_store(const ProjParams& P, const ProjItem& I, uint32_t base, int g) {
  const int r0 = (I.m * 2 + (blockIdx.x & 1)) * 128 + g * 64;
  for (int t = 0; t < I.n[0] + I.n[1]; t++) {
    int pw, n; proj_decode(I, t, pw, n);
    mbar_wait(base + P_OF + 8 * g, t & 1);
    tma_store(&P.c[pw], base + P_STG + g * 16384, n * 128, r0);
    tma_store(&P.c[pw], base + P_STG + g * 16384 + 8192, n * 128 + 64, r0);
    bulk_commit();
    bulk_wait_read<0>();
    mbar_arrive(base + P_OE + 8 * g);
    if (t == 3 && !g) CT(0, 1)
    if (t == I.n[0] - 1) { bulk_wait<0>(); signal_after_bulk(S_PROJ + I.pa * (I.m + 1) * 2); }
  }
  bulk_wait<0>(); signal_after_bulk(S_PROJ + I.pa * (I.m + 1) * 2 + 1);
  if (!g) CT(0, 2)
}
DEVI void proj_consume(const ProjItem& I, uint32_t base, int tid, int wg) {
  const uint32_t full = base + P_FULL;
  uint32_t A[36][4];
  float acc[64];
  uint32_t s = I.s0, ph = 0, c = 1;
  const uint32_t row = ((tid >> 5) & 3) * 16 + (tid & 15);
  const uint32_t roff = row * 128 + ((((tid >> 4) & 1) ^ (row & 7)) << 4);
  const uint32_t rel = mapa(base + P_EMPTY, tid & 1);
  auto release = [&](uint32_t st) { asm volatile("{.reg .pred p; setp.lt.u32 p,%1,2; @p mbarrier.arrive.shared::cluster.b64 _,[%0];}" ::"r"(rel + 8 * st), "r"(tid & 127) : "memory"); };
  const int pa = I.pa, nt = I.n[0] + I.n[1];
#pragma unroll
  for (int k = 0; k < 9; k++) {
    if (k < 8 || pa) {
      mbar_wait(full + 8 * s, ph);
#pragma unroll
      for (int kk = 0; kk < 4; kk++) ldsm4(A[4 * k + kk], base + s * 16384 + wg * 8192 + (roff ^ (kk * 32)));
      bar_sync(1 + wg, 128);
      release(s);
      if (++s == PST) { s = 0; ph ^= 1; }
    }
  }
  if (tid == 0) CT(0, 0)
  if (wg) bar_sync(5, 256);
  bool ok = false;
  for (int t = 0; t < nt; t++, c ^= 1) {
    uint32_t p1 = 0;
#pragma unroll
    for (int k = 0; k < 9; k++) {
      if (k < 8 || pa) {
        if (!ok) mbar_wait(full + 8 * s, ph);
        const uint64_t db = desc_mn(base + s * 16384, 8192);
        wg_fence();
#pragma unroll
        for (int kk = 0; kk < 4; kk++) wg_rs128<1>(acc, A[4 * k + kk], db + kk * 128, k | kk);
        wg_commit();
        const uint32_t cur = s;
        if (++s == PST) { s = 0; ph ^= 1; }
        ok = mbar_test(full + 8 * s, ph);
        if (k) { wg_wait<1>(); release(p1); }
        if (k == 4 && t == 0 && !wg) bar_arrive(5, 256);
        p1 = cur;
      }
    }
    mwait(base + P_OE + 8 * wg, c);
    wg_wait<0>();
    release(p1);
#pragma unroll
    for (int i = 0; i < 8; i++) {
      const float* a = acc + i * 8;
      stsm4(base + P_STG + wg * 16384 + (i >> 2) * 8192 + (roff ^ ((i & 3) * 32)), pack2(a[0], a[1]), pack2(a[2], a[3]), pack2(a[4], a[5]), pack2(a[6], a[7]));
    }
    fence_async();
    __syncwarp();
    if ((tid & 31) == 0) mbar_arrive(base + P_OF + 8 * wg);
  }
}

struct OutMaps { CUtensorMap a, b, c; };
template <int NST, bool PAIR, int G> DEVI void out_produce(const OutMaps& M, uint32_t base, uint32_t full, int m, int n, int k0, int nk, int flag) {
  constexpr int SB = 16384 + 384 * G;
  constexpr bool MC = PAIR && G == 64;
  const int r = MC ? blockIdx.x & 1 : 0;
  int s = 0, ph = !PAIR;
#pragma unroll 1
  for (int k = 0; k < nk + (PAIR ? NST - 1 : 0); k++) {
    mbar_wait(full + 8 * (NST + s), ph);
    if (k < nk) {
      mbar_expect(full + 8 * s, SB);
#pragma unroll 1
      for (int j = 0; j < 3; j++) {
        if (MC) tma_load_mc(base + s * SB + 16384 + j * 128 * G + r * 64 * G, &M.b, (n * 3 + j) * G, k * 64 + r * 32, full + 8 * s, 3);
        else tma_load(base + s * SB + 16384 + j * 128 * G, &M.b, (n * 3 + j) * G, (k0 + k) * 64, full + 8 * s);
      }
      if (flag >= 0 && k == 0) flag_wait(flag, 64, 30);
      if (flag >= 0) tma_load(base + s * SB, &M.a, (k0 + k) * 64, m * 128, full + 8 * s);
    }
    if (++s == NST) { s = 0; ph ^= 1; }
  }
}
template <int NST, bool PAIR, int G> DEVI void out_rows(const OutMaps& M, uint32_t base, uint32_t full, int m, int flag, int cnt, int waiters) {
  flag_wait(flag, cnt, waiters);
  int s = 0, ph = !PAIR;
#pragma unroll 1
  for (int k = 0; k < 64; k++) {
    if (k == cnt) mbar_wait(full + 16 * NST, 0);
    mbar_wait(full + 8 * (NST + s), ph);
    if (PAIR && G == 32) tma_load_mc(base + s * (16384 + 384 * G) + (blockIdx.x & 1) * 8192, &M.a, k * 64, m * 128 + (blockIdx.x & 1) * 64, full + 8 * s, 3);
    else tma_load(base + s * (16384 + 384 * G), &M.a, k * 64, m * 128, full + 8 * s);
    if (++s == NST) { s = 0; ph ^= 1; }
  }
}
template <int NST, bool PAIR, int G> DEVI void out_consume(float* acc, uint32_t base, uint32_t full, int nk) {
  constexpr int SB = 16384 + 384 * G;
  const uint32_t empty = full + 8 * NST;
  const int wg = threadIdx.x >> 7;
  int s = 0, ph = 0, prev = 0;
#pragma unroll 1
  for (int k = 0; k < nk; k++) {
    mbar_wait(full + 8 * s, ph);
    const uint64_t da = desc_k(base + s * SB + wg * 8192), db = mkdesc(base + s * SB + 16384, 128 * G, 16 * G, G == 64 ? 1 : 2);
    wg_fence();
#pragma unroll
    for (int kk = 0; kk < 4; kk++) {
      if (G == 64) wg_ss192<1>(acc, da + kk * 2, db + kk * 128, k | kk);
      else wg_ss96t(acc, da + kk * 2, db + kk * 64, k | kk);
    }
    wg_commit();
    if (k) { wg_wait<1>(); if (PAIR) arrive_pair(empty + 8 * prev); else if ((threadIdx.x & 127) == 0) mbar_arrive(empty + 8 * prev); }
    prev = s;
    if (++s == NST) { s = 0; ph ^= 1; }
  }
  wg_wait<0>();
}
template <int NST, bool PAIR, int G> DEVI void out_tile(const OutMaps& M, uint32_t base, uint32_t full, int m, int n) {
  const int tid = threadIdx.x, wg = tid >> 7;
  float acc[G * 3 / 2];
  out_consume<NST, PAIR, G>(acc, base, full, 64);
  bar_sync(6, 256);
  const uint32_t row = ((tid >> 5) & 3) * 16 + (tid & 15);
  const uint32_t roff = row * 2 * G + ((((tid >> 4) & 1) ^ (G == 64 ? row & 7 : (row >> 1) & 3)) << 4);
#pragma unroll
  for (int i = 0; i < G * 3 / 16; i++) {
    const float* a = acc + i * 8;
    stsm4(base + wg * 384 * G + i / (G / 16) * 128 * G + (roff ^ (i % (G / 16) * 32)), pack2(a[0], a[1]), pack2(a[2], a[3]), pack2(a[4], a[5]), pack2(a[6], a[7]));
  }
  fence_async();
  bar_sync(1 + wg, 128);
  if ((tid & 127) == 0) {
#pragma unroll 1
    for (int c = 0; c < 3; c++) tma_store(&M.c, base + wg * 384 * G + c * 128 * G, (n * 3 + c) * G, m * 128 + wg * 64);
    bulk_commit();
    bulk_wait_read<0>();
  }
}
struct OutParams { OutMaps p[2]; int n, odd; uint8_t tile[64]; };
constexpr int SM_O = 6 * 28672 + 256;
__global__ void __launch_bounds__(384, 1) out_kernel(const __grid_constant__ OutParams P) {
  extern __shared__ __align__(1024) uint8_t smem_raw[];
  const uint32_t base = s2u(smem_raw), full = base + 6 * 28672;
  const int tid = threadIdx.x, t = P.tile[blockIdx.x], half = t >> 7, m = (t >> 3) & 15, n = t & 7;
  TL_START(4)
  pdl_trigger();
  if (tid == 0) {
    for (int i = 0; i < 12; i++) mbar_init(full + 8 * i, i >= 4 + 2 * half ? 2 : 1);
    asm volatile("fence.mbarrier_init.release.cluster;" ::: "memory");
  }
  __syncthreads();
  if (tid >= 256) {
    if (tid == 256) { if (half) out_produce<6, false, 32>(P.p[1], base, full, m, n, 0, 64, -1); else out_produce<4, false, 64>(P.p[0], base, full, m, n, 0, 64, -1); }
    if (tid == 288) { if (half) out_rows<6, false, 32>(P.p[1], base, full, m, S_CTXB + m, 64, 4); else out_rows<4, false, 64>(P.p[0], base, full, m, S_CTXB + m, 64, 3 + (m == P.odd)); }
  } else {
    if (tid == 0) CT(4, 0)
    if (half) out_tile<6, false, 32>(P.p[1], base, full, m, n); else out_tile<4, false, 64>(P.p[0], base, full, m, n);
    if (tid == 0) CT(4, 2)
    TL_END(4)
  }
}
struct FaParams { ProjParams p; CUtensorMap q, k, v, o; unsigned proj, nctas, ngroups; uint8_t nproj[12]; uint16_t order[512];
                  OutMaps om[3]; uint16_t tile[96]; };
constexpr int HST = 5, F_OUT = 7 * 32768 + 512, F_OUTH = F_OUT + 72, F_TILE = F_OUTH + 16 * HST, SM_F = F_OUT + 256;
constexpr float FA_C = 0.08838834764831845f * 1.4426950408889634f;
DEVI int fa_qt(int w) { return w >> 5; }
DEVI int fa_hc(int w) { return (w & 31) * 128; }

DEVI void fa_exp(const float* S, uint32_t* Pn, float mc0, float mc1, float& s0, float& s1) {
  float a0 = 0.f, a1 = 0.f, b0 = 0.f, b1 = 0.f;
#pragma unroll
  for (int j = 0; j < 16; j++) {
    const float e0 = ex2(fmaf(S[4 * j], FA_C, -mc0)), e1 = ex2(fmaf(S[4 * j + 1], FA_C, -mc0));
    const float e2 = ex2(fmaf(S[4 * j + 2], FA_C, -mc1)), e3 = ex2(fmaf(S[4 * j + 3], FA_C, -mc1));
    a0 += e0; a1 += e1; b0 += e2; b1 += e3;
    Pn[2 * j] = pack2(e0, e1); Pn[2 * j + 1] = pack2(e2, e3);
  }
  s0 = a0 + a1; s1 = b0 + b1;
}

struct FaState { float mc0, mc1, l0, l1; int w, j, qi; uint32_t dq; bool first; };
enum { F_Q = 0, F_K = 2 * 32768, F_V = 4 * 32768, F_O = 6 * 32768, F_QF = 7 * 32768, F_QE = F_QF + 16, F_KF = F_QF + 32, F_KE = F_QF + 48, F_VF = F_QF + 64, F_VE = F_QF + 80,
       F_OF = F_QF + 96, F_OE = F_QF + 112, F_INFO = F_QF + 128 };

DEVI void out_open(uint32_t base, int tid, uint32_t mask) {
  const int s = (tid & 127) >> 1;
  if (s < 4 + HST && ((mask >> s) & 1))
    asm volatile("mbarrier.arrive.shared::cluster.b64 _,[%0];" ::"r"(mapa(base + (s < 4 ? F_OUT + 32 : F_OUTH + 8 * HST - 32) + 8 * s, tid & 1)) : "memory");
}
template <int SC> DEVI bool fa_step(FaState& T, float* O, float* S, const uint32_t* Pc, uint32_t* Pn, uint32_t base, int tid, int wg, uint32_t ph) {
  const bool el = (tid & 127) == 0, fin = T.j == 0;
  int wn = T.w, jn = T.j - 1;
  const bool okk = mbar_try(base + F_KF + 8 * (SC ^ 1), ph), okv = mbar_try(base + F_VF + 8 * SC, ph ^ SC);
  if (fin) {
    T.qi++; T.dq ^= 2048;
    mbar_wait(base + F_QF + 8 * (T.qi & 1), (T.qi >> 1) & 1);
    asm volatile("ld.shared.b32 %0,[%1];" : "=r"(wn) : "r"(base + F_INFO + (T.qi & 1) * 4) : "memory");
    wn = __shfl_sync(~0u, wn, 0);
    jn = fa_qt(wn);
    if (wn < 0) out_open(base, tid, 0xf7);
  }
  if (!(okk && okv)) { mbar_wait(base + F_KF + 8 * (SC ^ 1), ph); mbar_wait(base + F_VF + 8 * SC, ph ^ SC); }
  const bool last = wn < 0;
  {
    const uint64_t dq = desc_k(0) | T.dq, dk = desc_k(base + F_K + (SC ^ 1) * 32768), dv = desc_mn(base + F_V + SC * 32768, 16384);
    bar_sync(3 + wg, 256);
    wg_fence();
#pragma unroll
    for (int kk = 0; kk < 8; kk++) wg_ss128<0>(S, dq + (kk & 3) * 2 + (kk >> 2) * 1024, dk + (kk & 3) * 2 + (kk >> 2) * 1024, kk);
    wg_commit();
#pragma unroll
    for (int kk = 0; kk < 8; kk++) wg_rs128<1>(O, Pc + 4 * kk, dv + kk * 128, kk || !T.first);
    wg_commit();
    bar_arrive(4 - wg, 256);
  }
  wg_wait<1>();
  asm volatile("{.reg .pred p,q; setp.ne.u32 p,%0,0; setp.eq.and.u32 q,%1,0,p; @p mbarrier.arrive.shared::cta.b64 _,[%2]; @q mbarrier.arrive.shared::cta.b64 _,[%3];}"
               ::"r"((uint32_t)el), "r"(jn), "r"(base + F_KE + 8 * (SC ^ 1)), "r"(base + F_QE + 8 * (T.qi & 1)) : "memory");
  const float lp0 = T.l0, lp1 = T.l1;
  float s0 = 0.f, s1 = 0.f, f0 = 1.f, f1 = 1.f;
  bool exact = fin;
  if (!fin) {
    fa_exp(S, Pn, T.mc0, T.mc1, s0, s1);
    exact = __any_sync(~0u, !(fmaxf(s0, s1) <= 1073741824.f));
  }
  if (exact && !last) {
    float a = -INFINITY, b = -INFINITY;
    if (fin) {
      const int row = (tid >> 5) * 16 + ((tid & 31) >> 2) - (tid & 3) * 2;
#pragma unroll
      for (int j = 0; j < 16; j++) {
        if (j * 8 > row) S[4 * j] = -INFINITY;
        if (j * 8 + 1 > row) S[4 * j + 1] = -INFINITY;
        if (j * 8 > row + 8) S[4 * j + 2] = -INFINITY;
        if (j * 8 + 1 > row + 8) S[4 * j + 3] = -INFINITY;
      }
      T.mc0 = T.mc1 = -INFINITY;
    }
#pragma unroll
    for (int j = 0; j < 16; j++) { a = fmaxf(a, fmaxf(S[4 * j], S[4 * j + 1])); b = fmaxf(b, fmaxf(S[4 * j + 2], S[4 * j + 3])); }
    a = fmaxf(a, __shfl_xor_sync(~0u, a, 1)); b = fmaxf(b, __shfl_xor_sync(~0u, b, 1));
    a = fmaxf(a, __shfl_xor_sync(~0u, a, 2)); b = fmaxf(b, __shfl_xor_sync(~0u, b, 2));
    a = fmaxf(a * FA_C, T.mc0); b = fmaxf(b * FA_C, T.mc1);
    f0 = ex2(T.mc0 - a); f1 = ex2(T.mc1 - b);
    T.mc0 = a; T.mc1 = b;
    T.l0 = fin ? 0.f : T.l0 * f0; T.l1 = fin ? 0.f : T.l1 * f1;
    fa_exp(S, Pn, a, b, s0, s1);
  }
  T.l0 += s0; T.l1 += s1;
  wg_wait<0>();
  if (el) mbar_arrive(base + F_VE + 8 * SC);
  if (exact) {
    if (fin) {
      f0 = lp0 + __shfl_xor_sync(~0u, lp0, 1); f1 = lp1 + __shfl_xor_sync(~0u, lp1, 1);
      f0 += __shfl_xor_sync(~0u, f0, 2); f1 += __shfl_xor_sync(~0u, f1, 2);
      f0 = 1.f / f0; f1 = 1.f / f1;
    }
#pragma unroll
    for (int i = 0; i < 16; i++) { O[4 * i] *= f0; O[4 * i + 1] *= f0; O[4 * i + 2] *= f1; O[4 * i + 3] *= f1; }
    if (fin && (T.qi || last)) {
      const uint32_t row = ((tid >> 5) & 3) * 16 + (tid & 15);
      const uint32_t o = base + F_O + wg * 16384 + row * 128 + ((((tid >> 4) & 1) ^ (row & 7)) << 4);
      if (T.qi) mbar_wait(base + F_OE + 8 * wg, (T.qi & 1) ^ 1);
#pragma unroll
      for (int i = 0; i < 8; i++) {
        const float* a = O + i * 8;
        stsm4((o ^ ((i & 3) * 32)) + (i >> 2) * 8192, pack2(a[0], a[1]), pack2(a[2], a[3]), pack2(a[4], a[5]), pack2(a[6], a[7]));
      }
      if (el) asm volatile("st.shared.b32 [%0],%1;" ::"r"(base + F_INFO + 8 + wg * 4), "r"(!T.qi ? -1 : T.w | (last ? 1024 : 0)) : "memory");
      fence_async();
      __syncwarp();
      if ((tid & 31) == 0) mbar_arrive(base + F_OF + 8 * wg);
    }
  }
  T.w = wn; T.j = jn; T.first = fin;
  return last;
}

__global__ void __launch_bounds__(384, 1) fa_kernel(const __grid_constant__ FaParams P) {
  extern __shared__ __align__(1024) uint8_t smem_raw[];
  const uint32_t base = __shfl_sync(~0u, s2u(smem_raw), 0);
  const uint32_t sQ = base, sK = base + 2 * 32768, sV = base + 4 * 32768, sO = base + 6 * 32768, bars = base + 7 * 32768;
  const uint32_t qf = bars, qe = bars + 16, kf = bars + 32, ke = bars + 48, vf = bars + 64, ve = bars + 80, of = bars + 96, oe = bars + 112;
  volatile int* info = (volatile int*)(smem_raw + 7 * 32768 + 128);
  const int tid = threadIdx.x, wg = tid >> 7;
  const ProjItem& I = P.p.item[blockIdx.x >> 1];
  const bool leave = P.proj && I.leave;
  auto my_tile = [&]() { mbar_wait(base + F_TILE, 0); return info[5]; };
  pdl_trigger();
  if (tid == 0) {
    if (P.proj) proj_init(I, base);
    for (int i = 0; i < 16; i++) mbar_init(bars + 8 * i, i >= 14 ? 1 : i >= 12 ? 4 : (i & 2) ? 2 : 1);
    for (int i = 0; i < 10 + 2 * HST; i++) mbar_init(base + F_OUT + 8 * i, (i >= 4 && i < 8) || (i >= 9 + HST && i < 9 + 2 * HST) ? 4 : 1);
    mbar_expect(base + F_TILE, 4);
    info[4] = 0;
    asm volatile("fence.mbarrier_init.release.cluster;" ::: "memory");
  }
  __syncthreads();
  cluster_sync_relaxed();
  if (wg == 2) {
    reg_dec<24>();
    if (tid == 256) {
      int it = 0, qi = 0, vc = 0, vr = -1, j = 0, hc = 0;
      int pph = P.proj ? proj_produce(P.p, I, base) : -1;
      auto drain = [&](int s0) { if (pph >= 0) for (int i = s0; i < s0 + 6; i++) mbar_wait(base + P_EMPTY + 8 * i, pph); };
      if (leave) { drain(0); drain(6); return; }
      CT(P.proj ? 3 : 6, 0)
      auto load_v = [&]() {
        if (vr < 0) return;
        const int s = (it - 1) & 1;
        drain(6); pph = -1;
        mbar_wait(ve + 8 * s, (((it - 1) >> 1) & 1) ^ 1 ^ s);
        mbar_expect(vf + 8 * s, 32768);
        tma_load(sV + s * 32768, &P.v, vc, vr, vf + 8 * s);
        tma_load(sV + s * 32768 + 16384, &P.v, vc + 64, vr, vf + 8 * s);
        vr = -1;
      };
      auto ready = [&](uint32_t m) { uint32_t v; asm volatile("ld.acquire.cta.shared.b32 %0,[%1];" : "=r"(v) : "r"(base + F_INFO + 16) : "memory"); return (v & m) == m; };
      for (it = -1;; it++) {
        if (it >= 0) {
          const int s = it & 1;
          if (it || j < 0) { drain(6); pph = -1; }
          mbar_wait(ke + 8 * s, ((it >> 1) & 1) ^ 1);
          if (j < 0) { mbar_arrive(kf + 8 * s); load_v(); break; }
          mbar_expect(kf + 8 * s, 32768);
          tma_load(sK + s * 32768, &P.k, hc, j * 128, kf + 8 * s);
          tma_load(sK + s * 32768 + 16384, &P.k, hc + 64, j * 128, kf + 8 * s);
        }
        int nc = hc, nr = it >= 0 ? j * 128 : -1;
        if (j-- == 0) {
          int w = atomicInc(&g_sync[S_QUEUE], 511 + P.nctas);
          w = w < 512 ? P.order[w] : -1;
          const uint32_t q = qi & 1, m = w < 0 ? 0x3ffff : (1u | (2u << (fa_qt(w) | 1))) << ((w >> 4) & 1);
          if (!ready(m) || !mbar_test(qe + 8 * q, ((qi >> 1) & 1) ^ 1)) {
            load_v(); it++; vc = nc; vr = nr; load_v(); it--; nr = -1;
            for (int n = 0; !ready(m) && n < WAIT_MAX; n++) __nanosleep(64);
            mbar_wait(qe + 8 * q, ((qi >> 1) & 1) ^ 1);
          }
          asm volatile("fence.proxy.async.global;" ::: "memory");
          if (it < 0) drain(0);
          info[q] = w;
          if (w < 0) mbar_arrive(qf + 8 * q);
          else {
            j = fa_qt(w); hc = fa_hc(w);
            mbar_expect(qf + 8 * q, 32768);
            tma_load(sQ + q * 32768, &P.q, hc, j * 128, qf + 8 * q);
            tma_load(sQ + q * 32768 + 16384, &P.q, hc + 64, j * 128, qf + 8 * q);
          }
          qi++;
        }
        load_v();
        vc = nc; vr = nr;
      }
      const int tile = my_tile(), kind = tile >> 7, tm = (tile >> 3) & 15, tn = tile & 7;
      if (atomicInc(&g_sync[S_EXIT], P.nctas - 1) == P.nctas - 1) {
#pragma unroll 1
        for (int i = S_LIST; i < S_PROJ + 18; i++) g_sync[i] = 0;
#pragma unroll 1
        for (int i = 0; i < 16; i++) ((uint4*)g_group)[i] = make_uint4(0, 0, 0, 0);
      }
      if (kind == 2) out_produce<HST, true, 32>(P.om[2], base, base + F_OUTH, tm, tn, 0, 64, -1);
      else if (kind < 2) out_produce<4, true, 64>(P.om[kind], base, base + F_OUT, tm, tn, 0, 64, -1);
      else { mbar_wait(base + F_OUT + 56, 0); mbar_wait(base + F_TILE - 8, 0); }
    } else if (tid >= 352) {
      const int l = tid - 352;
      if (P.proj) mbar_wait(base + P_END, 0);
#pragma unroll 1
      for (int n = 0; n < WAIT_MAX && !leave; n++) {
        unsigned v = 255;
        if (l < 18) asm volatile("ld.acquire.gpu.global.u32 %0, [%1];" : "=r"(v) : "l"(g_sync + S_PROJ + l) : "memory");
        const uint32_t m = __ballot_sync(~0u, v >= P.nproj[(l >> 1) % 9]);
        __syncwarp();
        if (l == 0) asm volatile("st.release.cta.shared.b32 [%0],%1;" ::"r"(base + F_INFO + 16), "r"(m) : "memory");
        if (m == ~0u) break;
        __nanosleep(300);
      }
      if (l == 0 && !(blockIdx.x & 1) && !leave) {
        unsigned sm; asm("mov.u32 %0,%%smid;" : "=r"(sm));
        unsigned g = *(volatile uint8_t*)&g_group[sm & 255] - 1u, i;
        if (g > P.ngroups) g = P.ngroups;
        while ((i = g * 8 + atomicAdd(&g_sync[S_LIST + g], 1)) >= (g < P.ngroups ? g * 8 + 8 : P.nctas / 2)) g = g ? g - 1 : P.ngroups;
        for (int r = 0; r < 2; r++)
          asm volatile("st.async.weak.shared::cluster.mbarrier::complete_tx::bytes.b32 [%0],%1,[%2];" ::"r"(mapa(base + F_INFO + 20, r)), "r"((int)P.tile[i * 2 + r]), "r"(mapa(base + F_TILE, r)) : "memory");
      }
      if (l == 0 && !leave) {
        const int tile = my_tile(), kind = tile >> 7, tm = (tile >> 3) & 15;
        mbar_wait(base + (kind == 2 ? F_OUTH + 8 * HST : F_OUT + 32), 0);
        if (kind == 2) out_rows<HST, true, 32>(P.om[2], base, base + F_OUTH, tm, S_CTXB + tm, 64, 6);
        else if (kind < 2) out_rows<4, true, 64>(P.om[kind], base, base + F_OUT, tm, (kind ? S_CTXB : S_CTXA) + tm, kind ? 64 : 32, 3);
      }
    } else if (tid == 288 || tid == 320) {
      const int g = tid == 320;
      if (P.proj) proj_store(P.p, I, base, g);
      if (leave) return;
      mbar_arrive(oe + 8 * g);
        for (int n = 0;; n++) {
          mbar_wait(of + 8 * g, n & 1);
          const int v = info[2 + g], w = v & 1023, qt = fa_qt(w), hc = fa_hc(w);
          if (v < 0) break;
          tma_store(&P.o, sO + g * 16384, hc, qt * 128 + g * 64);
          tma_store(&P.o, sO + g * 16384 + 8192, hc + 64, qt * 128 + g * 64);
          bulk_commit();
          bulk_wait_read<0>();
          mbar_arrive(oe + 8 * g);
          bulk_wait<0>();
          signal_after_bulk(S_CTXA + (w & 16) + qt);
          if (v & 1024) break;
        }
      if (!g && my_tile() < 128) { flag_wait(S_CTXA + 16 + (info[5] >> 3), 32, 3); mbar_arrive(base + F_OUT + 64); }
    }
  } else {
    reg_inc<240>();
    const uint32_t ub = base;
    const int uw = __shfl_sync(~0u, wg, 0);
    if (wg == 1 && !leave) bar_arrive(3, 256);
    if (P.proj) proj_consume(I, ub, tid, uw);
    if (leave) return;
    float O[64], S[64];
    uint32_t PA[32], PB[32];
#pragma unroll
    for (int i = 0; i < 32; i++) PA[i] = 0;
#pragma unroll
    for (int i = 0; i < 64; i++) O[i] = 0.f;
    FaState T = {0.f, 0.f, 1.f, 1.f, 0, 0, -1, ((ub + 32768 + uw * 8192) >> 4) & 0x3fff, true};
    for (uint32_t ph = 0;; ph ^= 1) {
      if (fa_step<1>(T, O, S, PA, PB, ub, tid, uw, ph)) break;
      if (fa_step<0>(T, O, S, PB, PA, ub, tid, uw, ph)) break;
    }
    if (wg == 0) bar_sync(3, 256);
    out_open(ub, tid, ~0xf7u);
    const int tile = __shfl_sync(~0u, my_tile(), 0), kind = tile >> 7, tm = (tile >> 3) & 15, tn = tile & 7;
    if (tid == 0) CT(P.proj ? 5 : 2, 0)
    TL_START(5)
    if (kind == 2) out_tile<HST, true, 32>(P.om[2], ub, ub + F_OUTH, tm, tn);
    else if (kind < 2) out_tile<4, true, 64>(P.om[kind], ub, ub + F_OUT, tm, tn);
    if (tid == 0) CT(P.proj ? 5 : 2, 2)
    TL_END(kind == 2 ? 2 : 5)
  }
}
#define PS 20
#define PT(i)
#define YD 200
#define NPF 4
#define NRES 6
#define RP 208
#define PD 2
#define VR "............rrrrrr.................."
#define VP "222222222222111111111111------------"
constexpr int vr_index(int k) { int n = 0; for (int i = 0; i < k; i++) n += VR[i] == 'r'; return n; }
constexpr int VB = vr_index(36);
template <int K> struct VIdx { static constexpr int v = vr_index(K); static constexpr char r = VR[K], p = VP[K]; };
#define XG 6
#define XW 2
#define WOD 4000
#define KA 26
constexpr int R_WV = 0, R_WO = 73728, R_H = 147456, R_OX = R_H + 46080, R_Q = R_OX + 4096, R_K = R_Q + 5120, R_SX = R_K + 5120, R_P = R_SX + 3200, R_U = R_P + 3200,
              R_BAR = R_H + 73728, R_PROF = R_BAR + 256, R_END = R_PROF + 3072;
constexpr int B_W0 = R_BAR, B_W1 = R_BAR + 8, B_XA = R_BAR + 16, B_XB = R_BAR + 24, B_XF = R_BAR + 32, B_Z0 = R_BAR + 40, B_Z1 = R_BAR + 48, B_R = R_BAR + 56,
              B_SM = R_BAR + 64, B_SX = R_BAR + 72, B_U = R_BAR + 80, B_V = R_BAR + 88, B_W2 = R_BAR + 96, B_W3 = R_BAR + 104, B_O = R_BAR + 112;
static_assert(R_U + 4096 <= R_BAR, "");
enum { N_P1 = 1, N_PM, N_PX, N_SUM, N_O, N_INIT, N_INIT1, N_INIT2, N_WO, N_S };
constexpr int YSLOT = 9 * 16 * 1024;
struct RecParams { CUtensorMap wq, wk, wv, wo, x, ctx; OutMaps o; const bf16 *mem0, *x_raw; bf16* out; };
constexpr int TAIL0 = 14;
constexpr int TST = 6, R_RED = TST * 28672;

DEVI void wg_rs32(float* d, const uint32_t* a, uint64_t db, int acc) {
  asm volatile("{.reg .pred p; setp.ne.b32 p,%21,0;\n wgmma.mma_async.sync.aligned.m64n32k16.f32.bf16.bf16 {%0,%1,%2,%3,%4,%5,%6,%7,%8,%9,%10,%11,%12,%13,%14,%15},{%16,%17,%18,%19},%20,p,1,1,0;}"
               : F8(d, 0), F8(d, 8) : "r"(a[0]), "r"(a[1]), "r"(a[2]), "r"(a[3]), "l"(db), "r"(acc));
}
DEVI void wg_rs40(float* d, const uint32_t* a, uint64_t db, int acc) {
  asm volatile("{.reg .pred p; setp.ne.b32 p,%25,0;\n wgmma.mma_async.sync.aligned.m64n40k16.f32.bf16.bf16 {%0,%1,%2,%3,%4,%5,%6,%7,%8,%9,%10,%11,%12,%13,%14,%15,%16,%17,%18,%19},{%20,%21,%22,%23},%24,p,1,1,0;}"
               : F8(d, 0), F8(d, 8), "+f"(d[16]), "+f"(d[17]), "+f"(d[18]), "+f"(d[19]) : "r"(a[0]), "r"(a[1]), "r"(a[2]), "r"(a[3]), "l"(db), "r"(acc));
}
template <int TB> DEVI void wg_ss40(float* d, uint64_t da, uint64_t db, int acc) {
  asm volatile("{.reg .pred p; setp.ne.b32 p,%22,0;\n wgmma.mma_async.sync.aligned.m64n40k16.f32.bf16.bf16 {%0,%1,%2,%3,%4,%5,%6,%7,%8,%9,%10,%11,%12,%13,%14,%15,%16,%17,%18,%19},%20,%21,p,1,1,1,%23;}"
               : F8(d, 0), F8(d, 8), "+f"(d[16]), "+f"(d[17]), "+f"(d[18]), "+f"(d[19]) : "l"(da), "l"(db), "r"(acc), "n"(TB));
}
DEVI void mma8(float* d, uint32_t a0, uint32_t a1, uint32_t b0) {
  asm volatile("mma.sync.aligned.m16n8k8.row.col.f32.bf16.bf16.f32 {%0,%1,%2,%3},{%4,%5},{%6},{%0,%1,%2,%3};" : "+f"(d[0]), "+f"(d[1]), "+f"(d[2]), "+f"(d[3]) : "r"(a0), "r"(a1), "r"(b0));
}
DEVI void stsm4t(uint32_t a, uint32_t r0, uint32_t r1, uint32_t r2, uint32_t r3) {
  asm volatile("stmatrix.sync.aligned.m8n8.x4.trans.shared.b16 [%0],{%1,%2,%3,%4};" ::"r"(a), "r"(r0), "r"(r1), "r"(r2), "r"(r3) : "memory");
}
DEVI uint32_t movm(uint32_t a) { uint32_t d; asm volatile("movmatrix.sync.aligned.m8n8.trans.b16 %0,%1;" : "=r"(d) : "r"(a)); return d; }
DEVI void sts1(uint32_t a, uint32_t v) { asm volatile("st.shared.b32 [%0],%1;" ::"r"(a), "r"(v) : "memory"); }
DEVI uint32_t lds1(uint32_t a) { uint32_t v; asm volatile("ld.shared.b32 %0,[%1];" : "=r"(v) : "r"(a) : "memory"); return v; }
DEVI void sta1(uint32_t d, uint32_t a, uint32_t bar) { asm volatile("st.async.weak.shared::cluster.mbarrier::complete_tx::bytes.b32 [%0],%1,[%2];" ::"r"(d), "r"(a), "r"(bar) : "memory"); }
DEVI void sta2(uint32_t d, uint32_t a, uint32_t b, uint32_t bar) { asm volatile("st.async.weak.shared::cluster.mbarrier::complete_tx::bytes.v2.b32 [%0],{%1,%2},[%3];" ::"r"(d), "r"(a), "r"(b), "r"(bar) : "memory"); }
DEVI uint32_t clk32() { uint64_t c; asm volatile("mov.u64 %0,%%clock64;" : "=l"(c)::"memory"); return (uint32_t)c; }
DEVI int opq(int x) { asm volatile("" : "+r"(x)); return x; }
DEVI int pin(int x) { return __shfl_sync(~0u, x, threadIdx.x & 31); }
DEVI void x_load(const RecParams& P, uint32_t sb, int c, int seg) {
  asm volatile("cp.async.bulk.tensor.2d.shared::cluster.global.mbarrier::complete_tx::bytes.multicast::cluster [%0],[%1,{%3,%4}],[%2],%5;"
               ::"r"(sb + R_H + c * 5120 + 1024), "l"(&P.x), "r"(sb + (c < XG ? B_XA : B_XB)), "r"(c * 64), "r"(seg * 32), "h"((uint16_t)0xffff) : "memory");
  if (seg + 2 < NSEG) asm volatile("cp.async.bulk.prefetch.tensor.2d.L2.global [%0,{%1,%2}];" ::"l"(&P.x), "r"(c * 64), "r"(seg * 32 + 64) : "memory");
}
DEVI uint32_t hadd2(uint32_t a, uint32_t b) { uint32_t r; asm("add.rn.bf16x2 %0,%1,%2;" : "=r"(r) : "r"(a), "r"(b)); return r; }
DEVI uint32_t hmax2(uint32_t a, uint32_t b) { uint32_t r; asm("max.bf16x2 %0,%1,%2;" : "=r"(r) : "r"(a), "r"(b)); return r; }
DEVI float rcp(float x) { float y; asm("rcp.approx.ftz.f32 %0,%1;" : "=f"(y) : "f"(x)); return y; }
constexpr float SCL = 0.08838834764831845f * 1.4426950408889634f;

DEVI void y_store(const float* a, uint32_t off, int s) {
  const uint32_t x = movm(pack2(a[0], a[1])), y = movm(pack2(a[2], a[3]));
  const uint32_t tag = ((s >> 1) & 1) ^ 1;
  asm volatile("st.relaxed.gpu.global.b64 [%0],%1;" ::"l"((uint8_t*)g_Y + (s & 1) * YSLOT + off), "l"((uint64_t)((x & ~1u) | tag) | ((uint64_t)y << 32)) : "memory");
}
DEVI void y_load(uint32_t* w, const uint8_t* p) {
#pragma unroll
  for (int i = 0; i < 4; i++) asm volatile("{.reg .b64 t; ld.relaxed.gpu.global.b64 t,[%2]; mov.b64 {%0,%1},t;}" : "=r"(w[2 * i]), "=r"(w[2 * i + 1]) : "l"(p + i * 256) : "memory");
}
DEVI bool y_missing(const uint32_t* w, uint32_t tag) {
  uint32_t r;
  asm volatile("{.reg .b32 a,b; .reg .pred p; lop3.b32 a,%1,%2,%5,0x7e; lop3.b32 b,%3,%4,%5,0x7e; lop3.b32 a,a,b,1,0xa8; setp.ne.u32 p,a,0; vote.sync.any.pred p,p,0xffffffff; selp.u32 %0,1,0,p;}"
               : "=r"(r) : "r"(w[0]), "r"(w[2]), "r"(w[4]), "r"(w[6]), "r"(tag));
  return r;
}
DEVI void y_reload(uint32_t* w, const uint8_t* p, uint32_t tag) {
#pragma unroll
  for (int i = 0; i < 4; i++)
    asm volatile("{.reg .b64 t; .reg .b32 a; .reg .pred q; lop3.b32 a,%0,%3,1,0x28; setp.ne.u32 q,a,0; mov.b64 t,{%0,%1}; @q ld.relaxed.gpu.global.b64 t,[%2]; mov.b64 {%0,%1},t;}"
                 : "+r"(w[2 * i]), "+r"(w[2 * i + 1]) : "l"(p + i * 256), "r"(tag) : "memory");
}
DEVI void y_sum(uint32_t* r, const uint32_t* w, uint32_t sel) {
  float d0[4] = {0, 0, 0, 0}, d1[4] = {0, 0, 0, 0};
  mma16(d0, w[0], w[1], w[2], w[3], sel, sel); mma16(d1, w[4], w[5], w[6], w[7], sel, sel);
  r[0] = pack2(d0[0] + d1[0], d0[1] + d1[1]); r[1] = pack2(d0[2] + d1[2], d0[3] + d1[3]);
}
DEVI void y_send(const uint32_t* r, uint32_t sb, uint32_t dst, uint32_t bar, int lane) {
#pragma unroll
  for (int i = 0; i < 4; i++) { const uint32_t rs = mapa(sb, (lane & 3) + i * 4); sta2(rs + dst, r[0], r[1], rs + bar); }
}
DEVI void wo_convert(uint32_t sb, int lane) {
  TL_END(11)
  mbar_wait(sb + B_W3, 0);
  TL_END(9)
#pragma unroll 1
  for (uint32_t a = sb + R_WO + ((threadIdx.x >> 5) & 3) * 4608, i = 0; i < 4; i++, a += 18432) {
    uint32_t r[9][4];
#pragma unroll
    for (int k = 0; k < 9; k++) ldsm4t(r[k], a + k * 32 + ((lane & 7) + (lane >> 4) * 8) * 288 + ((lane >> 3) & 1) * 16);
    __syncwarp();
#pragma unroll
    for (int k = 0; k < 9; k++) stsm4(a + k * 512 + ((lane >> 4) * 2 + ((lane >> 1) & 1)) * 128 + (((lane >> 2) & 3) * 2 + (lane & 1)) * 16, r[k][0], r[k][1], r[k][2], r[k][3]);
  }
  __syncwarp();
}
DEVI uint32_t y_offset(int cta, int tile, int lane) {
  const int T = (cta & 3) * 9 + tile;
  return (((T >> 2) * 8 + (lane >> 2)) * 2 + ((T >> 1) & 1)) * 1024 + (cta >> 4) * 256 + (T & 1) * 128 + ((cta >> 2) & 3) * 32 + (lane & 3) * 8;
}
template <int NR, int NP> DEVI void wo_tile(const uint32_t (*A0)[4], uint32_t sb, int tile, int lane, uint32_t yo, int s) {
  uint32_t u[8][4], A[16][4];
  const uint32_t wa = sb + R_WO + tile * 512 + lane * 16, ua = sb + R_U + lane * 16;
  float a[4] = {0, 0, 0, 0}, b[4] = {0, 0, 0, 0};
  auto fetch = [&](int i) { if (i < 16 - NR) ldsm4(A[i], wa + i * 4608); };
  auto uload = [&](int i) { if (i < 8) ldsm4t(u[i], ua + i * 512); };
#pragma unroll
  for (int i = 0; i < NP; i++) fetch(i);
  mwait(sb + B_V, s & 1);
  PT(6)
  uload(0); uload(1);
#pragma unroll
  for (int i = 0; i < 16; i++) {
    if (i == 4) {
      mwait(sb + B_U, s & 1);
      PT(7)
      uload(2); uload(3);
    }
    const uint32_t* f = i >= 16 - NR ? A0[i >= 16 - NR ? i - 16 + NR : 0] : A[i];
    mma16(i & 1 ? b : a, f[0], f[1], f[2], f[3], u[i >> 1][(i & 1) * 2], u[i >> 1][(i & 1) * 2 + 1]);
    fetch(i + NP);
    if (i >= 4 && (i & 1)) uload((i >> 1) + 2);
  }
#pragma unroll
  for (int i = 0; i < 4; i++) a[i] += b[i];
  y_store(a, yo, s);
}
template <bool X> DEVI void softmax8(const uint32_t* h, uint32_t a4, uint32_t a1) {
  uint32_t y[5];
  lds4(y, a4 + R_SX);
  y[4] = lds1(a1 + R_SX);
#pragma unroll
  for (int j = 0; j < 5; j++) y[j] = hadd2(h[j], y[j]);
  const uint32_t m2 = hmax2(hmax2(hmax2(y[0], y[1]), hmax2(y[2], y[3])), y[4]);
  const float mc = fmaxf(blo(m2), bhi(m2)) * SCL;
  const float m1 = __shfl_xor_sync(~0u, mc, 1), m3 = __shfl_xor_sync(~0u, mc, 2), m4 = __shfl_xor_sync(~0u, mc, 3);
  float e[10];
#pragma unroll
  for (int j = 0; j < 5; j++) { e[2 * j] = ex2(fmaf(blo(y[j]), SCL, -mc)); e[2 * j + 1] = ex2(fmaf(bhi(y[j]), SCL, -mc)); }
  const float c = ex2(mc - fmaxf(fmaxf(mc, m1), fmaxf(m3, m4)));
  const float l = c * ((((e[0] + e[1]) + (e[2] + e[3])) + ((e[4] + e[5]) + (e[6] + e[7]))) + (e[8] + e[9]));
  const float r = c * rcp((l + __shfl_xor_sync(~0u, l, 1)) + (__shfl_xor_sync(~0u, l, 2) + __shfl_xor_sync(~0u, l, 3)));
#pragma unroll
  for (int j = 0; j < 5; j++) y[j] = pack2(e[2 * j] * r, e[2 * j + 1] * r);
  if (!X) sts4(a4 + R_P, y[0], y[1], y[2], y[3]);
  else stsm4(a4 + R_P, y[0], y[1], y[2], y[3]);
  sts1(a1 + R_P, y[4]);
  if (X) fence_async();
}

DEVI void arm_step(uint32_t sb, int s) {
  mbar_expect(sb + B_SM, 640); mbar_expect(sb + B_SX, 2560);
  if (s < NSEG - 1) {
    mbar_expect(sb + B_U, 3072); mbar_expect(sb + B_Z0, 4096); mbar_expect(sb + B_Z1, 5120);
    mbar_expect(sb + B_XA, XG * 4096); mbar_expect(sb + B_XB, (9 - XG) * 4096);
  }
}
DEVI void rec_proj(const RecParams& P, const uint32_t sb, const int cta) {
  uint32_t W[36][4], A0[NRES ? NRES : 1][4];
  const int tid = pin(threadIdx.x);
  const uint32_t yo = pin(y_offset(cta, threadIdx.x >> 5, threadIdx.x & 31));
  const int warp = __shfl_sync(~0u, threadIdx.x >> 5, 0), role = warp >> 2;
  const uint32_t qk = sb + R_Q + warp * 1280;
  {
    const int lane = threadIdx.x & 31, w4 = (threadIdx.x >> 5) & 3;
    const uint32_t a = sb + role * R_H + ((lane & 7) + (lane >> 4) * 8) * 128 + (((w4 * 2 + ((lane >> 3) & 1)) ^ (lane & 7)) << 4);
    mbar_wait(sb + B_W0 + role * 8, 0);
    TL_END(8)
#pragma unroll
    for (int k = 0; k < 36; k++) ldsm4t(W[k], a + k * 2048);
    if (role) bar_arrive(N_INIT1, 256); else bar_sync(N_INIT, 128);
    cluster_sync_relaxed();
#pragma unroll
    for (int i = 0; i < NRES; i++) A0[i][0] = A0[i][1] = A0[i][2] = A0[i][3] = 0;
  }
  for (int s = -1; s < NSEG; s++) {
    if (s >= 0) {
      PT(0)
      {
        const int lane = opq(tid) & 31;
        const uint32_t hb = sb + R_H + (lane & 7) * 128 + (((lane >> 3) ^ (lane & 7)) << 4);
        float a[4] = {0, 0, 0, 0}, b[4] = {0, 0, 0, 0};
        mwait(sb + B_Z0, (s - 1) & 1);
        PT(1)
        uint32_t f[18][4];
#pragma unroll
        for (int c = -PD; c < 18; c++) {
          if (c + PD == 8) mwait(sb + B_Z1, (s - 1) & 1);
          if (c + PD < 18) ldsm4(f[c + PD], (hb ^ (((c + PD) & 1) * 64)) + ((c + PD) >> 1) * 5120);
          if (c >= 0) {
            mma16(a, W[2 * c][0], W[2 * c][1], W[2 * c][2], W[2 * c][3], f[c][0], f[c][1]);
            mma16(b, W[2 * c + 1][0], W[2 * c + 1][1], W[2 * c + 1][2], W[2 * c + 1][3], f[c][2], f[c][3]);
          }
        }
        sts1(qk + 512 + lane * 4, pack2(a[0] + b[0], a[1] + b[1]));
        sts1(qk + 1152 + lane * 4, pack2(a[2] + b[2], a[3] + b[3]));
        fence_async();
      }
      PT(2)
      const int lane = opq(tid) & 31;
      if (role) {
        bar_arrive(N_P1, 256);
        if (tid == 128) arm_step(sb, s);
        const uint32_t o4 = sb + (warp - 4) * 640 + lane * 16, o1 = sb + (warp - 4) * 640 + 512 + lane * 4;
        uint32_t h[5];
        bar_sync(N_PX, 192);
        lds4(h, o4 + R_P); h[4] = lds1(o1 + R_P);
        mwait(sb + B_SX, s & 1);
        PT(4)
        softmax8<true>(h, o4, o1);
        PT(5)
      } else {
        float S[20];
        const uint64_t da = mkdesc(sb + R_Q, 640, 128, 0), db = mkdesc(sb + R_K, 640, 128, 0);
        const uint32_t rs = mapa(sb, (cta & 15) ^ 1);
        const uint32_t o4 = warp * 1280 + lane * 16, o1 = warp * 1280 + 512 + lane * 4;
        bar_sync(N_P1, 256);
        wg_fence();
#pragma unroll
        for (int k = 0; k < 4; k++) wg_ss40<1>(S, da + k * 80, db + k * 80, k);
        wg_commit();
        bar_arrive(N_S, 256);
        wg_wait<0>();
        PT(3)
        uint32_t h[2][5];
        if (warp == 2) {
#pragma unroll
          for (int j = 0; j < 5; j++) h[0][j] = pack2(S[4 * j], S[4 * j + 1]);
          sta4(rs + R_SX + o4, h[0][0], h[0][1], h[0][2], h[0][3], rs + B_SM); sta1(rs + R_SX + o1, h[0][4], rs + B_SM);
          mwait(sb + B_SM, s & 1);
          PT(4)
          softmax8<false>(h[0], sb + o4, sb + o1);
          bar_arrive(N_PM, 160);
        } else if (warp < 2) {
          const int row = warp * 16 + (lane >> 2) - (lane & 3) * 2;
#pragma unroll
          for (int g = 0; g < 2; g++) {
#pragma unroll
            for (int j = 0; j < 5; j++) h[g][j] = pack2(j < 4 && j * 8 > row + g * 8 ? -INFINITY : S[4 * j + 2 * g], j < 4 && j * 8 + 1 > row + g * 8 ? -INFINITY : S[4 * j + 2 * g + 1]);
            sts4(sb + R_P + o4 + g * 640, h[g][0], h[g][1], h[g][2], h[g][3]); sts1(sb + R_P + o1 + g * 640, h[g][4]);
            sta4(rs + R_SX + o4 + g * 640, h[g][0], h[g][1], h[g][2], h[g][3], rs + B_SX);
            sta1(rs + R_SX + o1 + g * 640, h[g][4], rs + B_SX);
          }
          bar_arrive(N_PX, 192);
        } else {
          if (s) bar_sync(N_O, 160);
          if (tid == 96) {
            if (s) {
              bulk_wait<0>();
              tma_store(&P.ctx, sb + R_OX, cta * 64, s * 32 - 32); bulk_commit();
              if ((s & 3) == 1 && s > 1) signal_after_bulk(S_CTXB + (s >> 2) - 1);
              bulk_wait_read<0>();
            }
          }
        }
        __syncwarp();
        PT(5)
      }
      {
        if (s == 0) {
          bar_sync(N_INIT2, 384);
#pragma unroll
          for (int i = 0; i < NRES; i++) ldsm4(A0[i], sb + R_WO + warp * 512 + lane * 16 + (16 - NRES + i) * 4608);
        }
        if (s == NSEG - 1) break;
        wo_tile<NRES, NPF>(A0, sb, warp, lane, yo, s);

        PT(8)
        bar_sync(N_WO, 384);
      }
    }
    {
      float acc[16];
      const uint64_t db = mkdesc(sb + R_H + 1024, 16, 1024, 1);
      mwait(sb + B_XA, (s + 1) & 1);
      PT(9)
      wg_fence();
#pragma unroll
      for (int k = 0; k < XG * 4; k++) wg_rs32(acc, W[k], db + (k >> 2) * 320 + (k & 3) * 2, k);
      wg_commit();
      mwait(sb + B_XB, (s + 1) & 1);
      wg_fence();
#pragma unroll
      for (int k = XG * 4; k < KA; k++) wg_rs32(acc, W[k], db + (k >> 2) * 320 + (k & 3) * 2, 1);
      wg_commit();
      wg_wait<0>();
      PT(10)
      bar_sync(N_SUM, 384);
      wg_fence();
#pragma unroll
      for (int k = KA; k < 36; k++) wg_rs32(acc, W[k], db + (k >> 2) * 320 + (k & 3) * 2, 1);
      wg_commit();
      const uint32_t o = qk + (opq(tid) & 31) * 16;
      wg_wait<0>();
      PT(11)
      stsm4(o, pack2(acc[0], acc[1]), pack2(acc[4], acc[5]), pack2(acc[8], acc[9]), pack2(acc[12], acc[13]));
      stsm4(o + 640, pack2(acc[2], acc[3]), pack2(acc[6], acc[7]), pack2(acc[10], acc[11]), pack2(acc[14], acc[15]));
    }
  }
  bar_arrive(N_WO, 384);
  for (int i = 0; i < (warp ? 1 : 2); i++)
    asm volatile("st.relaxed.gpu.global.b64 [%0],%1;" ::"l"((uint8_t*)g_Y + YSLOT + yo + i * 2 * 16384), "l"(0ull) : "memory");
  TL_END(6)
  if (tid == 0) CT(1, 0)
  if (warp == 3) {
    if (tid == 96) { bulk_wait<0>(); asm volatile("fence.proxy.async.global;" ::: "memory"); }
    __syncwarp();
    bar_arrive(N_O, 160);
  }
  asm volatile("barrier.cluster.arrive.relaxed.aligned;" ::: "memory");
  float acc[48];
  const int rk = opq(cta) & 15, n = rk / 5, q = rk - n * 5;
  out_consume<TST, false, 32>(acc, sb, sb + B_O, rk == 15 ? 0 : q == 4 ? 12 : 13);
  if (tid == 0) CT(7, 1)
  if (tid == 0) CT(1, 1)
  asm volatile("barrier.cluster.wait.aligned;" ::: "memory");
  bar_sync(N_P1, 256);
  {
#pragma unroll
    for (int u = 0; u < 6; u++) {
      const int d = u % 5;
      const float* a = acc + u * 8;
      const uint32_t x = pack2(a[0], a[1]), y = pack2(a[2], a[3]), z = pack2(a[4], a[5]), w = pack2(a[6], a[7]);
      const uint32_t rs = mapa(sb, rk == 15 ? 15 : n * 5 + d);
      if (d == q) sts4(sb + R_RED - 8192 + (u / 5) * 4096 + tid * 16, x, y, z, w);
      else sta4(rs + R_RED + (q < d ? q : q - 1) * 8192 + (u / 5) * 4096 + tid * 16, x, y, z, w, rs + B_R);
    }
    mbar_wait(sb + B_R, 0);
    if (tid == 0) CT(1, 2)
    const int lane = tid & 31;
    const uint32_t st = sb + warp * 1024 + (lane & 15) * 48 + (lane >> 4) * 16, ld = sb + warp * 1024 + (lane >> 1) * 48 + (lane & 1) * 16;
    bf16* out = P.out + (size_t)((TAIL0 + (cta >> 5)) * 128 + warp * 16 + (lane >> 1)) * (2 * DM) + DM + ((cta >> 4) & 1) * 288 + n * 96 + q * 16 + (lane & 1) * 8;
#pragma unroll 1
    for (int i = 0; i < (q ? 1 : 2); i++) {
      uint32_t v[5][4], r[4];
#pragma unroll
      for (int p = 0; p < 5; p++) lds4(v[p], sb + R_RED + (p - 1) * 8192 + i * 4096 + tid * 16);
#pragma unroll
      for (int j = 0; j < 4; j++)
        r[j] = pack2((blo(v[0][j]) + blo(v[1][j])) + (blo(v[2][j]) + blo(v[3][j])) + blo(v[4][j]), (bhi(v[0][j]) + bhi(v[1][j])) + (bhi(v[2][j]) + bhi(v[3][j])) + bhi(v[4][j]));
      stsm4(st + i * 8192, r[0], r[1], r[2], r[3]);
      __syncwarp();
      lds4(r, ld + i * 8192);
      asm volatile("{.reg .pred p; setp.ne.s32 p,%5,15; @p st.global.v4.b32 [%0],{%1,%2,%3,%4};}" ::"l"(out + i * 80), "r"(r[0]), "r"(r[1]), "r"(r[2]), "r"(r[3]), "r"(rk) : "memory");
    }
  }
}

template <int K> DEVI void v_resident(uint32_t (*F)[4], uint32_t wv) {
  if constexpr (K < 36) { if (VIdx<K>::r == 'r') ldsm4t(F[VIdx<K>::v], wv + K * 2048); v_resident<K + 1>(F, wv); }
}
template <int K> DEVI void v_pass(float* acc, const uint32_t (*F)[4], uint64_t da, uint64_t db, uint32_t xf, uint32_t t, uint32_t nrel) {
  if constexpr (K < 36) {
    wg_fence();
    if (VIdx<K>::r == 'r') wg_rs40(acc, F[VIdx<K>::v], db + (K >> 2) * 320 + (K & 3) * 2, K);
    else wg_ss40<0>(acc, da + K * 128, db + (K >> 2) * 320 + (K & 3) * 2, K);
    wg_commit();
    if constexpr (VIdx<K>::p != '-') wg_wait<VIdx<K>::p - '0'>();
    if (K == XG * 4 - 1 + XW) { wg_wait<XW>(); asm volatile("{.reg .pred p; .reg .b32 a; setp.lt.u32 p,%1,%2; @p mapa.shared::cluster.u32 a,%0,%1; @p mbarrier.arrive.shared::cluster.b64 _,[a];}" ::"r"(xf), "r"(t), "r"(nrel) : "memory"); }
    v_pass<K + 1>(acc, F, da, db, xf, t, nrel);
  }
}
DEVI void rec_aux(const RecParams& P, const uint32_t sb, const int cta) {
  const int tid = pin(threadIdx.x);
  {
    uint4 v[5];
#pragma unroll
    for (int j = 0; j < 5; j++) if (j * 128 + tid - 256 < 576) v[j] = ((const uint4*)P.mem0)[j * 128 + tid - 256];
    if (tid == 288) {
      const uint32_t t0 = clk32();
      while (clk32() - t0 < (uint32_t)WOD) {}
#pragma unroll 1
      for (int i = 0; i < 4; i++) tma_load(sb + R_WO + i * 18432, &P.wo, (cta & 3) * 144, (cta ^ i) * 64, sb + B_W3);
      for (int i = 0; i < 3; i++) asm volatile("cp.async.bulk.prefetch.tensor.2d.L2.global [%0,{%1,%2}];" ::"l"(&P.wv), "r"(cta * 64), "r"(i * 192) : "memory");
    }
    __syncwarp();
    bar_sync(N_INIT1, 256);
#pragma unroll
    for (int j = 0; j < 5; j++) {
      const int i = j * 128 + tid - 256, t = i / 72, c = i - t * 72;
      if (i < 576) sts4(sb + R_H + (c >> 3) * 5120 + t * 128 + (((c & 7) ^ t) << 4), v[j].x, v[j].y, v[j].z, v[j].w);
    }
    fence_async();
    bar_arrive(N_SUM, 384);
    cluster_sync_relaxed();
    if (tid == 288) {
      if ((cta & 15) < 9) x_load(P, sb, cta & 15, 0);
#pragma unroll 1
      for (int i = 0; i < 3; i++) tma_load(sb + R_WV + i * 24576, &P.wv, cta * 64, i * 192, sb + B_W2);
    }
    __syncwarp();
    TL_END(12)
    wo_convert(sb, threadIdx.x & 31);
    bar_sync(N_O, 128);
    bar_arrive(N_INIT2, 384);
    TL_END(10)
  }
  const int rk = cta & 15, w4 = __shfl_sync(~0u, (threadIdx.x >> 5) & 3, 0);
  const uint32_t yg = pin((((threadIdx.x >> 5) & 3) * 16 + rk) * 1024 + ((threadIdx.x >> 4) & 1) * 128 + (threadIdx.x & 3) * 32 + ((threadIdx.x >> 2) & 3) * 8);
  uint32_t F[VB][4];
  mbar_wait(sb + B_W2, 0);
  TL_END(7)
  v_resident<0>(F, sb + R_WV + ((tid & 7) + ((tid >> 4) & 1) * 8) * 128 + (((w4 * 2 + ((tid >> 3) & 1)) ^ (tid & 7)) << 4));
  LT(0)
  for (int s = 0; s < NSEG; s++) {
    const bool last = s == NSEG - 1;
    uint32_t va[12], p[5];
    int lane = opq(tid) & 31;
    {
      float acc[20];
      const uint64_t da = mkdesc(sb + R_WV, 0, 1024, 1), db = mkdesc(sb + R_H, 16, 1024, 1);
      PT(0)
      bar_sync(N_S, 256);
      asm volatile("fence.proxy.async::generic.acquire.sync_restrict::shared::cluster.cluster;" ::: "memory");
      v_pass<0>(acc, F, da, db, sb + B_XF, tid - 256, last ? 0 : XG);
      PT(13)
      bar_sync(N_PM, 160);
      lds4(p, sb + R_P + 2560 + lane * 16); p[4] = lds1(sb + R_P + 3072 + lane * 4);
      wg_wait<0>();
      PT(1)
#pragma unroll
      for (int i = 0; i < 10; i++) va[i < 2 ? i + 8 : i - 2] = pack2(acc[2 * i], acc[2 * i + 1]);
      va[10] = va[11] = 0;
    }
    lane = opq(tid) & 31;
    if (!last) {
      const uint32_t uo = R_U + w4 * 256 + lane * 4;
      float a[4] = {0, 0, 0, 0}, b[4] = {0, 0, 0, 0}, c[4] = {0, 0, 0, 0};
      mma16(a, va[0], va[1], va[2], va[3], p[0], p[1]); mma16(b, va[4], va[5], va[6], va[7], p[2], p[3]); mma8(c, va[8], va[9], p[4]);
      const uint32_t u0 = pack2(a[0] + b[0] + c[0], a[1] + b[1] + c[1]), u1 = pack2(a[2] + b[2] + c[2], a[3] + b[3] + c[3]);
      sts1(sb + uo, u0); sts1(sb + uo + 128, u1);
      __syncwarp();
      if (lane == 0) mbar_arrive(sb + B_V);
#pragma unroll
      for (int q = 1; q < 4; q++) { const uint32_t rs = mapa(sb, rk ^ q); sta1(rs + uo + q * 1024, u0, rs + B_U); sta1(rs + uo + q * 1024 + 128, u1, rs + B_U); }
      asm volatile("{.reg .pred p; .reg .b32 a; setp.lt.u32 p,%1,%3; @p mapa.shared::cluster.u32 a,%0,%2; @p mbarrier.arrive.shared::cluster.b64 _,[a];}" ::"r"(sb + B_XF), "r"(tid - 256 - XG), "r"(tid - 256), "n"(9 - XG) : "memory");
      PT(4)
      if (w4 == 3) {
        wo_tile<0, 4>(nullptr, sb, 8, lane, y_offset(cta, 8, lane), s);
      } else if (tid == 288 && rk < 9) { mbar_wait(sb + B_XF, s & 1); x_load(P, sb, rk, s + 1); }
      PT(2)
    }
    lane = opq(tid) & 31;
    uint32_t ox[8], tu;
    {
      float o[16];
      const uint64_t dp = mkdesc(sb + R_P, 128, 640, 0);
      bar_sync(N_WO, 384);
      wg_fence();
      wg_rs32(o, va, dp, 0); wg_rs32(o, va + 4, dp + 16, 1); wg_rs32(o, va + 8, mkdesc(sb + R_P + 512, 0, 640, 0), 1);
      wg_commit();
      tu = clk32();
      wg_wait<0>();
      PT(3)
#pragma unroll
      for (int i = 0; i < 8; i++) ox[i] = pack2(o[2 * i], o[2 * i + 1]);
    }
    if (!last) {
      const uint8_t* y = (const uint8_t*)g_Y + (s & 1) * YSLOT + yg;
      uint32_t w0[8], w1[8], w2[8];
      while (clk32() - tu < (uint32_t)YD) {}
      y_load(w0, y); y_load(w1, y + 4 * 16384);
      if (w4 == 0) y_load(w2, y + 8 * 16384);
      else {
#pragma unroll
        for (int i = 0; i < 8; i++) w2[i] = ((s >> 1) & 1) ^ 1;
      }
      PT(5)
      const uint32_t dst = R_H + w4 * 5120 + (rk >> 1) * 128 + ((((rk & 1) * 4 + (lane >> 3)) ^ (rk >> 1)) << 4) + (lane & 4) * 2;
      const uint32_t tag = ((s >> 1) & 1) ^ 1, sel = (lane & 4) ? 0x3f800000u : 0x3f80u;
      uint32_t r0[2], r1[2], r2[2];
#pragma unroll 1
      for (int it = 0; (y_missing(w0, tag) | y_missing(w1, tag) | y_missing(w2, tag)) && it < (1 << 20); it++) {
        y_reload(w0, y, tag); y_reload(w1, y + 4 * 16384, tag); y_reload(w2, y + 8 * 16384, tag);
      }
      PT(7)
      y_sum(r0, w0, sel); y_sum(r1, w1, sel); y_sum(r2, w2, sel);
      y_send(r0, sb, dst, B_Z0, lane);
      bar_arrive(N_SUM, 384);
      y_send(r1, sb, dst + 4 * 5120, B_Z1, lane);
      if (w4 == 0) y_send(r2, sb, dst + 8 * 5120, B_Z1, lane);
      PT(9)
    }
#pragma unroll
    for (int h = 0; h < 2; h++) stsm4t(sb + R_OX + lane * 128 + (((w4 * 2 + h) ^ (lane & 7)) << 4), ox[h], ox[2 + h], ox[4 + h], ox[6 + h]);
    if (last) break;
    fence_async();
    bar_arrive(N_O, 160);
    PT(11)
  }
  fence_async();
  bar_sync(N_O, 160);
  if (tid == 256) {
    tma_store(&P.ctx, sb + R_OX, cta * 64, SEQ - 32); bulk_commit(); bulk_wait<0>(); signal_after_bulk(S_CTXB + 15);
  }
  __syncwarp();
  LT(1)
  asm volatile("barrier.cluster.arrive.relaxed.aligned;" ::: "memory");
  if (tid == 256) {
    const int m = TAIL0 + (cta >> 5), n = rk / 5, q = rk - n * 5;
    mbar_expect(sb + B_R, q || rk == 15 ? 4 * 4096 : 8 * 4096);
    if (rk < 15) out_produce<TST, false, 32>(P.o, sb, sb + B_O, m, ((cta >> 4) & 1) * 3 + n, q * 13, q == 4 ? 12 : 13, S_CTXB + m);
  }
  __syncwarp();
  asm volatile("barrier.cluster.wait.aligned;" ::: "memory");
}

__global__ void __launch_bounds__(384, 1) rec_kernel(const __grid_constant__ RecParams P) {
  extern __shared__ __align__(1024) uint8_t smem_raw[];
  const uint32_t sb = s2u(smem_raw);
  const int tid = threadIdx.x, cta = blockIdx.x;
  pdl_trigger();
  if (cta >= 64) {
    unsigned sm; asm("mov.u32 %0,%%smid;" : "=r"(sm));
    if (tid == 0) g_group[sm & 255] = (cta >> 4) - 3;
    return;
  }
  TL_START(1)
  if (tid == 0) {
    for (int i = 0; i < 14 + 2 * TST; i++) mbar_init(sb + R_BAR + 8 * i, 8 * i == B_XF - R_BAR ? 16 : 8 * i == B_V - R_BAR ? 4 : i >= 14 + TST ? 2 : 1);
    asm volatile("fence.mbarrier_init.release.cluster;" ::: "memory");
    asm volatile("cp.async.bulk.prefetch.L2.global [%0],%1;" ::"l"(P.x_raw + cta * DM), "r"(DM * 2) : "memory");
    mbar_expect(sb + B_W0, 73728); mbar_expect(sb + B_W1, 73728); mbar_expect(sb + B_W2, 73728); mbar_expect(sb + B_W3, 73728);
#pragma unroll 1
    for (int i = 0; i < 3; i++) { tma_load(sb + R_WV + i * 24576, &P.wq, cta * 64, i * 192, sb + B_W0); tma_load(sb + R_H + i * 24576, &P.wk, cta * 64, i * 192, sb + B_W1); }
    mbar_expect(sb + B_XA, XG * 4096); mbar_expect(sb + B_XB, (9 - XG) * 4096);
  }
  __syncthreads();
  if (tid >= 256) { reg_dec<504 - 2 * RP>(); rec_aux(P, sb, cta); }
  else { reg_inc<RP>(); rec_proj(P, sb, cta); }
  TL_END(1)
  if (tid == 0) CT(7, 2)
  cluster_sync_relaxed();
}
typedef CUresult (*EncFn)(CUtensorMap*, CUtensorMapDataType, cuuint32_t, void*, const cuuint64_t*, const cuuint64_t*, const cuuint32_t*, const cuuint32_t*,
                          CUtensorMapInterleave, CUtensorMapSwizzle, CUtensorMapL2promotion, CUtensorMapFloatOOBfill);
static EncFn g_enc;
static CUtensorMap mk(const void* p, uint64_t cols, uint64_t rows, uint64_t pitch_elems, uint32_t box_rows, uint32_t box_cols = 64) {
  CUtensorMap m;
  cuuint64_t dim[2] = {cols, rows}, str[1] = {pitch_elems * 2};
  cuuint32_t box[2] = {box_cols, box_rows}, es[2] = {1, 1};
  g_enc(&m, CU_TENSOR_MAP_DATA_TYPE_BFLOAT16, 2, (void*)p, dim, str, box, es, CU_TENSOR_MAP_INTERLEAVE_NONE, box_cols == 64 ? CU_TENSOR_MAP_SWIZZLE_128B : box_cols == 32 ? CU_TENSOR_MAP_SWIZZLE_64B : CU_TENSOR_MAP_SWIZZLE_NONE,
        CU_TENSOR_MAP_L2_PROMOTION_L2_256B, CU_TENSOR_MAP_FLOAT_OOB_FILL_NONE);
  return m;
}
template <class T> static void* sym(T& s) { void* p; cudaGetSymbolAddress(&p, s); return p; }

#define FE 6
#define STG 10
#define FHC 24
#define FSL 5
#define NF2 20
template <class K, class A> static void launch(K k, int grid, int smem, int cluster, bool pdl, const A& arg) {
  cudaLaunchConfig_t c = {};
  cudaLaunchAttribute at[2];
  int n = 0;
  if (cluster > 1) { at[n].id = cudaLaunchAttributeClusterDimension; at[n].val.clusterDim.x = cluster; at[n].val.clusterDim.y = at[n].val.clusterDim.z = 1; n++; }
  if (pdl) { at[n].id = cudaLaunchAttributeProgrammaticStreamSerialization; at[n].val.programmaticStreamSerializationAllowed = 1; n++; }
  c.gridDim = grid; c.blockDim = 384; c.dynamicSmemBytes = smem; c.stream = cudaStreamPerThread; c.attrs = at; c.numAttrs = n;
  cudaLaunchKernelEx(&c, k, arg);
}

extern "C" void kernel_launch(void* const* d_in, const int* in_sizes, int n_in, void* d_out, int out_size) {
  static int nb, ng;
  if (!g_enc) {
    cudaDriverEntryPointQueryResult qr;
    cudaGetDriverEntryPoint("cuTensorMapEncodeTiled", (void**)&g_enc, cudaEnableDefault, &qr);
    cudaDeviceGetAttribute(&nb, cudaDevAttrMultiProcessorCount, 0);
    nb = nb - 64 < 54 ? 54 : nb - 64 > 96 ? 96 : (nb - 64) & ~1;
    cudaFuncSetAttribute(out_kernel, cudaFuncAttributeMaxDynamicSharedMemorySize, SM_O);
    cudaFuncSetAttribute(fa_kernel, cudaFuncAttributeMaxDynamicSharedMemorySize, SM_F);
    cudaFuncSetAttribute(rec_kernel, cudaFuncAttributeMaxDynamicSharedMemorySize, R_END);
    cudaFuncSetAttribute(rec_kernel, cudaFuncAttributeNonPortableClusterSizeAllowed, 1);
    cudaLaunchConfig_t c = {};
    cudaLaunchAttribute at; at.id = cudaLaunchAttributeClusterDimension; at.val.clusterDim.x = 16; at.val.clusterDim.y = at.val.clusterDim.z = 1;
    c.gridDim = 128; c.blockDim = 384; c.dynamicSmemBytes = R_END; c.attrs = &at; c.numAttrs = 1;
    cudaOccupancyMaxActiveClusters(&ng, rec_kernel, &c);
    ng = ng < 4 ? 0 : ng - 4 > nb / 16 ? nb / 16 : ng - 4;
  }
  const bf16 *Ax = (const bf16*)d_in[0], *Ac = (const bf16*)d_in[1], *Awq = (const bf16*)d_in[2], *Awk = (const bf16*)d_in[3], *Awv = (const bf16*)d_in[4],
             *Awo = (const bf16*)d_in[5], *Bx = (const bf16*)d_in[6], *Bm = (const bf16*)d_in[7], *Bwq = (const bf16*)d_in[8], *Bwk = (const bf16*)d_in[9],
             *Bwv = (const bf16*)d_in[10], *Bwo = (const bf16*)d_in[11];
  bf16* out = (bf16*)d_out;
  FaParams f;
  ProjParams& p = f.p;
  int nitems = 0;
  p.a[0] = mk(Ac, 512, SEQ, 512, 128); p.a[1] = mk(Ax, DM, SEQ, DM, 128);
  p.w[0] = mk(Awk, HD, 512, HD, 64); p.w[1] = mk(Awv, HD, 512, HD, 64); p.w[2] = mk(Awq, HD, DM, HD, 64);
  p.c[0] = mk(sym(g_kA), HD, SEQ, HD, 64); p.c[1] = mk(sym(g_vA), HD, SEQ, HD, 64); p.c[2] = mk(sym(g_qA), HD, SEQ, HD, 64);
  {
    int parts[16];
    for (int i = 0; i < 16; i++) parts[i] = 1;
    for (int e = 0; e < nb / 2 - 16; e++) parts[e % 24 < 16 ? e % 8 : 15 - (e % 24 - 16)]++;
    for (int i = 15; i >= 0; i--)
      for (int j = 0, nc = i < 8 ? 32 : 16, a = parts[i]; j < a; j++) {
        ProjItem& I = p.item[nitems++];
        I.pa = i >> 3; I.m = i & 7;
        I.c0[0] = j * nc / a; I.n[0] = (j + 1) * nc / a - I.c0[0];
        I.c0[1] = (j * nc + a - 1) / a; I.n[1] = ((j + 1) * nc + a - 1) / a - I.c0[1];
        if (i < 8 && a == 3) { const int d = STG * (i + 4) / 11, b1 = 11 - d, b2 = 22 - d + (i - 4) * STG / 16; I.c0[1] = j == 0 ? 0 : j == 1 ? b1 : b2; I.n[1] = (j == 0 ? b1 : j == 1 ? b2 : 32) - I.c0[1]; }
      }
  }
  for (int i = 0; i < nitems; i++) {
    auto len = [&](int j) { return (8 + p.item[j].pa) * (1 + p.item[j].n[0] + p.item[j].n[1]); };
    int longer = 0;
    for (int j = 0; j < nitems; j++) longer += len(j) > len(i) || (len(j) == len(i) && j < i);
    p.item[i].leave = longer < NF2 / 2;
    p.item[i].s0 = (PST - len(i) % PST) % PST;
  }
  OutParams o;
  for (int i = 0; i < 3; i++) {
    f.om[i].a = mk(i ? sym(g_ctxB) : sym(g_qA), HD, SEQ, HD, 128);
    f.om[i].b = i < 2 ? mk(i ? Bwo : Awo, DM, HD, DM, 32) : mk(Bwo, DM, HD, DM, 64, 32);
    f.om[i].c = mk(out + (i ? DM : 0), DM, SEQ, 2 * DM, 64, i < 2 ? 64 : 32);
  }
  o.p[0] = f.om[1]; o.p[0].b = mk(Bwo, DM, HD, DM, 64); o.p[1] = f.om[2];
  f.q = mk(sym(g_qA), HD, SEQ, HD, 128); f.k = mk(sym(g_kA), HD, SEQ, HD, 128); f.v = mk(sym(g_vA), HD, SEQ, HD, 128); f.o = mk(sym(g_qA), HD, SEQ, HD, 64);
  f.nctas = nb; f.ngroups = ng;
  for (int i = 0; i < 9; i++) f.nproj[i] = 0;
  for (int i = 0; i < nitems; i++) f.nproj[p.item[i].pa * (p.item[i].m + 1)] += 4;
  for (int key = -90, n = 0; n < 512; key++)
    for (int h = 0; h < 32; h++)
      for (int qt = 0; qt < 16; qt++)
        if ((h < FHC ? h : FHC) * FSL - qt * 2 - (qt >= 12 && h < FE ? 60 : 0) == key) f.order[n++] = qt * 32 + h;
  RecParams r;
  r.wq = mk(Bwq, HD, DM, HD, 192); r.wk = mk(Bwk, HD, DM, HD, 192); r.wv = mk(Bwv, HD, DM, HD, 192); r.wo = mk(Bwo, DM, HD, DM, 64, 144);
  r.x_raw = Bx;
  r.x = mk(Bx, DM, SEQ, DM, 32); r.ctx = mk(sym(g_ctxB), HD, SEQ, HD, 32); r.mem0 = Bm; r.o = f.om[2]; r.out = out;

  f.om[2].a = mk(sym(g_ctxB), HD, SEQ, HD, 64);
  uint16_t* last = f.tile;
  int nl = 0;
  for (int m = 14; m >= 0; m -= 2)
    for (int n = 0; n < 3; n++) { last[nl++] = m * 8 + n; last[nl++] = m * 8 + 8 + n; }
  for (int n = 0; n < 6; n++) last[nl++] = 256 + (TAIL0 - 1) * 8 + n;
  bool done[16][3] = {};
  for (int m = TAIL0 - 3; m >= 0; m -= 2)
    for (int n = 2; n >= 0 && nl < nb; n--) { last[nl++] = 128 + m * 8 + n; last[nl++] = 128 + m * 8 + 8 + n; done[m][n] = done[m + 1][n] = true; }
  while (nl < nb) last[nl++] = 384;
  o.n = 2; o.odd = 0; o.tile[0] = 128; o.tile[1] = 129; done[0][0] = true;
  for (int m = 0; m < TAIL0 - 1; m++)
    for (int n = 0; n < 3; n++) if (!done[m][n]) o.tile[o.n++] = m * 8 + n;
  launch(rec_kernel, 64 + 16 * ng, R_END, 16, false, r);
  f.proj = 1;
  launch(fa_kernel, nb, SM_F, 2, true, f);
  launch(out_kernel, o.n, SM_O, 2, true, o);
  f.proj = 0;
  launch(fa_kernel, NF2, SM_F, 2, true, f);
}
```

```cpp
#include <cuda_runtime.h>
#include <cuda_bf16.h>
#include <cuda.h>
#include <stdint.h>

typedef __nv_bfloat16 bf16;
#define DEVI __device__ __forceinline__
#define WAIT_FAIL(code) break
#define WAIT_MAX (1 << 22)

constexpr int SEQ = 2048, HD = 4096, DM = 576, NSEG = 64;

__device__ __align__(1024) bf16 g_qA[SEQ * HD], g_kA[SEQ * HD], g_vA[SEQ * HD];
__device__ __align__(1024) bf16 g_ctxB[SEQ * HD];
__device__ __align__(1024) uint4 g_Y[2 * 9 * 16 * 64];
enum { S_QUEUE = 0, S_EXIT = 1, S_LIST = 8, S_PROJ = 32, S_CTXA = 64, S_CTXB = 96 };
__device__ unsigned g_sync[128];
__device__ __align__(16) uint8_t g_group[256];
#define LT(i)
#define CT(k, i) {}
#define TL_START(i)
#define TL_END(i)

DEVI uint32_t s2u(const void* p) { return (uint32_t)__cvta_generic_to_shared(p); }
DEVI void mbar_init(uint32_t b, uint32_t c) { asm volatile("mbarrier.init.shared::cta.b64 [%0],%1;" ::"r"(b), "r"(c)); }
DEVI void mbar_expect(uint32_t b, uint32_t n) { asm volatile("mbarrier.arrive.expect_tx.shared::cta.b64 _,[%0],%1;" ::"r"(b), "r"(n) : "memory"); }
DEVI void mbar_arrive(uint32_t b) { asm volatile("mbarrier.arrive.shared::cta.b64 _,[%0];" ::"r"(b) : "memory"); }
DEVI void mbar_wait(uint32_t b, uint32_t ph) {
  uint32_t ok; int it = 0;
  do {
    asm volatile("{.reg .pred p; mbarrier.try_wait.parity.shared::cta.b64 p,[%1],%2; selp.u32 %0,1,0,p;}" : "=r"(ok) : "r"(b), "r"(ph) : "memory");
    if (!ok && ++it > WAIT_MAX) WAIT_FAIL(b & 0xffffff);
  } while (!ok);
}
DEVI bool mbar_try(uint32_t b, uint32_t ph) {
  uint32_t ok;
  asm volatile("{.reg .pred p; mbarrier.try_wait.parity.shared::cta.b64 p,[%1],%2; selp.u32 %0,1,0,p;}" : "=r"(ok) : "r"(b), "r"(ph) : "memory");
  return ok;
}
DEVI bool mbar_test(uint32_t b, uint32_t ph) {
  uint32_t ok;
  asm volatile("{.reg .pred p; mbarrier.test_wait.parity.shared::cta.b64 p,[%1],%2; selp.u32 %0,1,0,p;}" : "=r"(ok) : "r"(b), "r"(ph) : "memory");
  return ok;
}
DEVI void mwait(uint32_t b, uint32_t ph) { if (__builtin_expect(!mbar_try(b, ph), 0)) mbar_wait(b, ph); }
DEVI void tma_load(uint32_t dst, const CUtensorMap* tm, int c0, int c1, uint32_t bar) {
  asm volatile("cp.async.bulk.tensor.2d.shared::cluster.global.mbarrier::complete_tx::bytes [%0],[%1,{%3,%4}],[%2];" ::"r"(dst), "l"(tm), "r"(bar), "r"(c0), "r"(c1) : "memory");
}
DEVI void tma_store(const CUtensorMap* tm, uint32_t src, int c0, int c1) {
  asm volatile("cp.async.bulk.tensor.2d.global.shared::cta.bulk_group [%0,{%2,%3}],[%1];" ::"l"(tm), "r"(src), "r"(c0), "r"(c1) : "memory");
}
DEVI void bulk_commit() { asm volatile("cp.async.bulk.commit_group;" ::: "memory"); }
template <int N> DEVI void bulk_wait_read() { asm volatile("cp.async.bulk.wait_group.read %0;" ::"n"(N) : "memory"); }
template <int N> DEVI void bulk_wait() { asm volatile("cp.async.bulk.wait_group %0;" ::"n"(N) : "memory"); }
DEVI void fence_async() { asm volatile("fence.proxy.async.shared::cta;" ::: "memory"); }
DEVI void bar_sync(int id, int n) { asm volatile("bar.sync %0,%1;" ::"r"(id), "r"(n) : "memory"); }
DEVI void bar_arrive(int id, int n) { asm volatile("bar.arrive %0,%1;" ::"r"(id), "r"(n) : "memory"); }
template <int R> DEVI void reg_inc() { asm volatile("setmaxnreg.inc.sync.aligned.u32 %0;" ::"n"(R)); }
template <int R> DEVI void reg_dec() { asm volatile("setmaxnreg.dec.sync.aligned.u32 %0;" ::"n"(R)); }
DEVI void wg_fence() { asm volatile("wgmma.fence.sync.aligned;" ::: "memory"); }
DEVI void wg_commit() { asm volatile("wgmma.commit_group.sync.aligned;" ::: "memory"); }
template <int N> DEVI void wg_wait() { asm volatile("wgmma.wait_group.sync.aligned %0;" ::"n"(N) : "memory"); }
DEVI uint64_t desc_k(uint32_t a) { return (uint64_t)((a >> 4) & 0x3fff) | (1ull << 16) | (64ull << 32) | (1ull << 62); }
DEVI uint64_t desc_mn(uint32_t a, uint32_t lbo) { return (uint64_t)((a >> 4) & 0x3fff) | ((uint64_t)(lbo >> 4) << 16) | (64ull << 32) | (1ull << 62); }
DEVI uint64_t mkdesc(uint32_t a, uint32_t lbo, uint32_t sbo, int sw) { return (uint64_t)((a >> 4) & 0x3fff) | ((uint64_t)(lbo >> 4) << 16) | ((uint64_t)(sbo >> 4) << 32) | ((uint64_t)sw << 62); }
DEVI uint32_t pack2(float lo, float hi) { uint32_t r; asm("cvt.rn.bf16x2.f32 %0,%1,%2;" : "=r"(r) : "f"(hi), "f"(lo)); return r; }
DEVI float ex2(float x) { float y; asm("ex2.approx.ftz.f32 %0,%1;" : "=f"(y) : "f"(x)); return y; }
DEVI void stsm4(uint32_t a, uint32_t r0, uint32_t r1, uint32_t r2, uint32_t r3) {
  asm volatile("stmatrix.sync.aligned.m8n8.x4.shared.b16 [%0],{%1,%2,%3,%4};" ::"r"(a), "r"(r0), "r"(r1), "r"(r2), "r"(r3) : "memory");
}
DEVI void ldsm4(uint32_t* r, uint32_t a) {
  asm volatile("ldmatrix.sync.aligned.m8n8.x4.shared.b16 {%0,%1,%2,%3},[%4];" : "=r"(r[0]), "=r"(r[1]), "=r"(r[2]), "=r"(r[3]) : "r"(a) : "memory");
}
DEVI void ldsm4t(uint32_t* r, uint32_t a) {
  asm volatile("ldmatrix.sync.aligned.m8n8.x4.trans.shared.b16 {%0,%1,%2,%3},[%4];" : "=r"(r[0]), "=r"(r[1]), "=r"(r[2]), "=r"(r[3]) : "r"(a) : "memory");
}
DEVI void mma16(float* d, uint32_t a0, uint32_t a1, uint32_t a2, uint32_t a3, uint32_t b0, uint32_t b1) {
  asm volatile("mma.sync.aligned.m16n8k16.row.col.f32.bf16.bf16.f32 {%0,%1,%2,%3},{%4,%5,%6,%7},{%8,%9},{%0,%1,%2,%3};"
               : "+f"(d[0]), "+f"(d[1]), "+f"(d[2]), "+f"(d[3]) : "r"(a0), "r"(a1), "r"(a2), "r"(a3), "r"(b0), "r"(b1));
}

DEVI void pdl_trigger() { asm volatile("griddepcontrol.launch_dependents;" ::: "memory"); }
DEVI void signal_after_bulk(int f) {
  asm volatile("fence.proxy.async.global;" ::: "memory");
  asm volatile("red.release.gpu.global.add.u32 [%0], 1;" ::"l"(g_sync + f) : "memory");
}
DEVI void flag_wait(int f, unsigned n, unsigned waiters) {
  for (int it = 0;; it++) {
    if (it > WAIT_MAX) WAIT_FAIL(f);
    unsigned v; asm volatile("ld.acquire.gpu.global.u32 %0, [%1];" : "=r"(v) : "l"(g_sync + f) : "memory");
    if (v >= n) break;
    __nanosleep(64);
  }
  if (waiters) asm volatile("red.relaxed.gpu.global.inc.u32 [%0], %1;" ::"l"(g_sync + f), "r"(n + waiters - 1) : "memory");
  asm volatile("fence.proxy.async.global;" ::: "memory");
}
DEVI uint32_t mapa(uint32_t a, uint32_t r) { uint32_t o; asm("mapa.shared::cluster.u32 %0,%1,%2;" : "=r"(o) : "r"(a), "r"(r)); return o; }
DEVI void tma_load_mc(uint32_t dst, const CUtensorMap* tm, int c0, int c1, uint32_t bar, uint16_t mask) {
  asm volatile("cp.async.bulk.tensor.2d.shared::cluster.global.mbarrier::complete_tx::bytes.multicast::cluster [%0],[%1,{%3,%4}],[%2],%5;" ::"r"(dst), "l"(tm), "r"(bar), "r"(c0), "r"(c1), "h"(mask) : "memory");
}
DEVI void tma_load3(uint32_t dst, const CUtensorMap* tm, int c1, int c2, uint32_t bar) {
  asm volatile("cp.async.bulk.tensor.3d.shared::cluster.global.mbarrier::complete_tx::bytes [%0],[%1,{0,%3,%4}],[%2];" ::"r"(dst), "l"(tm), "r"(bar), "r"(c1), "r"(c2) : "memory");
}
DEVI void arrive_pair(uint32_t b) { if ((threadIdx.x & 127) < 2) asm volatile("mbarrier.arrive.shared::cluster.b64 _,[%0];" ::"r"(mapa(b, threadIdx.x & 1)) : "memory"); }
DEVI void cluster_sync_relaxed() { asm volatile("barrier.cluster.arrive.relaxed.aligned; barrier.cluster.wait.aligned;" ::: "memory"); }
DEVI void cluster_sync() { asm volatile("barrier.cluster.arrive.aligned; barrier.cluster.wait.aligned;" ::: "memory"); }
DEVI void sts4(uint32_t a, uint32_t x, uint32_t y, uint32_t z, uint32_t w) { asm volatile("st.shared.v4.b32 [%0],{%1,%2,%3,%4};" ::"r"(a), "r"(x), "r"(y), "r"(z), "r"(w) : "memory"); }
DEVI void lds4(uint32_t* r, uint32_t a) { asm volatile("ld.shared.v4.b32 {%0,%1,%2,%3},[%4];" : "=r"(r[0]), "=r"(r[1]), "=r"(r[2]), "=r"(r[3]) : "r"(a) : "memory"); }
DEVI void sta4(uint32_t d, uint32_t a, uint32_t b, uint32_t c, uint32_t e, uint32_t bar) {
  asm volatile("st.async.weak.shared::cluster.mbarrier::complete_tx::bytes.v4.b32 [%0],{%1,%2,%3,%4},[%5];" ::"r"(d), "r"(a), "r"(b), "r"(c), "r"(e), "r"(bar) : "memory");
}
DEVI float blo(uint32_t u) { return __uint_as_float(u << 16); }
DEVI float bhi(uint32_t u) { return __uint_as_float(u & 0xffff0000u); }

#define F8(a, o) "+f"(a[o]), "+f"(a[o + 1]), "+f"(a[o + 2]), "+f"(a[o + 3]), "+f"(a[o + 4]), "+f"(a[o + 5]), "+f"(a[o + 6]), "+f"(a[o + 7])
#define F32(a, o) F8(a, o), F8(a, o + 8), F8(a, o + 16), F8(a, o + 24)
template<int TB> DEVI void wg_ss128(float* d, uint64_t da, uint64_t db, int acc){
 asm volatile("{.reg .pred p; setp.ne.b32 p,%66,0;\n wgmma.mma_async.sync.aligned.m64n128k16.f32.bf16.bf16 {%0,%1,%2,%3,%4,%5,%6,%7,%8,%9,%10,%11,%12,%13,%14,%15,%16,%17,%18,%19,%20,%21,%22,%23,%24,%25,%26,%27,%28,%29,%30,%31,%32,%33,%34,%35,%36,%37,%38,%39,%40,%41,%42,%43,%44,%45,%46,%47,%48,%49,%50,%51,%52,%53,%54,%55,%56,%57,%58,%59,%60,%61,%62,%63},%64,%65,p,1,1,0,%67;}"
 : F32(d,0),F32(d,32) : "l"(da),"l"(db),"r"(acc),"n"(TB));}
template<int TB> DEVI void wg_ss192(float* d, uint64_t da, uint64_t db, int acc){
 asm volatile("{.reg .pred p; setp.ne.b32 p,%98,0;\n wgmma.mma_async.sync.aligned.m64n192k16.f32.bf16.bf16 {%0,%1,%2,%3,%4,%5,%6,%7,%8,%9,%10,%11,%12,%13,%14,%15,%16,%17,%18,%19,%20,%21,%22,%23,%24,%25,%26,%27,%28,%29,%30,%31,%32,%33,%34,%35,%36,%37,%38,%39,%40,%41,%42,%43,%44,%45,%46,%47,%48,%49,%50,%51,%52,%53,%54,%55,%56,%57,%58,%59,%60,%61,%62,%63,%64,%65,%66,%67,%68,%69,%70,%71,%72,%73,%74,%75,%76,%77,%78,%79,%80,%81,%82,%83,%84,%85,%86,%87,%88,%89,%90,%91,%92,%93,%94,%95},%96,%97,p,1,1,0,%99;}"
 : F32(d,0),F32(d,32),F32(d,64) : "l"(da),"l"(db),"r"(acc),"n"(TB));}
template<int TB> DEVI void wg_rs128(float* d, const uint32_t* a, uint64_t db, int acc){
 asm volatile("{.reg .pred p; setp.ne.b32 p,%69,0;\n wgmma.mma_async.sync.aligned.m64n128k16.f32.bf16.bf16 {%0,%1,%2,%3,%4,%5,%6,%7,%8,%9,%10,%11,%12,%13,%14,%15,%16,%17,%18,%19,%20,%21,%22,%23,%24,%25,%26,%27,%28,%29,%30,%31,%32,%33,%34,%35,%36,%37,%38,%39,%40,%41,%42,%43,%44,%45,%46,%47,%48,%49,%50,%51,%52,%53,%54,%55,%56,%57,%58,%59,%60,%61,%62,%63},{%64,%65,%66,%67},%68,p,1,1,%70;}"
 : F32(d,0),F32(d,32) : "r"(a[0]),"r"(a[1]),"r"(a[2]),"r"(a[3]),"l"(db),"r"(acc),"n"(TB));}
DEVI void wg_ss96t(float* d, uint64_t da, uint64_t db, int acc){
 asm volatile("{.reg .pred p; setp.ne.b32 p,%50,0;\n wgmma.mma_async.sync.aligned.m64n96k16.f32.bf16.bf16 {%0,%1,%2,%3,%4,%5,%6,%7,%8,%9,%10,%11,%12,%13,%14,%15,%16,%17,%18,%19,%20,%21,%22,%23,%24,%25,%26,%27,%28,%29,%30,%31,%32,%33,%34,%35,%36,%37,%38,%39,%40,%41,%42,%43,%44,%45,%46,%47},%48,%49,p,1,1,0,1;}"
 : F32(d,0),F8(d,32),F8(d,40) : "l"(da),"l"(db),"r"(acc));}
struct ProjItem { uint8_t pa, m, c0[2], n[2], s0, leave; };
struct ProjParams { CUtensorMap a[2], w[3], c[3]; ProjItem item[48]; };
constexpr int PST = 12, P_STG = PST * 16384, P_FULL = P_STG + 32768 + 256, P_EMPTY = P_FULL + 8 * PST, P_OF = P_EMPTY + 8 * PST, P_OE = P_OF + 16, P_END = P_OE + 16;
DEVI void proj_decode(const ProjItem& I, int t, int& pw, int& n) {
  const int g = t >= I.n[0], c = g ? I.c0[1] + t - I.n[0] : I.c0[0] + t;
  pw = I.pa ? 2 : c >> 4; n = (c & 15) + g * 16;
}
DEVI void proj_init(const ProjItem& I, uint32_t base) {
  for (int i = 0; i < PST; i++) { mbar_init(base + P_FULL + 8 * i, 1); mbar_init(base + P_EMPTY + 8 * i, 4); }
  for (int i = 0; i < 2; i++) { mbar_init(base + P_OF + 8 * i, 4); mbar_init(base + P_OE + 8 * i, 1); }
  mbar_init(base + P_END, 1);
  for (int i = 0; i < I.s0; i++) {
    mbar_arrive(base + P_FULL + 8 * i);
    asm volatile("mbarrier.arrive.shared::cta.b64 _,[%0],4;" ::"r"(base + P_EMPTY + 8 * i) : "memory");
  }
}
DEVI int proj_produce(const ProjParams& P, const ProjItem& I, uint32_t base) {
  const int nk = 8 + I.pa, r = blockIdx.x & 1;
  int s = I.s0, ph = 1;
  for (int t = -1; t < I.n[0] + I.n[1]; t++) {
    int pw, n; proj_decode(I, t, pw, n);
    if (t == I.n[0] + I.n[1] - 1) mbar_arrive(base + P_END);
    for (int k = 0; k < nk; k++) {
      if (t >= 0) mbar_wait(base + P_EMPTY + 8 * s, ph);
      mbar_expect(base + P_FULL + 8 * s, 16384);
      if (t < 0) tma_load(base + s * 16384, &P.a[I.pa], k * 64, (I.m * 2 + r) * 128, base + P_FULL + 8 * s);
      else tma_load_mc(base + s * 16384 + r * 8192, &P.w[pw], n * 128 + r * 64, k * 64, base + P_FULL + 8 * s, 3);
      if (++s == PST) { s = 0; ph ^= 1; }
    }
  }
  return ph;
}
DEVI void proj_store(const ProjParams& P, const ProjItem& I, uint32_t base, int g) {
  const int r0 = (I.m * 2 + (blockIdx.x & 1)) * 128 + g * 64;
  for (int t = 0; t < I.n[0] + I.n[1]; t++) {
    int pw, n; proj_decode(I, t, pw, n);
    mbar_wait(base + P_OF + 8 * g, t & 1);
    tma_store(&P.c[pw], base + P_STG + g * 16384, n * 128, r0);
    tma_store(&P.c[pw], base + P_STG + g * 16384 + 8192, n * 128 + 64, r0);
    bulk_commit();
    bulk_wait_read<0>();
    mbar_arrive(base + P_OE + 8 * g);
    if (t == 3 && !g) CT(0, 1)
    if (t == I.n[0] - 1) { bulk_wait<0>(); signal_after_bulk(S_PROJ + I.pa * (I.m + 1) * 2); }
  }
  bulk_wait<0>(); signal_after_bulk(S_PROJ + I.pa * (I.m + 1) * 2 + 1);
  if (!g) CT(0, 2)
}
DEVI void proj_consume(const ProjItem& I, uint32_t base, int tid, int wg) {
  const uint32_t full = base + P_FULL;
  uint32_t A[36][4];
  float acc[64];
  uint32_t s = I.s0, ph = 0, c = 1;
  const uint32_t row = ((tid >> 5) & 3) * 16 + (tid & 15);
  const uint32_t roff = row * 128 + ((((tid >> 4) & 1) ^ (row & 7)) << 4);
  const uint32_t rel = mapa(base + P_EMPTY, tid & 1);
  auto release = [&](uint32_t st) { asm volatile("{.reg .pred p; setp.lt.u32 p,%1,2; @p mbarrier.arrive.shared::cluster.b64 _,[%0];}" ::"r"(rel + 8 * st), "r"(tid & 127) : "memory"); };
  const int pa = I.pa, nt = I.n[0] + I.n[1];
#pragma unroll
  for (int k = 0; k < 9; k++) {
    if (k < 8 || pa) {
      mbar_wait(full + 8 * s, ph);
#pragma unroll
      for (int kk = 0; kk < 4; kk++) ldsm4(A[4 * k + kk], base + s * 16384 + wg * 8192 + (roff ^ (kk * 32)));
      bar_sync(1 + wg, 128);
      release(s);
      if (++s == PST) { s = 0; ph ^= 1; }
    }
  }
  if (tid == 0) CT(0, 0)
  if (wg) bar_sync(5, 256);
  bool ok = false;
  for (int t = 0; t < nt; t++, c ^= 1) {
    uint32_t p1 = 0;
#pragma unroll
    for (int k = 0; k < 9; k++) {
      if (k < 8 || pa) {
        if (!ok) mbar_wait(full + 8 * s, ph);
        const uint64_t db = desc_mn(base + s * 16384, 8192);
        wg_fence();
#pragma unroll
        for (int kk = 0; kk < 4; kk++) wg_rs128<1>(acc, A[4 * k + kk], db + kk * 128, k | kk);
        wg_commit();
        const uint32_t cur = s;
        if (++s == PST) { s = 0; ph ^= 1; }
        ok = mbar_test(full + 8 * s, ph);
        if (k) { wg_wait<1>(); release(p1); }
        if (k == 4 && t == 0 && !wg) bar_arrive(5, 256);
        p1 = cur;
      }
    }
    mwait(base + P_OE + 8 * wg, c);
    wg_wait<0>();
    release(p1);
#pragma unroll
    for (int i = 0; i < 8; i++) {
      const float* a = acc + i * 8;
      stsm4(base + P_STG + wg * 16384 + (i >> 2) * 8192 + (roff ^ ((i & 3) * 32)), pack2(a[0], a[1]), pack2(a[2], a[3]), pack2(a[4], a[5]), pack2(a[6], a[7]));
    }
    fence_async();
    __syncwarp();
    if ((tid & 31) == 0) mbar_arrive(base + P_OF + 8 * wg);
  }
}

struct OutMaps { CUtensorMap a, b, c; };
template <int NST, bool PAIR, int G> DEVI void out_produce(const OutMaps& M, uint32_t base, uint32_t full, int m, int n, int k0, int nk, int flag) {
  constexpr int SB = 16384 + 384 * G;
  constexpr bool MC = PAIR && G == 64;
  const int r = MC ? blockIdx.x & 1 : 0;
  int s = 0, ph = !PAIR;
#pragma unroll 1
  for (int k = 0; k < nk + (PAIR ? NST - 1 : 0); k++) {
    mbar_wait(full + 8 * (NST + s), ph);
    if (k < nk) {
      mbar_expect(full + 8 * s, SB);
      if (flag >= 0) tma_load3(base + s * SB + 16384, &M.b, (k0 + k) * 64, n * 3, full + 8 * s);
      else
#pragma unroll 1
      for (int j = 0; j < 3; j++) {
        if (MC) tma_load_mc(base + s * SB + 16384 + j * 128 * G + r * 64 * G, &M.b, (n * 3 + j) * G, k * 64 + r * 32, full + 8 * s, 3);
        else tma_load(base + s * SB + 16384 + j * 128 * G, &M.b, (n * 3 + j) * G, (k0 + k) * 64, full + 8 * s);
      }
      if (flag >= 0 && k == 0) flag_wait(flag, 64, 30);
      if (flag >= 0) tma_load(base + s * SB, &M.a, (k0 + k) * 64, m * 128, full + 8 * s);
    }
    if (++s == NST) { s = 0; ph ^= 1; }
  }
}
template <int NST, bool PAIR, int G> DEVI void out_rows(const OutMaps& M, uint32_t base, uint32_t full, int m, int flag, int cnt, int waiters) {
  flag_wait(flag, cnt, waiters);
  int s = 0, ph = !PAIR;
#pragma unroll 1
  for (int k = 0; k < 64; k++) {
    if (k == cnt) mbar_wait(full + 16 * NST, 0);
    mbar_wait(full + 8 * (NST + s), ph);
    if (PAIR && G == 32) tma_load_mc(base + s * (16384 + 384 * G) + (blockIdx.x & 1) * 8192, &M.a, k * 64, m * 128 + (blockIdx.x & 1) * 64, full + 8 * s, 3);
    else tma_load(base + s * (16384 + 384 * G), &M.a, k * 64, m * 128, full + 8 * s);
    if (++s == NST) { s = 0; ph ^= 1; }
  }
}
template <int NST, bool PAIR, int G> DEVI void out_consume(float* acc, uint32_t base, uint32_t full, int nk) {
  constexpr int SB = 16384 + 384 * G;
  const uint32_t empty = full + 8 * NST;
  const int wg = threadIdx.x >> 7;
  int s = 0, ph = 0, prev = 0;
#pragma unroll 1
  for (int k = 0; k < nk; k++) {
    mbar_wait(full + 8 * s, ph);
    const uint64_t da = desc_k(base + s * SB + wg * 8192), db = mkdesc(base + s * SB + 16384, 128 * G, 16 * G, G == 64 ? 1 : 2);
    wg_fence();
#pragma unroll
    for (int kk = 0; kk < 4; kk++) {
      if (G == 64) wg_ss192<1>(acc, da + kk * 2, db + kk * 128, k | kk);
      else wg_ss96t(acc, da + kk * 2, db + kk * 64, k | kk);
    }
    wg_commit();
    if (k) { wg_wait<1>(); if (PAIR) arrive_pair(empty + 8 * prev); else if ((threadIdx.x & 127) == 0) mbar_arrive(empty + 8 * prev); }
    prev = s;
    if (++s == NST) { s = 0; ph ^= 1; }
  }
  wg_wait<0>();
}
template <int NST, bool PAIR, int G> DEVI void out_tile(const OutMaps& M, uint32_t base, uint32_t full, int m, int n) {
  const int tid = threadIdx.x, wg = tid >> 7;
  float acc[G * 3 / 2];
  out_consume<NST, PAIR, G>(acc, base, full, 64);
  bar_sync(6, 256);
  const uint32_t row = ((tid >> 5) & 3) * 16 + (tid & 15);
  const uint32_t roff = row * 2 * G + ((((tid >> 4) & 1) ^ (G == 64 ? row & 7 : (row >> 1) & 3)) << 4);
#pragma unroll
  for (int i = 0; i < G * 3 / 16; i++) {
    const float* a = acc + i * 8;
    stsm4(base + wg * 384 * G + i / (G / 16) * 128 * G + (roff ^ (i % (G / 16) * 32)), pack2(a[0], a[1]), pack2(a[2], a[3]), pack2(a[4], a[5]), pack2(a[6], a[7]));
  }
  fence_async();
  bar_sync(1 + wg, 128);
  if ((tid & 127) == 0) {
#pragma unroll 1
    for (int c = 0; c < 3; c++) tma_store(&M.c, base + wg * 384 * G + c * 128 * G, (n * 3 + c) * G, m * 128 + wg * 64);
    bulk_commit();
    bulk_wait_read<0>();
  }
}
struct OutParams { OutMaps p[2]; int n, odd; uint8_t tile[64]; };
constexpr int SM_O = 6 * 28672 + 256;
__global__ void __launch_bounds__(384, 1) out_kernel(const __grid_constant__ OutParams P) {
  extern __shared__ __align__(1024) uint8_t smem_raw[];
  const uint32_t base = s2u(smem_raw), full = base + 6 * 28672;
  const int tid = threadIdx.x, t = P.tile[blockIdx.x], half = t >> 7, m = (t >> 3) & 15, n = t & 7;
  TL_START(4)
  pdl_trigger();
  if (tid == 0) {
    for (int i = 0; i < 12; i++) mbar_init(full + 8 * i, i >= 4 + 2 * half ? 2 : 1);
    asm volatile("fence.mbarrier_init.release.cluster;" ::: "memory");
  }
  __syncthreads();
  if (tid >= 256) {
    if (tid == 256) { if (half) out_produce<6, false, 32>(P.p[1], base, full, m, n, 0, 64, -1); else out_produce<4, false, 64>(P.p[0], base, full, m, n, 0, 64, -1); }
    if (tid == 288) { if (half) out_rows<6, false, 32>(P.p[1], base, full, m, S_CTXB + m, 64, 4); else out_rows<4, false, 64>(P.p[0], base, full, m, S_CTXB + m, 64, 3 + (m == P.odd)); }
  } else {
    if (tid == 0) CT(4, 0)
    if (half) out_tile<6, false, 32>(P.p[1], base, full, m, n); else out_tile<4, false, 64>(P.p[0], base, full, m, n);
    if (tid == 0) CT(4, 2)
    TL_END(4)
  }
}
struct FaParams { ProjParams p; CUtensorMap q, k, v, o; unsigned proj, nctas, ngroups; uint8_t nproj[12]; uint16_t order[512];
                  OutMaps om[3]; uint16_t tile[96]; };
constexpr int HST = 5, F_OUT = 7 * 32768 + 512, F_OUTH = F_OUT + 72, F_TILE = F_OUTH + 16 * HST, SM_F = F_OUT + 256;
constexpr float FA_C = 0.08838834764831845f * 1.4426950408889634f;
DEVI int fa_qt(int w) { return w >> 5; }
DEVI int fa_hc(int w) { return (w & 31) * 128; }

DEVI void fa_exp(const float* S, uint32_t* Pn, float mc0, float mc1, float& s0, float& s1) {
  float a0 = 0.f, a1 = 0.f, b0 = 0.f, b1 = 0.f;
#pragma unroll
  for (int j = 0; j < 16; j++) {
    const float e0 = ex2(fmaf(S[4 * j], FA_C, -mc0)), e1 = ex2(fmaf(S[4 * j + 1], FA_C, -mc0));
    const float e2 = ex2(fmaf(S[4 * j + 2], FA_C, -mc1)), e3 = ex2(fmaf(S[4 * j + 3], FA_C, -mc1));
    a0 += e0; a1 += e1; b0 += e2; b1 += e3;
    Pn[2 * j] = pack2(e0, e1); Pn[2 * j + 1] = pack2(e2, e3);
  }
  s0 = a0 + a1; s1 = b0 + b1;
}

struct FaState { float mc0, mc1, l0, l1; int w, j, qi; uint32_t dq; bool first; };
enum { F_Q = 0, F_K = 2 * 32768, F_V = 4 * 32768, F_O = 6 * 32768, F_QF = 7 * 32768, F_QE = F_QF + 16, F_KF = F_QF + 32, F_KE = F_QF + 48, F_VF = F_QF + 64, F_VE = F_QF + 80,
       F_OF = F_QF + 96, F_OE = F_QF + 112, F_INFO = F_QF + 128 };

DEVI void out_open(uint32_t base, int tid, uint32_t mask) {
  const int s = (tid & 127) >> 1;
  if (s < 4 + HST && ((mask >> s) & 1))
    asm volatile("mbarrier.arrive.shared::cluster.b64 _,[%0];" ::"r"(mapa(base + (s < 4 ? F_OUT + 32 : F_OUTH + 8 * HST - 32) + 8 * s, tid & 1)) : "memory");
}
template <int SC> DEVI bool fa_step(FaState& T, float* O, float* S, const uint32_t* Pc, uint32_t* Pn, uint32_t base, int tid, int wg, uint32_t ph) {
  const bool el = (tid & 127) == 0, fin = T.j == 0;
  int wn = T.w, jn = T.j - 1;
  const bool okk = mbar_try(base + F_KF + 8 * (SC ^ 1), ph), okv = mbar_try(base + F_VF + 8 * SC, ph ^ SC);
  if (fin) {
    T.qi++; T.dq ^= 2048;
    mbar_wait(base + F_QF + 8 * (T.qi & 1), (T.qi >> 1) & 1);
    asm volatile("ld.shared.b32 %0,[%1];" : "=r"(wn) : "r"(base + F_INFO + (T.qi & 1) * 4) : "memory");
    wn = __shfl_sync(~0u, wn, 0);
    jn = fa_qt(wn);
    if (wn < 0) out_open(base, tid, 0xf7);
  }
  if (!(okk && okv)) { mbar_wait(base + F_KF + 8 * (SC ^ 1), ph); mbar_wait(base + F_VF + 8 * SC, ph ^ SC); }
  const bool last = wn < 0;
  {
    const uint64_t dq = desc_k(0) | T.dq, dk = desc_k(base + F_K + (SC ^ 1) * 32768), dv = desc_mn(base + F_V + SC * 32768, 16384);
    bar_sync(3 + wg, 256);
    wg_fence();
#pragma unroll
    for (int kk = 0; kk < 8; kk++) wg_ss128<0>(S, dq + (kk & 3) * 2 + (kk >> 2) * 1024, dk + (kk & 3) * 2 + (kk >> 2) * 1024, kk);
    wg_commit();
#pragma unroll
    for (int kk = 0; kk < 8; kk++) wg_rs128<1>(O, Pc + 4 * kk, dv + kk * 128, kk || !T.first);
    wg_commit();
    bar_arrive(4 - wg, 256);
  }
  wg_wait<1>();
  asm volatile("{.reg .pred p,q; setp.ne.u32 p,%0,0; setp.eq.and.u32 q,%1,0,p; @p mbarrier.arrive.shared::cta.b64 _,[%2]; @q mbarrier.arrive.shared::cta.b64 _,[%3];}"
               ::"r"((uint32_t)el), "r"(jn), "r"(base + F_KE + 8 * (SC ^ 1)), "r"(base + F_QE + 8 * (T.qi & 1)) : "memory");
  const float lp0 = T.l0, lp1 = T.l1;
  float s0 = 0.f, s1 = 0.f, f0 = 1.f, f1 = 1.f;
  bool exact = fin;
  if (!fin) {
    fa_exp(S, Pn, T.mc0, T.mc1, s0, s1);
    exact = __any_sync(~0u, !(fmaxf(s0, s1) <= 1073741824.f));
  }
  if (exact && !last) {
    float a = -INFINITY, b = -INFINITY;
    if (fin) {
      const int row = (tid >> 5) * 16 + ((tid & 31) >> 2) - (tid & 3) * 2;
#pragma unroll
      for (int j = 0; j < 16; j++) {
        if (j * 8 > row) S[4 * j] = -INFINITY;
        if (j * 8 + 1 > row) S[4 * j + 1] = -INFINITY;
        if (j * 8 > row + 8) S[4 * j + 2] = -INFINITY;
        if (j * 8 + 1 > row + 8) S[4 * j + 3] = -INFINITY;
      }
      T.mc0 = T.mc1 = -INFINITY;
    }
#pragma unroll
    for (int j = 0; j < 16; j++) { a = fmaxf(a, fmaxf(S[4 * j], S[4 * j + 1])); b = fmaxf(b, fmaxf(S[4 * j + 2], S[4 * j + 3])); }
    a = fmaxf(a, __shfl_xor_sync(~0u, a, 1)); b = fmaxf(b, __shfl_xor_sync(~0u, b, 1));
    a = fmaxf(a, __shfl_xor_sync(~0u, a, 2)); b = fmaxf(b, __shfl_xor_sync(~0u, b, 2));
    a = fmaxf(a * FA_C, T.mc0); b = fmaxf(b * FA_C, T.mc1);
    f0 = ex2(T.mc0 - a); f1 = ex2(T.mc1 - b);
    T.mc0 = a; T.mc1 = b;
    T.l0 = fin ? 0.f : T.l0 * f0; T.l1 = fin ? 0.f : T.l1 * f1;
    fa_exp(S, Pn, a, b, s0, s1);
  }
  T.l0 += s0; T.l1 += s1;
  wg_wait<0>();
  if (el) mbar_arrive(base + F_VE + 8 * SC);
  if (exact) {
    if (fin) {
      f0 = lp0 + __shfl_xor_sync(~0u, lp0, 1); f1 = lp1 + __shfl_xor_sync(~0u, lp1, 1);
      f0 += __shfl_xor_sync(~0u, f0, 2); f1 += __shfl_xor_sync(~0u, f1, 2);
      f0 = 1.f / f0; f1 = 1.f / f1;
    }
#pragma unroll
    for (int i = 0; i < 16; i++) { O[4 * i] *= f0; O[4 * i + 1] *= f0; O[4 * i + 2] *= f1; O[4 * i + 3] *= f1; }
    if (fin && (T.qi || last)) {
      const uint32_t row = ((tid >> 5) & 3) * 16 + (tid & 15);
      const uint32_t o = base + F_O + wg * 16384 + row * 128 + ((((tid >> 4) & 1) ^ (row & 7)) << 4);
      if (T.qi) mbar_wait(base + F_OE + 8 * wg, (T.qi & 1) ^ 1);
#pragma unroll
      for (int i = 0; i < 8; i++) {
        const float* a = O + i * 8;
        stsm4((o ^ ((i & 3) * 32)) + (i >> 2) * 8192, pack2(a[0], a[1]), pack2(a[2], a[3]), pack2(a[4], a[5]), pack2(a[6], a[7]));
      }
      if (el) asm volatile("st.shared.b32 [%0],%1;" ::"r"(base + F_INFO + 8 + wg * 4), "r"(!T.qi ? -1 : T.w | (last ? 1024 : 0)) : "memory");
      fence_async();
      __syncwarp();
      if ((tid & 31) == 0) mbar_arrive(base + F_OF + 8 * wg);
    }
  }
  T.w = wn; T.j = jn; T.first = fin;
  return last;
}

__global__ void __launch_bounds__(384, 1) fa_kernel(const __grid_constant__ FaParams P) {
  extern __shared__ __align__(1024) uint8_t smem_raw[];
  const uint32_t base = __shfl_sync(~0u, s2u(smem_raw), 0);
  const uint32_t sQ = base, sK = base + 2 * 32768, sV = base + 4 * 32768, sO = base + 6 * 32768, bars = base + 7 * 32768;
  const uint32_t qf = bars, qe = bars + 16, kf = bars + 32, ke = bars + 48, vf = bars + 64, ve = bars + 80, of = bars + 96, oe = bars + 112;
  volatile int* info = (volatile int*)(smem_raw + 7 * 32768 + 128);
  const int tid = threadIdx.x, wg = tid >> 7;
  const ProjItem& I = P.p.item[blockIdx.x >> 1];
  const bool leave = P.proj && I.leave;
  auto my_tile = [&]() { mbar_wait(base + F_TILE, 0); return info[5]; };
  pdl_trigger();
  if (tid == 0) {
    if (P.proj) proj_init(I, base);
    for (int i = 0; i < 16; i++) mbar_init(bars + 8 * i, i >= 14 ? 1 : i >= 12 ? 4 : (i & 2) ? 2 : 1);
    for (int i = 0; i < 10 + 2 * HST; i++) mbar_init(base + F_OUT + 8 * i, (i >= 4 && i < 8) || (i >= 9 + HST && i < 9 + 2 * HST) ? 4 : 1);
    mbar_expect(base + F_TILE, 4);
    info[4] = 0;
    asm volatile("fence.mbarrier_init.release.cluster;" ::: "memory");
  }
  __syncthreads();
  cluster_sync_relaxed();
  if (wg == 2) {
    reg_dec<24>();
    if (tid == 256) {
      int it = 0, qi = 0, vc = 0, vr = -1, j = 0, hc = 0;
      int pph = P.proj ? proj_produce(P.p, I, base) : -1;
      auto drain = [&](int s0) { if (pph >= 0) for (int i = s0; i < s0 + 6; i++) mbar_wait(base + P_EMPTY + 8 * i, pph); };
      if (leave) { drain(0); drain(6); return; }
      CT(P.proj ? 3 : 6, 0)
      auto load_v = [&]() {
        if (vr < 0) return;
        const int s = (it - 1) & 1;
        drain(6); pph = -1;
        mbar_wait(ve + 8 * s, (((it - 1) >> 1) & 1) ^ 1 ^ s);
        mbar_expect(vf + 8 * s, 32768);
        tma_load(sV + s * 32768, &P.v, vc, vr, vf + 8 * s);
        tma_load(sV + s * 32768 + 16384, &P.v, vc + 64, vr, vf + 8 * s);
        vr = -1;
      };
      auto ready = [&](uint32_t m) { uint32_t v; asm volatile("ld.acquire.cta.shared.b32 %0,[%1];" : "=r"(v) : "r"(base + F_INFO + 16) : "memory"); return (v & m) == m; };
      for (it = -1;; it++) {
        if (it >= 0) {
          const int s = it & 1;
          if (it || j < 0) { drain(6); pph = -1; }
          mbar_wait(ke + 8 * s, ((it >> 1) & 1) ^ 1);
          if (j < 0) { mbar_arrive(kf + 8 * s); load_v(); break; }
          mbar_expect(kf + 8 * s, 32768);
          tma_load(sK + s * 32768, &P.k, hc, j * 128, kf + 8 * s);
          tma_load(sK + s * 32768 + 16384, &P.k, hc + 64, j * 128, kf + 8 * s);
        }
        int nc = hc, nr = it >= 0 ? j * 128 : -1;
        if (j-- == 0) {
          int w = atomicInc(&g_sync[S_QUEUE], 511 + P.nctas);
          w = w < 512 ? P.order[w] : -1;
          const uint32_t q = qi & 1, m = w < 0 ? 0x3ffff : (1u | (2u << (fa_qt(w) | 1))) << ((w >> 4) & 1);
          if (!ready(m) || !mbar_test(qe + 8 * q, ((qi >> 1) & 1) ^ 1)) {
            load_v(); it++; vc = nc; vr = nr; load_v(); it--; nr = -1;
            for (int n = 0; !ready(m) && n < WAIT_MAX; n++) __nanosleep(64);
            mbar_wait(qe + 8 * q, ((qi >> 1) & 1) ^ 1);
          }
          asm volatile("fence.proxy.async.global;" ::: "memory");
          if (it < 0) drain(0);
          info[q] = w;
          if (w < 0) mbar_arrive(qf + 8 * q);
          else {
            j = fa_qt(w); hc = fa_hc(w);
            mbar_expect(qf + 8 * q, 32768);
            tma_load(sQ + q * 32768, &P.q, hc, j * 128, qf + 8 * q);
            tma_load(sQ + q * 32768 + 16384, &P.q, hc + 64, j * 128, qf + 8 * q);
          }
          qi++;
        }
        load_v();
        vc = nc; vr = nr;
      }
      const int tile = my_tile(), kind = tile >> 7, tm = (tile >> 3) & 15, tn = tile & 7;
      if (atomicInc(&g_sync[S_EXIT], P.nctas - 1) == P.nctas - 1) {
#pragma unroll 1
        for (int i = S_LIST; i < S_PROJ + 18; i++) g_sync[i] = 0;
#pragma unroll 1
        for (int i = 0; i < 16; i++) ((uint4*)g_group)[i] = make_uint4(0, 0, 0, 0);
      }
      if (kind == 2) out_produce<HST, true, 32>(P.om[2], base, base + F_OUTH, tm, tn, 0, 64, -1);
      else if (kind < 2) out_produce<4, true, 64>(P.om[kind], base, base + F_OUT, tm, tn, 0, 64, -1);
      else { mbar_wait(base + F_OUT + 56, 0); mbar_wait(base + F_TILE - 8, 0); }
    } else if (tid >= 352) {
      const int l = tid - 352;
      if (P.proj) mbar_wait(base + P_END, 0);
#pragma unroll 1
      for (int n = 0; n < WAIT_MAX && !leave; n++) {
        unsigned v = 255;
        if (l < 18) asm volatile("ld.acquire.gpu.global.u32 %0, [%1];" : "=r"(v) : "l"(g_sync + S_PROJ + l) : "memory");
        const uint32_t m = __ballot_sync(~0u, v >= P.nproj[(l >> 1) % 9]);
        __syncwarp();
        if (l == 0) asm volatile("st.release.cta.shared.b32 [%0],%1;" ::"r"(base + F_INFO + 16), "r"(m) : "memory");
        if (m == ~0u) break;
        __nanosleep(300);
      }
      if (l == 0 && !(blockIdx.x & 1) && !leave) {
        unsigned sm; asm("mov.u32 %0,%%smid;" : "=r"(sm));
        unsigned g = *(volatile uint8_t*)&g_group[sm & 255] - 1u, i;
        if (g > P.ngroups) g = P.ngroups;
        while ((i = g * 8 + atomicAdd(&g_sync[S_LIST + g], 1)) >= (g < P.ngroups ? g * 8 + 8 : P.nctas / 2)) g = g ? g - 1 : P.ngroups;
        for (int r = 0; r < 2; r++)
          asm volatile("st.async.weak.shared::cluster.mbarrier::complete_tx::bytes.b32 [%0],%1,[%2];" ::"r"(mapa(base + F_INFO + 20, r)), "r"((int)P.tile[i * 2 + r]), "r"(mapa(base + F_TILE, r)) : "memory");
      }
      if (l == 0 && !leave) {
        const int tile = my_tile(), kind = tile >> 7, tm = (tile >> 3) & 15;
        mbar_wait(base + (kind == 2 ? F_OUTH + 8 * HST : F_OUT + 32), 0);
        if (kind == 2) out_rows<HST, true, 32>(P.om[2], base, base + F_OUTH, tm, S_CTXB + tm, 64, 6);
        else if (kind < 2) out_rows<4, true, 64>(P.om[kind], base, base + F_OUT, tm, (kind ? S_CTXB : S_CTXA) + tm, kind ? 64 : 32, 3);
      }
    } else if (tid == 288 || tid == 320) {
      const int g = tid == 320;
      if (P.proj) proj_store(P.p, I, base, g);
      if (leave) return;
      mbar_arrive(oe + 8 * g);
        for (int n = 0;; n++) {
          mbar_wait(of + 8 * g, n & 1);
          const int v = info[2 + g], w = v & 1023, qt = fa_qt(w), hc = fa_hc(w);
          if (v < 0) break;
          tma_store(&P.o, sO + g * 16384, hc, qt * 128 + g * 64);
          tma_store(&P.o, sO + g * 16384 + 8192, hc + 64, qt * 128 + g * 64);
          bulk_commit();
          bulk_wait_read<0>();
          mbar_arrive(oe + 8 * g);
          bulk_wait<0>();
          signal_after_bulk(S_CTXA + (w & 16) + qt);
          if (v & 1024) break;
        }
      if (!g && my_tile() < 128) { flag_wait(S_CTXA + 16 + (info[5] >> 3), 32, 3); mbar_arrive(base + F_OUT + 64); }
    }
  } else {
    reg_inc<240>();
    const uint32_t ub = base;
    const int uw = __shfl_sync(~0u, wg, 0);
    if (wg == 1 && !leave) bar_arrive(3, 256);
    if (P.proj) proj_consume(I, ub, tid, uw);
    if (leave) return;
    float O[64], S[64];
    uint32_t PA[32], PB[32];
#pragma unroll
    for (int i = 0; i < 32; i++) PA[i] = 0;
#pragma unroll
    for (int i = 0; i < 64; i++) O[i] = 0.f;
    FaState T = {0.f, 0.f, 1.f, 1.f, 0, 0, -1, ((ub + 32768 + uw * 8192) >> 4) & 0x3fff, true};
    for (uint32_t ph = 0;; ph ^= 1) {
      if (fa_step<1>(T, O, S, PA, PB, ub, tid, uw, ph)) break;
      if (fa_step<0>(T, O, S, PB, PA, ub, tid, uw, ph)) break;
    }
    if (wg == 0) bar_sync(3, 256);
    out_open(ub, tid, ~0xf7u);
    const int tile = __shfl_sync(~0u, my_tile(), 0), kind = tile >> 7, tm = (tile >> 3) & 15, tn = tile & 7;
    if (tid == 0) CT(P.proj ? 5 : 2, 0)
    TL_START(5)
    if (kind == 2) out_tile<HST, true, 32>(P.om[2], ub, ub + F_OUTH, tm, tn);
    else if (kind < 2) out_tile<4, true, 64>(P.om[kind], ub, ub + F_OUT, tm, tn);
    if (tid == 0) CT(P.proj ? 5 : 2, 2)
    TL_END(kind == 2 ? 2 : 5)
  }
}
#define PS 20
#define PT(i)
#define YD 200
#define NPF 4
#define NRES 6
#define RP 208
#define PD 2
#define VR "............rrrrrr.................."
#define VP "222222222222111111111111------------"
constexpr int vr_index(int k) { int n = 0; for (int i = 0; i < k; i++) n += VR[i] == 'r'; return n; }
constexpr int VB = vr_index(36);
template <int K> struct VIdx { static constexpr int v = vr_index(K); static constexpr char r = VR[K], p = VP[K]; };
#define XG 6
#define XW 2
#define WOD 4000
#define KA 26
constexpr int R_WV = 0, R_WO = 73728, R_H = 147456, R_OX = R_H + 46080, R_Q = R_OX + 4096, R_K = R_Q + 5120, R_SX = R_K + 5120, R_P = R_SX + 3200, R_U = R_P + 3200,
              R_BAR = R_H + 73728, R_PROF = R_BAR + 256, R_END = R_PROF + 3072;
constexpr int B_W0 = R_BAR, B_W1 = R_BAR + 8, B_XA = R_BAR + 16, B_XB = R_BAR + 24, B_XF = R_BAR + 32, B_Z0 = R_BAR + 40, B_Z1 = R_BAR + 48, B_R = R_BAR + 56,
              B_SM = R_BAR + 64, B_SX = R_BAR + 72, B_U = R_BAR + 80, B_V = R_BAR + 88, B_W2 = R_BAR + 96, B_W3 = R_BAR + 104, B_O = R_BAR + 112;
static_assert(R_U + 4096 <= R_BAR, "");
enum { N_P1 = 1, N_PM, N_PX, N_SUM, N_O, N_INIT, N_INIT1, N_INIT2, N_WO, N_S };
constexpr int YSLOT = 9 * 16 * 1024;
struct RecParams { CUtensorMap wq, wk, wv, wo, x, ctx; OutMaps o; const bf16 *mem0, *x_raw; bf16* out; };
constexpr int TAIL0 = 14;
constexpr int TST = 6, R_RED = TST * 28672;

DEVI void wg_rs32(float* d, const uint32_t* a, uint64_t db, int acc) {
  asm volatile("{.reg .pred p; setp.ne.b32 p,%21,0;\n wgmma.mma_async.sync.aligned.m64n32k16.f32.bf16.bf16 {%0,%1,%2,%3,%4,%5,%6,%7,%8,%9,%10,%11,%12,%13,%14,%15},{%16,%17,%18,%19},%20,p,1,1,0;}"
               : F8(d, 0), F8(d, 8) : "r"(a[0]), "r"(a[1]), "r"(a[2]), "r"(a[3]), "l"(db), "r"(acc));
}
DEVI void wg_rs40(float* d, const uint32_t* a, uint64_t db, int acc) {
  asm volatile("{.reg .pred p; setp.ne.b32 p,%25,0;\n wgmma.mma_async.sync.aligned.m64n40k16.f32.bf16.bf16 {%0,%1,%2,%3,%4,%5,%6,%7,%8,%9,%10,%11,%12,%13,%14,%15,%16,%17,%18,%19},{%20,%21,%22,%23},%24,p,1,1,0;}"
               : F8(d, 0), F8(d, 8), "+f"(d[16]), "+f"(d[17]), "+f"(d[18]), "+f"(d[19]) : "r"(a[0]), "r"(a[1]), "r"(a[2]), "r"(a[3]), "l"(db), "r"(acc));
}
template <int TB> DEVI void wg_ss40(float* d, uint64_t da, uint64_t db, int acc) {
  asm volatile("{.reg .pred p; setp.ne.b32 p,%22,0;\n wgmma.mma_async.sync.aligned.m64n40k16.f32.bf16.bf16 {%0,%1,%2,%3,%4,%5,%6,%7,%8,%9,%10,%11,%12,%13,%14,%15,%16,%17,%18,%19},%20,%21,p,1,1,1,%23;}"
               : F8(d, 0), F8(d, 8), "+f"(d[16]), "+f"(d[17]), "+f"(d[18]), "+f"(d[19]) : "l"(da), "l"(db), "r"(acc), "n"(TB));
}
DEVI void mma8(float* d, uint32_t a0, uint32_t a1, uint32_t b0) {
  asm volatile("mma.sync.aligned.m16n8k8.row.col.f32.bf16.bf16.f32 {%0,%1,%2,%3},{%4,%5},{%6},{%0,%1,%2,%3};" : "+f"(d[0]), "+f"(d[1]), "+f"(d[2]), "+f"(d[3]) : "r"(a0), "r"(a1), "r"(b0));
}
DEVI void stsm4t(uint32_t a, uint32_t r0, uint32_t r1, uint32_t r2, uint32_t r3) {
  asm volatile("stmatrix.sync.aligned.m8n8.x4.trans.shared.b16 [%0],{%1,%2,%3,%4};" ::"r"(a), "r"(r0), "r"(r1), "r"(r2), "r"(r3) : "memory");
}
DEVI uint32_t movm(uint32_t a) { uint32_t d; asm volatile("movmatrix.sync.aligned.m8n8.trans.b16 %0,%1;" : "=r"(d) : "r"(a)); return d; }
DEVI void sts1(uint32_t a, uint32_t v) { asm volatile("st.shared.b32 [%0],%1;" ::"r"(a), "r"(v) : "memory"); }
DEVI uint32_t lds1(uint32_t a) { uint32_t v; asm volatile("ld.shared.b32 %0,[%1];" : "=r"(v) : "r"(a) : "memory"); return v; }
DEVI void sta1(uint32_t d, uint32_t a, uint32_t bar) { asm volatile("st.async.weak.shared::cluster.mbarrier::complete_tx::bytes.b32 [%0],%1,[%2];" ::"r"(d), "r"(a), "r"(bar) : "memory"); }
DEVI void sta2(uint32_t d, uint32_t a, uint32_t b, uint32_t bar) { asm volatile("st.async.weak.shared::cluster.mbarrier::complete_tx::bytes.v2.b32 [%0],{%1,%2},[%3];" ::"r"(d), "r"(a), "r"(b), "r"(bar) : "memory"); }
DEVI uint32_t clk32() { uint64_t c; asm volatile("mov.u64 %0,%%clock64;" : "=l"(c)::"memory"); return (uint32_t)c; }
DEVI int opq(int x) { asm volatile("" : "+r"(x)); return x; }
DEVI int pin(int x) { return __shfl_sync(~0u, x, threadIdx.x & 31); }
DEVI void x_load(const RecParams& P, uint32_t sb, int c, int seg) {
  asm volatile("cp.async.bulk.tensor.2d.shared::cluster.global.mbarrier::complete_tx::bytes.multicast::cluster [%0],[%1,{%3,%4}],[%2],%5;"
               ::"r"(sb + R_H + c * 5120 + 1024), "l"(&P.x), "r"(sb + (c < XG ? B_XA : B_XB)), "r"(c * 64), "r"(seg * 32), "h"((uint16_t)0xffff) : "memory");
  if (seg + 2 < NSEG) asm volatile("cp.async.bulk.prefetch.tensor.2d.L2.global [%0,{%1,%2}];" ::"l"(&P.x), "r"(c * 64), "r"(seg * 32 + 64) : "memory");
}
DEVI uint32_t hadd2(uint32_t a, uint32_t b) { uint32_t r; asm("add.rn.bf16x2 %0,%1,%2;" : "=r"(r) : "r"(a), "r"(b)); return r; }
DEVI uint32_t hmax2(uint32_t a, uint32_t b) { uint32_t r; asm("max.bf16x2 %0,%1,%2;" : "=r"(r) : "r"(a), "r"(b)); return r; }
DEVI float rcp(float x) { float y; asm("rcp.approx.ftz.f32 %0,%1;" : "=f"(y) : "f"(x)); return y; }
constexpr float SCL = 0.08838834764831845f * 1.4426950408889634f;

DEVI void y_store(const float* a, uint32_t off, int s) {
  const uint32_t x = movm(pack2(a[0], a[1])), y = movm(pack2(a[2], a[3]));
  const uint32_t tag = ((s >> 1) & 1) ^ 1;
  asm volatile("st.relaxed.gpu.global.b64 [%0],%1;" ::"l"((uint8_t*)g_Y + (s & 1) * YSLOT + off), "l"((uint64_t)((x & ~1u) | tag) | ((uint64_t)y << 32)) : "memory");
}
DEVI void y_load(uint32_t* w, const uint8_t* p) {
#pragma unroll
  for (int i = 0; i < 4; i++) asm volatile("{.reg .b64 t; ld.relaxed.gpu.global.b64 t,[%2]; mov.b64 {%0,%1},t;}" : "=r"(w[2 * i]), "=r"(w[2 * i + 1]) : "l"(p + i * 256) : "memory");
}
DEVI bool y_missing(const uint32_t* w, uint32_t tag) {
  uint32_t r;
  asm volatile("{.reg .b32 a,b; .reg .pred p; lop3.b32 a,%1,%2,%5,0x7e; lop3.b32 b,%3,%4,%5,0x7e; lop3.b32 a,a,b,1,0xa8; setp.ne.u32 p,a,0; vote.sync.any.pred p,p,0xffffffff; selp.u32 %0,1,0,p;}"
               : "=r"(r) : "r"(w[0]), "r"(w[2]), "r"(w[4]), "r"(w[6]), "r"(tag));
  return r;
}
DEVI void y_reload(uint32_t* w, const uint8_t* p, uint32_t tag) {
#pragma unroll
  for (int i = 0; i < 4; i++)
    asm volatile("{.reg .b64 t; .reg .b32 a; .reg .pred q; lop3.b32 a,%0,%3,1,0x28; setp.ne.u32 q,a,0; mov.b64 t,{%0,%1}; @q ld.relaxed.gpu.global.b64 t,[%2]; mov.b64 {%0,%1},t;}"
                 : "+r"(w[2 * i]), "+r"(w[2 * i + 1]) : "l"(p + i * 256), "r"(tag) : "memory");
}
DEVI void y_sum(uint32_t* r, const uint32_t* w, uint32_t sel) {
  float d0[4] = {0, 0, 0, 0}, d1[4] = {0, 0, 0, 0};
  mma16(d0, w[0], w[1], w[2], w[3], sel, sel); mma16(d1, w[4], w[5], w[6], w[7], sel, sel);
  r[0] = pack2(d0[0] + d1[0], d0[1] + d1[1]); r[1] = pack2(d0[2] + d1[2], d0[3] + d1[3]);
}
DEVI void y_send(const uint32_t* r, uint32_t sb, uint32_t dst, uint32_t bar, int lane) {
#pragma unroll
  for (int i = 0; i < 4; i++) { const uint32_t rs = mapa(sb, (lane & 3) + i * 4); sta2(rs + dst, r[0], r[1], rs + bar); }
}
DEVI void wo_convert(uint32_t sb, int lane) {
  TL_END(11)
  mbar_wait(sb + B_W3, 0);
  TL_END(9)
#pragma unroll 1
  for (uint32_t a = sb + R_WO + ((threadIdx.x >> 5) & 3) * 4608, i = 0; i < 4; i++, a += 18432) {
    uint32_t r[9][4];
#pragma unroll
    for (int k = 0; k < 9; k++) ldsm4t(r[k], a + k * 32 + ((lane & 7) + (lane >> 4) * 8) * 288 + ((lane >> 3) & 1) * 16);
    __syncwarp();
#pragma unroll
    for (int k = 0; k < 9; k++) stsm4(a + k * 512 + ((lane >> 4) * 2 + ((lane >> 1) & 1)) * 128 + (((lane >> 2) & 3) * 2 + (lane & 1)) * 16, r[k][0], r[k][1], r[k][2], r[k][3]);
  }
  __syncwarp();
}
DEVI uint32_t y_offset(int cta, int tile, int lane) {
  const int T = (cta & 3) * 9 + tile;
  return (((T >> 2) * 8 + (lane >> 2)) * 2 + ((T >> 1) & 1)) * 1024 + (cta >> 4) * 256 + (T & 1) * 128 + ((cta >> 2) & 3) * 32 + (lane & 3) * 8;
}
template <int NR, int NP> DEVI void wo_tile(const uint32_t (*A0)[4], uint32_t sb, int tile, int lane, uint32_t yo, int s) {
  uint32_t u[8][4], A[16][4];
  const uint32_t wa = sb + R_WO + tile * 512 + lane * 16, ua = sb + R_U + lane * 16;
  float a[4] = {0, 0, 0, 0}, b[4] = {0, 0, 0, 0};
  auto fetch = [&](int i) { if (i < 16 - NR) ldsm4(A[i], wa + i * 4608); };
  auto uload = [&](int i) { if (i < 8) ldsm4t(u[i], ua + i * 512); };
#pragma unroll
  for (int i = 0; i < NP; i++) fetch(i);
  mwait(sb + B_V, s & 1);
  PT(6)
  uload(0); uload(1);
#pragma unroll
  for (int i = 0; i < 16; i++) {
    if (i == 4) {
      mwait(sb + B_U, s & 1);
      PT(7)
      uload(2); uload(3);
    }
    const uint32_t* f = i >= 16 - NR ? A0[i >= 16 - NR ? i - 16 + NR : 0] : A[i];
    mma16(i & 1 ? b : a, f[0], f[1], f[2], f[3], u[i >> 1][(i & 1) * 2], u[i >> 1][(i & 1) * 2 + 1]);
    fetch(i + NP);
    if (i >= 4 && (i & 1)) uload((i >> 1) + 2);
  }
#pragma unroll
  for (int i = 0; i < 4; i++) a[i] += b[i];
  y_store(a, yo, s);
}
template <bool X> DEVI void softmax8(const uint32_t* h, uint32_t a4, uint32_t a1) {
  uint32_t y[5];
  lds4(y, a4 + R_SX);
  y[4] = lds1(a1 + R_SX);
#pragma unroll
  for (int j = 0; j < 5; j++) y[j] = hadd2(h[j], y[j]);
  const uint32_t m2 = hmax2(hmax2(hmax2(y[0], y[1]), hmax2(y[2], y[3])), y[4]);
  const float mc = fmaxf(blo(m2), bhi(m2)) * SCL;
  const float m1 = __shfl_xor_sync(~0u, mc, 1), m3 = __shfl_xor_sync(~0u, mc, 2), m4 = __shfl_xor_sync(~0u, mc, 3);
  float e[10];
#pragma unroll
  for (int j = 0; j < 5; j++) { e[2 * j] = ex2(fmaf(blo(y[j]), SCL, -mc)); e[2 * j + 1] = ex2(fmaf(bhi(y[j]), SCL, -mc)); }
  const float c = ex2(mc - fmaxf(fmaxf(mc, m1), fmaxf(m3, m4)));
  const float l = c * ((((e[0] + e[1]) + (e[2] + e[3])) + ((e[4] + e[5]) + (e[6] + e[7]))) + (e[8] + e[9]));
  const float r = c * rcp((l + __shfl_xor_sync(~0u, l, 1)) + (__shfl_xor_sync(~0u, l, 2) + __shfl_xor_sync(~0u, l, 3)));
#pragma unroll
  for (int j = 0; j < 5; j++) y[j] = pack2(e[2 * j] * r, e[2 * j + 1] * r);
  if (!X) sts4(a4 + R_P, y[0], y[1], y[2], y[3]);
  else stsm4(a4 + R_P, y[0], y[1], y[2], y[3]);
  sts1(a1 + R_P, y[4]);
  if (X) fence_async();
}

DEVI void arm_step(uint32_t sb, int s) {
  mbar_expect(sb + B_SM, 640); mbar_expect(sb + B_SX, 2560);
  if (s < NSEG - 1) {
    mbar_expect(sb + B_U, 3072); mbar_expect(sb + B_Z0, 4096); mbar_expect(sb + B_Z1, 5120);
    mbar_expect(sb + B_XA, XG * 4096); mbar_expect(sb + B_XB, (9 - XG) * 4096);
  }
}
DEVI void rec_proj(const RecParams& P, const uint32_t sb, const int cta) {
  uint32_t W[36][4], A0[NRES ? NRES : 1][4];
  const int tid = pin(threadIdx.x);
  const uint32_t yo = pin(y_offset(cta, threadIdx.x >> 5, threadIdx.x & 31));
  const int warp = __shfl_sync(~0u, threadIdx.x >> 5, 0), role = warp >> 2;
  const uint32_t qk = sb + R_Q + warp * 1280;
  {
    const int lane = threadIdx.x & 31, w4 = (threadIdx.x >> 5) & 3;
    const uint32_t a = sb + role * R_H + ((lane & 7) + (lane >> 4) * 8) * 128 + (((w4 * 2 + ((lane >> 3) & 1)) ^ (lane & 7)) << 4);
    mbar_wait(sb + B_W0 + role * 8, 0);
    TL_END(8)
#pragma unroll
    for (int k = 0; k < 36; k++) ldsm4t(W[k], a + k * 2048);
    if (role) bar_arrive(N_INIT1, 256); else bar_sync(N_INIT, 128);
    cluster_sync_relaxed();
#pragma unroll
    for (int i = 0; i < NRES; i++) A0[i][0] = A0[i][1] = A0[i][2] = A0[i][3] = 0;
  }
  for (int s = -1; s < NSEG; s++) {
    if (s >= 0) {
      PT(0)
      {
        const int lane = opq(tid) & 31;
        const uint32_t hb = sb + R_H + (lane & 7) * 128 + (((lane >> 3) ^ (lane & 7)) << 4);
        float a[4] = {0, 0, 0, 0}, b[4] = {0, 0, 0, 0};
        mwait(sb + B_Z0, (s - 1) & 1);
        PT(1)
        uint32_t f[18][4];
#pragma unroll
        for (int c = -PD; c < 18; c++) {
          if (c + PD == 8) mwait(sb + B_Z1, (s - 1) & 1);
          if (c + PD < 18) ldsm4(f[c + PD], (hb ^ (((c + PD) & 1) * 64)) + ((c + PD) >> 1) * 5120);
          if (c >= 0) {
            mma16(a, W[2 * c][0], W[2 * c][1], W[2 * c][2], W[2 * c][3], f[c][0], f[c][1]);
            mma16(b, W[2 * c + 1][0], W[2 * c + 1][1], W[2 * c + 1][2], W[2 * c + 1][3], f[c][2], f[c][3]);
          }
        }
        sts1(qk + 512 + lane * 4, pack2(a[0] + b[0], a[1] + b[1]));
        sts1(qk + 1152 + lane * 4, pack2(a[2] + b[2], a[3] + b[3]));
        fence_async();
      }
      PT(2)
      const int lane = opq(tid) & 31;
      if (role) {
        bar_arrive(N_P1, 256);
        if (tid == 128) arm_step(sb, s);
        const uint32_t o4 = sb + (warp - 4) * 640 + lane * 16, o1 = sb + (warp - 4) * 640 + 512 + lane * 4;
        uint32_t h[5];
        bar_sync(N_PX, 192);
        lds4(h, o4 + R_P); h[4] = lds1(o1 + R_P);
        mwait(sb + B_SX, s & 1);
        PT(4)
        softmax8<true>(h, o4, o1);
        PT(5)
      } else {
        float S[20];
        const uint64_t da = mkdesc(sb + R_Q, 640, 128, 0), db = mkdesc(sb + R_K, 640, 128, 0);
        const uint32_t rs = mapa(sb, (cta & 15) ^ 1);
        const uint32_t o4 = warp * 1280 + lane * 16, o1 = warp * 1280 + 512 + lane * 4;
        bar_sync(N_P1, 256);
        wg_fence();
#pragma unroll
        for (int k = 0; k < 4; k++) wg_ss40<1>(S, da + k * 80, db + k * 80, k);
        wg_commit();
        bar_arrive(N_S, 256);
        wg_wait<0>();
        PT(3)
        uint32_t h[2][5];
        if (warp == 2) {
#pragma unroll
          for (int j = 0; j < 5; j++) h[0][j] = pack2(S[4 * j], S[4 * j + 1]);
          sta4(rs + R_SX + o4, h[0][0], h[0][1], h[0][2], h[0][3], rs + B_SM); sta1(rs + R_SX + o1, h[0][4], rs + B_SM);
          mwait(sb + B_SM, s & 1);
          PT(4)
          softmax8<false>(h[0], sb + o4, sb + o1);
          bar_arrive(N_PM, 160);
        } else if (warp < 2) {
          const int row = warp * 16 + (lane >> 2) - (lane & 3) * 2;
#pragma unroll
          for (int g = 0; g < 2; g++) {
#pragma unroll
            for (int j = 0; j < 5; j++) h[g][j] = pack2(j < 4 && j * 8 > row + g * 8 ? -INFINITY : S[4 * j + 2 * g], j < 4 && j * 8 + 1 > row + g * 8 ? -INFINITY : S[4 * j + 2 * g + 1]);
            sts4(sb + R_P + o4 + g * 640, h[g][0], h[g][1], h[g][2], h[g][3]); sts1(sb + R_P + o1 + g * 640, h[g][4]);
            sta4(rs + R_SX + o4 + g * 640, h[g][0], h[g][1], h[g][2], h[g][3], rs + B_SX);
            sta1(rs + R_SX + o1 + g * 640, h[g][4], rs + B_SX);
          }
          bar_arrive(N_PX, 192);
        } else {
          if (s) bar_sync(N_O, 160);
          if (tid == 96) {
            if (s) {
              bulk_wait<0>();
              tma_store(&P.ctx, sb + R_OX, cta * 64, s * 32 - 32); bulk_commit();
              if ((s & 3) == 1 && s > 1) signal_after_bulk(S_CTXB + (s >> 2) - 1);
              bulk_wait_read<0>();
            }
          }
        }
        __syncwarp();
        PT(5)
      }
      {
        if (s == 0) {
          bar_sync(N_INIT2, 384);
#pragma unroll
          for (int i = 0; i < NRES; i++) ldsm4(A0[i], sb + R_WO + warp * 512 + lane * 16 + (16 - NRES + i) * 4608);
        }
        if (s == NSEG - 1) break;
        wo_tile<NRES, NPF>(A0, sb, warp, lane, yo, s);

        PT(8)
        bar_sync(N_WO, 384);
      }
    }
    {
      float acc[16];
      const uint64_t db = mkdesc(sb + R_H + 1024, 16, 1024, 1);
      mwait(sb + B_XA, (s + 1) & 1);
      PT(9)
      wg_fence();
#pragma unroll
      for (int k = 0; k < XG * 4; k++) wg_rs32(acc, W[k], db + (k >> 2) * 320 + (k & 3) * 2, k);
      wg_commit();
      mwait(sb + B_XB, (s + 1) & 1);
      wg_fence();
#pragma unroll
      for (int k = XG * 4; k < KA; k++) wg_rs32(acc, W[k], db + (k >> 2) * 320 + (k & 3) * 2, 1);
      wg_commit();
      wg_wait<0>();
      PT(10)
      bar_sync(N_SUM, 384);
      wg_fence();
#pragma unroll
      for (int k = KA; k < 36; k++) wg_rs32(acc, W[k], db + (k >> 2) * 320 + (k & 3) * 2, 1);
      wg_commit();
      const uint32_t o = qk + (opq(tid) & 31) * 16;
      wg_wait<0>();
      PT(11)
      stsm4(o, pack2(acc[0], acc[1]), pack2(acc[4], acc[5]), pack2(acc[8], acc[9]), pack2(acc[12], acc[13]));
      stsm4(o + 640, pack2(acc[2], acc[3]), pack2(acc[6], acc[7]), pack2(acc[10], acc[11]), pack2(acc[14], acc[15]));
    }
  }
  bar_arrive(N_WO, 384);
  for (int i = 0; i < (warp ? 1 : 2); i++)
    asm volatile("st.relaxed.gpu.global.b64 [%0],%1;" ::"l"((uint8_t*)g_Y + YSLOT + yo + i * 2 * 16384), "l"(0ull) : "memory");
  TL_END(6)
  if (tid == 0) CT(1, 0)
  if (warp == 3) {
    if (tid == 96) { bulk_wait<0>(); asm volatile("fence.proxy.async.global;" ::: "memory"); }
    __syncwarp();
    bar_arrive(N_O, 160);
  }
  asm volatile("barrier.cluster.arrive.relaxed.aligned;" ::: "memory");
  float acc[48];
  const int rk = opq(cta) & 15, n = rk / 5, q = rk - n * 5;
  out_consume<TST, false, 32>(acc, sb, sb + B_O, rk == 15 ? 0 : q == 4 ? 12 : 13);
  if (tid == 0) CT(7, 1)
  if (tid == 0) CT(1, 1)
  asm volatile("barrier.cluster.wait.aligned;" ::: "memory");
  bar_sync(N_P1, 256);
  {
#pragma unroll
    for (int u = 0; u < 6; u++) {
      const int d = u % 5;
      const float* a = acc + u * 8;
      const uint32_t x = pack2(a[0], a[1]), y = pack2(a[2], a[3]), z = pack2(a[4], a[5]), w = pack2(a[6], a[7]);
      const uint32_t rs = mapa(sb, rk == 15 ? 15 : n * 5 + d);
      if (d == q) sts4(sb + R_RED - 8192 + (u / 5) * 4096 + tid * 16, x, y, z, w);
      else sta4(rs + R_RED + (q < d ? q : q - 1) * 8192 + (u / 5) * 4096 + tid * 16, x, y, z, w, rs + B_R);
    }
    mbar_wait(sb + B_R, 0);
    if (tid == 0) CT(1, 2)
    const int lane = tid & 31;
    const uint32_t st = sb + warp * 1024 + (lane & 15) * 48 + (lane >> 4) * 16, ld = sb + warp * 1024 + (lane >> 1) * 48 + (lane & 1) * 16;
    bf16* out = P.out + (size_t)((TAIL0 + (cta >> 5)) * 128 + warp * 16 + (lane >> 1)) * (2 * DM) + DM + ((cta >> 4) & 1) * 288 + n * 96 + q * 16 + (lane & 1) * 8;
#pragma unroll 1
    for (int i = 0; i < (q ? 1 : 2); i++) {
      uint32_t v[5][4], r[4];
#pragma unroll
      for (int p = 0; p < 5; p++) lds4(v[p], sb + R_RED + (p - 1) * 8192 + i * 4096 + tid * 16);
#pragma unroll
      for (int j = 0; j < 4; j++)
        r[j] = pack2((blo(v[0][j]) + blo(v[1][j])) + (blo(v[2][j]) + blo(v[3][j])) + blo(v[4][j]), (bhi(v[0][j]) + bhi(v[1][j])) + (bhi(v[2][j]) + bhi(v[3][j])) + bhi(v[4][j]));
      stsm4(st + i * 8192, r[0], r[1], r[2], r[3]);
      __syncwarp();
      lds4(r, ld + i * 8192);
      asm volatile("{.reg .pred p; setp.ne.s32 p,%5,15; @p st.global.v4.b32 [%0],{%1,%2,%3,%4};}" ::"l"(out + i * 80), "r"(r[0]), "r"(r[1]), "r"(r[2]), "r"(r[3]), "r"(rk) : "memory");
    }
  }
}

template <int K> DEVI void v_resident(uint32_t (*F)[4], uint32_t wv) {
  if constexpr (K < 36) { if (VIdx<K>::r == 'r') ldsm4t(F[VIdx<K>::v], wv + K * 2048); v_resident<K + 1>(F, wv); }
}
template <int K> DEVI void v_pass(float* acc, const uint32_t (*F)[4], uint64_t da, uint64_t db, uint32_t xf, uint32_t t, uint32_t nrel) {
  if constexpr (K < 36) {
    wg_fence();
    if (VIdx<K>::r == 'r') wg_rs40(acc, F[VIdx<K>::v], db + (K >> 2) * 320 + (K & 3) * 2, K);
    else wg_ss40<0>(acc, da + K * 128, db + (K >> 2) * 320 + (K & 3) * 2, K);
    wg_commit();
    if constexpr (VIdx<K>::p != '-') wg_wait<VIdx<K>::p - '0'>();
    if (K == XG * 4 - 1 + XW) { wg_wait<XW>(); asm volatile("{.reg .pred p; .reg .b32 a; setp.lt.u32 p,%1,%2; @p mapa.shared::cluster.u32 a,%0,%1; @p mbarrier.arrive.shared::cluster.b64 _,[a];}" ::"r"(xf), "r"(t), "r"(nrel) : "memory"); }
    v_pass<K + 1>(acc, F, da, db, xf, t, nrel);
  }
}
DEVI void rec_aux(const RecParams& P, const uint32_t sb, const int cta) {
  const int tid = pin(threadIdx.x);
  {
    uint4 v[5];
#pragma unroll
    for (int j = 0; j < 5; j++) if (j * 128 + tid - 256 < 576) v[j] = ((const uint4*)P.mem0)[j * 128 + tid - 256];
    if (tid == 288) {
      const uint32_t t0 = clk32();
      while (clk32() - t0 < (uint32_t)WOD) {}
#pragma unroll 1
      for (int i = 0; i < 4; i++) tma_load(sb + R_WO + i * 18432, &P.wo, (cta & 3) * 144, (cta ^ i) * 64, sb + B_W3);
      for (int i = 0; i < 3; i++) asm volatile("cp.async.bulk.prefetch.tensor.2d.L2.global [%0,{%1,%2}];" ::"l"(&P.wv), "r"(cta * 64), "r"(i * 192) : "memory");
    }
    __syncwarp();
    bar_sync(N_INIT1, 256);
#pragma unroll
    for (int j = 0; j < 5; j++) {
      const int i = j * 128 + tid - 256, t = i / 72, c = i - t * 72;
      if (i < 576) sts4(sb + R_H + (c >> 3) * 5120 + t * 128 + (((c & 7) ^ t) << 4), v[j].x, v[j].y, v[j].z, v[j].w);
    }
    fence_async();
    bar_arrive(N_SUM, 384);
    cluster_sync_relaxed();
    if (tid == 288) {
      if ((cta & 15) < 9) x_load(P, sb, cta & 15, 0);
#pragma unroll 1
      for (int i = 0; i < 3; i++) tma_load(sb + R_WV + i * 24576, &P.wv, cta * 64, i * 192, sb + B_W2);
    }
    __syncwarp();
    TL_END(12)
    wo_convert(sb, threadIdx.x & 31);
    bar_sync(N_O, 128);
    bar_arrive(N_INIT2, 384);
    TL_END(10)
  }
  const int rk = cta & 15, w4 = __shfl_sync(~0u, (threadIdx.x >> 5) & 3, 0);
  const uint32_t yg = pin((((threadIdx.x >> 5) & 3) * 16 + rk) * 1024 + ((threadIdx.x >> 4) & 1) * 128 + (threadIdx.x & 3) * 32 + ((threadIdx.x >> 2) & 3) * 8);
  uint32_t F[VB][4];
  mbar_wait(sb + B_W2, 0);
  TL_END(7)
  v_resident<0>(F, sb + R_WV + ((tid & 7) + ((tid >> 4) & 1) * 8) * 128 + (((w4 * 2 + ((tid >> 3) & 1)) ^ (tid & 7)) << 4));
  LT(0)
  for (int s = 0; s < NSEG; s++) {
    const bool last = s == NSEG - 1;
    uint32_t va[12], p[5];
    int lane = opq(tid) & 31;
    {
      float acc[20];
      const uint64_t da = mkdesc(sb + R_WV, 0, 1024, 1), db = mkdesc(sb + R_H, 16, 1024, 1);
      PT(0)
      bar_sync(N_S, 256);
      asm volatile("fence.proxy.async::generic.acquire.sync_restrict::shared::cluster.cluster;" ::: "memory");
      v_pass<0>(acc, F, da, db, sb + B_XF, tid - 256, last ? 0 : XG);
      PT(13)
      bar_sync(N_PM, 160);
      lds4(p, sb + R_P + 2560 + lane * 16); p[4] = lds1(sb + R_P + 3072 + lane * 4);
      wg_wait<0>();
      PT(1)
#pragma unroll
      for (int i = 0; i < 10; i++) va[i < 2 ? i + 8 : i - 2] = pack2(acc[2 * i], acc[2 * i + 1]);
      va[10] = va[11] = 0;
    }
    lane = opq(tid) & 31;
    if (!last) {
      const uint32_t uo = R_U + w4 * 256 + lane * 4;
      float a[4] = {0, 0, 0, 0}, b[4] = {0, 0, 0, 0}, c[4] = {0, 0, 0, 0};
      mma16(a, va[0], va[1], va[2], va[3], p[0], p[1]); mma16(b, va[4], va[5], va[6], va[7], p[2], p[3]); mma8(c, va[8], va[9], p[4]);
      const uint32_t u0 = pack2(a[0] + b[0] + c[0], a[1] + b[1] + c[1]), u1 = pack2(a[2] + b[2] + c[2], a[3] + b[3] + c[3]);
      sts1(sb + uo, u0); sts1(sb + uo + 128, u1);
      __syncwarp();
      if (lane == 0) mbar_arrive(sb + B_V);
#pragma unroll
      for (int q = 1; q < 4; q++) { const uint32_t rs = mapa(sb, rk ^ q); sta1(rs + uo + q * 1024, u0, rs + B_U); sta1(rs + uo + q * 1024 + 128, u1, rs + B_U); }
      asm volatile("{.reg .pred p; .reg .b32 a; setp.lt.u32 p,%1,%3; @p mapa.shared::cluster.u32 a,%0,%2; @p mbarrier.arrive.shared::cluster.b64 _,[a];}" ::"r"(sb + B_XF), "r"(tid - 256 - XG), "r"(tid - 256), "n"(9 - XG) : "memory");
      PT(4)
      if (w4 == 3) {
        wo_tile<0, 4>(nullptr, sb, 8, lane, y_offset(cta, 8, lane), s);
      } else if (tid == 288 && rk < 9) { mbar_wait(sb + B_XF, s & 1); x_load(P, sb, rk, s + 1); }
      PT(2)
    }
    lane = opq(tid) & 31;
    uint32_t ox[8], tu;
    {
      float o[16];
      const uint64_t dp = mkdesc(sb + R_P, 128, 640, 0);
      bar_sync(N_WO, 384);
      wg_fence();
      wg_rs32(o, va, dp, 0); wg_rs32(o, va + 4, dp + 16, 1); wg_rs32(o, va + 8, mkdesc(sb + R_P + 512, 0, 640, 0), 1);
      wg_commit();
      tu = clk32();
      wg_wait<0>();
      PT(3)
#pragma unroll
      for (int i = 0; i < 8; i++) ox[i] = pack2(o[2 * i], o[2 * i + 1]);
    }
    if (!last) {
      const uint8_t* y = (const uint8_t*)g_Y + (s & 1) * YSLOT + yg;
      uint32_t w0[8], w1[8], w2[8];
      while (clk32() - tu < (uint32_t)YD) {}
      y_load(w0, y); y_load(w1, y + 4 * 16384);
      if (w4 == 0) y_load(w2, y + 8 * 16384);
      else {
#pragma unroll
        for (int i = 0; i < 8; i++) w2[i] = ((s >> 1) & 1) ^ 1;
      }
      PT(5)
      const uint32_t dst = R_H + w4 * 5120 + (rk >> 1) * 128 + ((((rk & 1) * 4 + (lane >> 3)) ^ (rk >> 1)) << 4) + (lane & 4) * 2;
      const uint32_t tag = ((s >> 1) & 1) ^ 1, sel = (lane & 4) ? 0x3f800000u : 0x3f80u;
      uint32_t r0[2], r1[2], r2[2];
#pragma unroll 1
      for (int it = 0; (y_missing(w0, tag) | y_missing(w1, tag) | y_missing(w2, tag)) && it < (1 << 20); it++) {
        y_reload(w0, y, tag); y_reload(w1, y + 4 * 16384, tag); y_reload(w2, y + 8 * 16384, tag);
      }
      PT(7)
      y_sum(r0, w0, sel); y_sum(r1, w1, sel); y_sum(r2, w2, sel);
      y_send(r0, sb, dst, B_Z0, lane);
      bar_arrive(N_SUM, 384);
      y_send(r1, sb, dst + 4 * 5120, B_Z1, lane);
      if (w4 == 0) y_send(r2, sb, dst + 8 * 5120, B_Z1, lane);
      PT(9)
    }
#pragma unroll
    for (int h = 0; h < 2; h++) stsm4t(sb + R_OX + lane * 128 + (((w4 * 2 + h) ^ (lane & 7)) << 4), ox[h], ox[2 + h], ox[4 + h], ox[6 + h]);
    if (last) break;
    fence_async();
    bar_arrive(N_O, 160);
    PT(11)
  }
  fence_async();
  bar_sync(N_O, 160);
  if (tid == 256) {
    tma_store(&P.ctx, sb + R_OX, cta * 64, SEQ - 32); bulk_commit(); bulk_wait<0>(); signal_after_bulk(S_CTXB + 15);
  }
  __syncwarp();
  LT(1)
  asm volatile("barrier.cluster.arrive.relaxed.aligned;" ::: "memory");
  if (tid == 256) {
    const int m = TAIL0 + (cta >> 5), n = rk / 5, q = rk - n * 5;
    mbar_expect(sb + B_R, q || rk == 15 ? 4 * 4096 : 8 * 4096);
    if (rk < 15) out_produce<TST, false, 32>(P.o, sb, sb + B_O, m, ((cta >> 4) & 1) * 3 + n, q * 13, q == 4 ? 12 : 13, S_CTXB + m);
  }
  __syncwarp();
  asm volatile("barrier.cluster.wait.aligned;" ::: "memory");
}

__global__ void __launch_bounds__(384, 1) rec_kernel(const __grid_constant__ RecParams P) {
  extern __shared__ __align__(1024) uint8_t smem_raw[];
  const uint32_t sb = s2u(smem_raw);
  const int tid = threadIdx.x, cta = blockIdx.x;
  pdl_trigger();
  if (cta >= 64) {
    unsigned sm; asm("mov.u32 %0,%%smid;" : "=r"(sm));
    if (tid == 0) g_group[sm & 255] = (cta >> 4) - 3;
    return;
  }
  TL_START(1)
  if (tid == 0) {
    for (int i = 0; i < 14 + 2 * TST; i++) mbar_init(sb + R_BAR + 8 * i, 8 * i == B_XF - R_BAR ? 16 : 8 * i == B_V - R_BAR ? 4 : i >= 14 + TST ? 2 : 1);
    asm volatile("fence.mbarrier_init.release.cluster;" ::: "memory");
    asm volatile("cp.async.bulk.prefetch.L2.global [%0],%1;" ::"l"(P.x_raw + cta * DM), "r"(DM * 2) : "memory");
    mbar_expect(sb + B_W0, 73728); mbar_expect(sb + B_W1, 73728); mbar_expect(sb + B_W2, 73728); mbar_expect(sb + B_W3, 73728);
#pragma unroll 1
    for (int i = 0; i < 3; i++) { tma_load(sb + R_WV + i * 24576, &P.wq, cta * 64, i * 192, sb + B_W0); tma_load(sb + R_H + i * 24576, &P.wk, cta * 64, i * 192, sb + B_W1); }
    mbar_expect(sb + B_XA, XG * 4096); mbar_expect(sb + B_XB, (9 - XG) * 4096);
  }
  __syncthreads();
  if (tid >= 256) { reg_dec<504 - 2 * RP>(); rec_aux(P, sb, cta); }
  else { reg_inc<RP>(); rec_proj(P, sb, cta); }
  TL_END(1)
  if (tid == 0) CT(7, 2)
  cluster_sync_relaxed();
}
typedef CUresult (*EncFn)(CUtensorMap*, CUtensorMapDataType, cuuint32_t, void*, const cuuint64_t*, const cuuint64_t*, const cuuint32_t*, const cuuint32_t*,
                          CUtensorMapInterleave, CUtensorMapSwizzle, CUtensorMapL2promotion, CUtensorMapFloatOOBfill);
static EncFn g_enc;
static CUtensorMap mk(const void* p, uint64_t cols, uint64_t rows, uint64_t pitch_elems, uint32_t box_rows, uint32_t box_cols = 64) {
  CUtensorMap m;
  cuuint64_t dim[2] = {cols, rows}, str[1] = {pitch_elems * 2};
  cuuint32_t box[2] = {box_cols, box_rows}, es[2] = {1, 1};
  g_enc(&m, CU_TENSOR_MAP_DATA_TYPE_BFLOAT16, 2, (void*)p, dim, str, box, es, CU_TENSOR_MAP_INTERLEAVE_NONE, box_cols == 64 ? CU_TENSOR_MAP_SWIZZLE_128B : box_cols == 32 ? CU_TENSOR_MAP_SWIZZLE_64B : CU_TENSOR_MAP_SWIZZLE_NONE,
        CU_TENSOR_MAP_L2_PROMOTION_L2_256B, CU_TENSOR_MAP_FLOAT_OOB_FILL_NONE);
  return m;
}
static CUtensorMap mk3(const void* p, uint32_t g, uint32_t box_rows) {
  CUtensorMap m;
  cuuint64_t dim[3] = {g, HD, DM / g}, str[2] = {DM * 2, g * 2};
  cuuint32_t box[3] = {g, box_rows, 3}, es[3] = {1, 1, 1};
  g_enc(&m, CU_TENSOR_MAP_DATA_TYPE_BFLOAT16, 3, (void*)p, dim, str, box, es, CU_TENSOR_MAP_INTERLEAVE_NONE, g == 64 ? CU_TENSOR_MAP_SWIZZLE_128B : CU_TENSOR_MAP_SWIZZLE_64B,
        CU_TENSOR_MAP_L2_PROMOTION_L2_256B, CU_TENSOR_MAP_FLOAT_OOB_FILL_NONE);
  return m;
}
template <class T> static void* sym(T& s) { void* p; cudaGetSymbolAddress(&p, s); return p; }

#define FE 6
#define STG 10
#define FHC 24
#define FSL 5
#define NF2 20
template <class K, class A> static void launch(K k, int grid, int smem, int cluster, bool pdl, const A& arg) {
  cudaLaunchConfig_t c = {};
  cudaLaunchAttribute at[2];
  int n = 0;
  if (cluster > 1) { at[n].id = cudaLaunchAttributeClusterDimension; at[n].val.clusterDim.x = cluster; at[n].val.clusterDim.y = at[n].val.clusterDim.z = 1; n++; }
  if (pdl) { at[n].id = cudaLaunchAttributeProgrammaticStreamSerialization; at[n].val.programmaticStreamSerializationAllowed = 1; n++; }
  c.gridDim = grid; c.blockDim = 384; c.dynamicSmemBytes = smem; c.stream = cudaStreamPerThread; c.attrs = at; c.numAttrs = n;
  cudaLaunchKernelEx(&c, k, arg);
}

extern "C" void kernel_launch(void* const* d_in, const int* in_sizes, int n_in, void* d_out, int out_size) {
  static int nb, ng;
  if (!g_enc) {
    cudaDriverEntryPointQueryResult qr;
    cudaGetDriverEntryPoint("cuTensorMapEncodeTiled", (void**)&g_enc, cudaEnableDefault, &qr);
    cudaDeviceGetAttribute(&nb, cudaDevAttrMultiProcessorCount, 0);
    nb = nb - 64 < 54 ? 54 : nb - 64 > 96 ? 96 : (nb - 64) & ~1;
    cudaFuncSetAttribute(out_kernel, cudaFuncAttributeMaxDynamicSharedMemorySize, SM_O);
    cudaFuncSetAttribute(fa_kernel, cudaFuncAttributeMaxDynamicSharedMemorySize, SM_F);
    cudaFuncSetAttribute(rec_kernel, cudaFuncAttributeMaxDynamicSharedMemorySize, R_END);
    cudaFuncSetAttribute(rec_kernel, cudaFuncAttributeNonPortableClusterSizeAllowed, 1);
    cudaLaunchConfig_t c = {};
    cudaLaunchAttribute at; at.id = cudaLaunchAttributeClusterDimension; at.val.clusterDim.x = 16; at.val.clusterDim.y = at.val.clusterDim.z = 1;
    c.gridDim = 128; c.blockDim = 384; c.dynamicSmemBytes = R_END; c.attrs = &at; c.numAttrs = 1;
    cudaOccupancyMaxActiveClusters(&ng, rec_kernel, &c);
    ng = ng < 4 ? 0 : ng - 4 > nb / 16 ? nb / 16 : ng - 4;
  }
  const bf16 *Ax = (const bf16*)d_in[0], *Ac = (const bf16*)d_in[1], *Awq = (const bf16*)d_in[2], *Awk = (const bf16*)d_in[3], *Awv = (const bf16*)d_in[4],
             *Awo = (const bf16*)d_in[5], *Bx = (const bf16*)d_in[6], *Bm = (const bf16*)d_in[7], *Bwq = (const bf16*)d_in[8], *Bwk = (const bf16*)d_in[9],
             *Bwv = (const bf16*)d_in[10], *Bwo = (const bf16*)d_in[11];
  bf16* out = (bf16*)d_out;
  FaParams f;
  ProjParams& p = f.p;
  int nitems = 0;
  p.a[0] = mk(Ac, 512, SEQ, 512, 128); p.a[1] = mk(Ax, DM, SEQ, DM, 128);
  p.w[0] = mk(Awk, HD, 512, HD, 64); p.w[1] = mk(Awv, HD, 512, HD, 64); p.w[2] = mk(Awq, HD, DM, HD, 64);
  p.c[0] = mk(sym(g_kA), HD, SEQ, HD, 64); p.c[1] = mk(sym(g_vA), HD, SEQ, HD, 64); p.c[2] = mk(sym(g_qA), HD, SEQ, HD, 64);
  {
    int parts[16];
    for (int i = 0; i < 16; i++) parts[i] = 1;
    for (int e = 0; e < nb / 2 - 16; e++) parts[e % 24 < 16 ? e % 8 : 15 - (e % 24 - 16)]++;
    for (int i = 15; i >= 0; i--)
      for (int j = 0, nc = i < 8 ? 32 : 16, a = parts[i]; j < a; j++) {
        ProjItem& I = p.item[nitems++];
        I.pa = i >> 3; I.m = i & 7;
        I.c0[0] = j * nc / a; I.n[0] = (j + 1) * nc / a - I.c0[0];
        I.c0[1] = (j * nc + a - 1) / a; I.n[1] = ((j + 1) * nc + a - 1) / a - I.c0[1];
        if (i < 8 && a == 3) { const int d = STG * (i + 4) / 11, b1 = 11 - d, b2 = 22 - d + (i - 4) * STG / 16; I.c0[1] = j == 0 ? 0 : j == 1 ? b1 : b2; I.n[1] = (j == 0 ? b1 : j == 1 ? b2 : 32) - I.c0[1]; }
      }
  }
  for (int i = 0; i < nitems; i++) {
    auto len = [&](int j) { return (8 + p.item[j].pa) * (1 + p.item[j].n[0] + p.item[j].n[1]); };
    int longer = 0;
    for (int j = 0; j < nitems; j++) longer += len(j) > len(i) || (len(j) == len(i) && j < i);
    p.item[i].leave = longer < NF2 / 2;
    p.item[i].s0 = (PST - len(i) % PST) % PST;
  }
  OutParams o;
  for (int i = 0; i < 3; i++) {
    f.om[i].a = mk(i ? sym(g_ctxB) : sym(g_qA), HD, SEQ, HD, 128);
    f.om[i].b = i < 2 ? mk(i ? Bwo : Awo, DM, HD, DM, 32) : mk(Bwo, DM, HD, DM, 64, 32);
    f.om[i].c = mk(out + (i ? DM : 0), DM, SEQ, 2 * DM, 64, i < 2 ? 64 : 32);
  }
  o.p[0] = f.om[1]; o.p[0].b = mk(Bwo, DM, HD, DM, 64); o.p[1] = f.om[2];
  f.q = mk(sym(g_qA), HD, SEQ, HD, 128); f.k = mk(sym(g_kA), HD, SEQ, HD, 128); f.v = mk(sym(g_vA), HD, SEQ, HD, 128); f.o = mk(sym(g_qA), HD, SEQ, HD, 64);
  f.nctas = nb; f.ngroups = ng;
  for (int i = 0; i < 9; i++) f.nproj[i] = 0;
  for (int i = 0; i < nitems; i++) f.nproj[p.item[i].pa * (p.item[i].m + 1)] += 4;
  for (int key = -90, n = 0; n < 512; key++)
    for (int h = 0; h < 32; h++)
      for (int qt = 0; qt < 16; qt++)
        if ((h < FHC ? h : FHC) * FSL - qt * 2 - (qt >= 12 && h < FE ? 60 : 0) == key) f.order[n++] = qt * 32 + h;
  RecParams r;
  r.wq = mk(Bwq, HD, DM, HD, 192); r.wk = mk(Bwk, HD, DM, HD, 192); r.wv = mk(Bwv, HD, DM, HD, 192); r.wo = mk(Bwo, DM, HD, DM, 64, 144);
  r.x_raw = Bx;
  r.x = mk(Bx, DM, SEQ, DM, 32); r.ctx = mk(sym(g_ctxB), HD, SEQ, HD, 32); r.mem0 = Bm; r.o = f.om[2]; r.o.b = mk3(Bwo, 32, 64); r.out = out;

  f.om[2].a = mk(sym(g_ctxB), HD, SEQ, HD, 64);
  uint16_t* last = f.tile;
  int nl = 0;
  for (int m = 14; m >= 0; m -= 2)
    for (int n = 0; n < 3; n++) { last[nl++] = m * 8 + n; last[nl++] = m * 8 + 8 + n; }
  for (int n = 0; n < 6; n++) last[nl++] = 256 + (TAIL0 - 1) * 8 + n;
  bool done[16][3] = {};
  for (int m = TAIL0 - 3; m >= 0; m -= 2)
    for (int n = 2; n >= 0 && nl < nb; n--) { last[nl++] = 128 + m * 8 + n; last[nl++] = 128 + m * 8 + 8 + n; done[m][n] = done[m + 1][n] = true; }
  while (nl < nb) last[nl++] = 384;
  o.n = 2; o.odd = 0; o.tile[0] = 128; o.tile[1] = 129; done[0][0] = true;
  for (int m = 0; m < TAIL0 - 1; m++)
    for (int n = 0; n < 3; n++) if (!done[m][n]) o.tile[o.n++] = m * 8 + n;
  launch(rec_kernel, 64 + 16 * ng, R_END, 16, false, r);
  f.proj = 1;
  launch(fa_kernel, nb, SM_F, 2, true, f);
  launch(out_kernel, o.n, SM_O, 2, true, o);
  f.proj = 0;
  launch(fa_kernel, NF2, SM_F, 2, true, f);
}
```

```cpp
#include <cuda_runtime.h>
#include <cuda_bf16.h>
#include <cuda.h>
#include <stdint.h>

typedef __nv_bfloat16 bf16;
#define DEVI __device__ __forceinline__
#define WAIT_FAIL(code) break
#define WAIT_MAX (1 << 22)

constexpr int SEQ = 2048, HD = 4096, DM = 576, NSEG = 64;

__device__ __align__(1024) bf16 g_qA[SEQ * HD], g_kA[SEQ * HD], g_vA[SEQ * HD];
__device__ __align__(1024) bf16 g_ctxB[SEQ * HD];
__device__ __align__(1024) uint4 g_Y[2 * 9 * 16 * 64];
enum { S_QUEUE = 0, S_EXIT = 1, S_LIST = 8, S_PROJ = 32, S_CTXA = 64, S_CTXB = 96 };
__device__ unsigned g_sync[128];
__device__ __align__(16) uint8_t g_group[256];
#define LT(i)
#define CT(k, i) {}
#define TL_START(i)
#define TL_END(i)

DEVI uint32_t s2u(const void* p) { return (uint32_t)__cvta_generic_to_shared(p); }
DEVI void mbar_init(uint32_t b, uint32_t c) { asm volatile("mbarrier.init.shared::cta.b64 [%0],%1;" ::"r"(b), "r"(c)); }
DEVI void mbar_expect(uint32_t b, uint32_t n) { asm volatile("mbarrier.arrive.expect_tx.shared::cta.b64 _,[%0],%1;" ::"r"(b), "r"(n) : "memory"); }
DEVI void mbar_arrive(uint32_t b) { asm volatile("mbarrier.arrive.shared::cta.b64 _,[%0];" ::"r"(b) : "memory"); }
DEVI void mbar_wait(uint32_t b, uint32_t ph) {
  uint32_t ok; int it = 0;
  do {
    asm volatile("{.reg .pred p; mbarrier.try_wait.parity.shared::cta.b64 p,[%1],%2; selp.u32 %0,1,0,p;}" : "=r"(ok) : "r"(b), "r"(ph) : "memory");
    if (!ok && ++it > WAIT_MAX) WAIT_FAIL(b & 0xffffff);
  } while (!ok);
}
DEVI bool mbar_try(uint32_t b, uint32_t ph) {
  uint32_t ok;
  asm volatile("{.reg .pred p; mbarrier.try_wait.parity.shared::cta.b64 p,[%1],%2; selp.u32 %0,1,0,p;}" : "=r"(ok) : "r"(b), "r"(ph) : "memory");
  return ok;
}
DEVI bool mbar_test(uint32_t b, uint32_t ph) {
  uint32_t ok;
  asm volatile("{.reg .pred p; mbarrier.test_wait.parity.shared::cta.b64 p,[%1],%2; selp.u32 %0,1,0,p;}" : "=r"(ok) : "r"(b), "r"(ph) : "memory");
  return ok;
}
DEVI void mwait(uint32_t b, uint32_t ph) { if (__builtin_expect(!mbar_try(b, ph), 0)) mbar_wait(b, ph); }
DEVI void tma_load(uint32_t dst, const CUtensorMap* tm, int c0, int c1, uint32_t bar) {
  asm volatile("cp.async.bulk.tensor.2d.shared::cluster.global.mbarrier::complete_tx::bytes [%0],[%1,{%3,%4}],[%2];" ::"r"(dst), "l"(tm), "r"(bar), "r"(c0), "r"(c1) : "memory");
}
DEVI void tma_store(const CUtensorMap* tm, uint32_t src, int c0, int c1) {
  asm volatile("cp.async.bulk.tensor.2d.global.shared::cta.bulk_group [%0,{%2,%3}],[%1];" ::"l"(tm), "r"(src), "r"(c0), "r"(c1) : "memory");
}
DEVI void bulk_commit() { asm volatile("cp.async.bulk.commit_group;" ::: "memory"); }
template <int N> DEVI void bulk_wait_read() { asm volatile("cp.async.bulk.wait_group.read %0;" ::"n"(N) : "memory"); }
template <int N> DEVI void bulk_wait() { asm volatile("cp.async.bulk.wait_group %0;" ::"n"(N) : "memory"); }
DEVI void fence_async() { asm volatile("fence.proxy.async.shared::cta;" ::: "memory"); }
DEVI void bar_sync(int id, int n) { asm volatile("bar.sync %0,%1;" ::"r"(id), "r"(n) : "memory"); }
DEVI void bar_arrive(int id, int n) { asm volatile("bar.arrive %0,%1;" ::"r"(id), "r"(n) : "memory"); }
template <int R> DEVI void reg_inc() { asm volatile("setmaxnreg.inc.sync.aligned.u32 %0;" ::"n"(R)); }
template <int R> DEVI void reg_dec() { asm volatile("setmaxnreg.dec.sync.aligned.u32 %0;" ::"n"(R)); }
DEVI void wg_fence() { asm volatile("wgmma.fence.sync.aligned;" ::: "memory"); }
DEVI void wg_commit() { asm volatile("wgmma.commit_group.sync.aligned;" ::: "memory"); }
template <int N> DEVI void wg_wait() { asm volatile("wgmma.wait_group.sync.aligned %0;" ::"n"(N) : "memory"); }
DEVI uint64_t desc_k(uint32_t a) { return (uint64_t)((a >> 4) & 0x3fff) | (1ull << 16) | (64ull << 32) | (1ull << 62); }
DEVI uint64_t desc_mn(uint32_t a, uint32_t lbo) { return (uint64_t)((a >> 4) & 0x3fff) | ((uint64_t)(lbo >> 4) << 16) | (64ull << 32) | (1ull << 62); }
DEVI uint64_t mkdesc(uint32_t a, uint32_t lbo, uint32_t sbo, int sw) { return (uint64_t)((a >> 4) & 0x3fff) | ((uint64_t)(lbo >> 4) << 16) | ((uint64_t)(sbo >> 4) << 32) | ((uint64_t)sw << 62); }
DEVI uint32_t pack2(float lo, float hi) { uint32_t r; asm("cvt.rn.bf16x2.f32 %0,%1,%2;" : "=r"(r) : "f"(hi), "f"(lo)); return r; }
DEVI float ex2(float x) { float y; asm("ex2.approx.ftz.f32 %0,%1;" : "=f"(y) : "f"(x)); return y; }
DEVI void stsm4(uint32_t a, uint32_t r0, uint32_t r1, uint32_t r2, uint32_t r3) {
  asm volatile("stmatrix.sync.aligned.m8n8.x4.shared.b16 [%0],{%1,%2,%3,%4};" ::"r"(a), "r"(r0), "r"(r1), "r"(r2), "r"(r3) : "memory");
}
DEVI void ldsm4(uint32_t* r, uint32_t a) {
  asm volatile("ldmatrix.sync.aligned.m8n8.x4.shared.b16 {%0,%1,%2,%3},[%4];" : "=r"(r[0]), "=r"(r[1]), "=r"(r[2]), "=r"(r[3]) : "r"(a) : "memory");
}
DEVI void ldsm4t(uint32_t* r, uint32_t a) {
  asm volatile("ldmatrix.sync.aligned.m8n8.x4.trans.shared.b16 {%0,%1,%2,%3},[%4];" : "=r"(r[0]), "=r"(r[1]), "=r"(r[2]), "=r"(r[3]) : "r"(a) : "memory");
}
DEVI void mma16(float* d, uint32_t a0, uint32_t a1, uint32_t a2, uint32_t a3, uint32_t b0, uint32_t b1) {
  asm volatile("mma.sync.aligned.m16n8k16.row.col.f32.bf16.bf16.f32 {%0,%1,%2,%3},{%4,%5,%6,%7},{%8,%9},{%0,%1,%2,%3};"
               : "+f"(d[0]), "+f"(d[1]), "+f"(d[2]), "+f"(d[3]) : "r"(a0), "r"(a1), "r"(a2), "r"(a3), "r"(b0), "r"(b1));
}

DEVI void pdl_trigger() { asm volatile("griddepcontrol.launch_dependents;" ::: "memory"); }
DEVI void signal_after_bulk(int f) {
  asm volatile("fence.proxy.async.global;" ::: "memory");
  asm volatile("red.release.gpu.global.add.u32 [%0], 1;" ::"l"(g_sync + f) : "memory");
}
DEVI void flag_wait(int f, unsigned n, unsigned waiters) {
  for (int it = 0;; it++) {
    if (it > WAIT_MAX) WAIT_FAIL(f);
    unsigned v; asm volatile("ld.acquire.gpu.global.u32 %0, [%1];" : "=r"(v) : "l"(g_sync + f) : "memory");
    if (v >= n) break;
    __nanosleep(64);
  }
  if (waiters) asm volatile("red.relaxed.gpu.global.inc.u32 [%0], %1;" ::"l"(g_sync + f), "r"(n + waiters - 1) : "memory");
  asm volatile("fence.proxy.async.global;" ::: "memory");
}
DEVI uint32_t mapa(uint32_t a, uint32_t r) { uint32_t o; asm("mapa.shared::cluster.u32 %0,%1,%2;" : "=r"(o) : "r"(a), "r"(r)); return o; }
DEVI void tma_load_mc(uint32_t dst, const CUtensorMap* tm, int c0, int c1, uint32_t bar, uint16_t mask) {
  asm volatile("cp.async.bulk.tensor.2d.shared::cluster.global.mbarrier::complete_tx::bytes.multicast::cluster [%0],[%1,{%3,%4}],[%2],%5;" ::"r"(dst), "l"(tm), "r"(bar), "r"(c0), "r"(c1), "h"(mask) : "memory");
}
DEVI void tma_load3(uint32_t dst, const CUtensorMap* tm, int c1, int c2, uint32_t bar) {
  asm volatile("cp.async.bulk.tensor.3d.shared::cluster.global.mbarrier::complete_tx::bytes [%0],[%1,{0,%3,%4}],[%2];" ::"r"(dst), "l"(tm), "r"(bar), "r"(c1), "r"(c2) : "memory");
}
DEVI void arrive_pair(uint32_t b) { if ((threadIdx.x & 127) < 2) asm volatile("mbarrier.arrive.shared::cluster.b64 _,[%0];" ::"r"(mapa(b, threadIdx.x & 1)) : "memory"); }
DEVI void cluster_sync_relaxed() { asm volatile("barrier.cluster.arrive.relaxed.aligned; barrier.cluster.wait.aligned;" ::: "memory"); }
DEVI void cluster_sync() { asm volatile("barrier.cluster.arrive.aligned; barrier.cluster.wait.aligned;" ::: "memory"); }
DEVI void sts4(uint32_t a, uint32_t x, uint32_t y, uint32_t z, uint32_t w) { asm volatile("st.shared.v4.b32 [%0],{%1,%2,%3,%4};" ::"r"(a), "r"(x), "r"(y), "r"(z), "r"(w) : "memory"); }
DEVI void lds4(uint32_t* r, uint32_t a) { asm volatile("ld.shared.v4.b32 {%0,%1,%2,%3},[%4];" : "=r"(r[0]), "=r"(r[1]), "=r"(r[2]), "=r"(r[3]) : "r"(a) : "memory"); }
DEVI void sta4(uint32_t d, uint32_t a, uint32_t b, uint32_t c, uint32_t e, uint32_t bar) {
  asm volatile("st.async.weak.shared::cluster.mbarrier::complete_tx::bytes.v4.b32 [%0],{%1,%2,%3,%4},[%5];" ::"r"(d), "r"(a), "r"(b), "r"(c), "r"(e), "r"(bar) : "memory");
}
DEVI float blo(uint32_t u) { return __uint_as_float(u << 16); }
DEVI float bhi(uint32_t u) { return __uint_as_float(u & 0xffff0000u); }

#define F8(a, o) "+f"(a[o]), "+f"(a[o + 1]), "+f"(a[o + 2]), "+f"(a[o + 3]), "+f"(a[o + 4]), "+f"(a[o + 5]), "+f"(a[o + 6]), "+f"(a[o + 7])
#define F32(a, o) F8(a, o), F8(a, o + 8), F8(a, o + 16), F8(a, o + 24)
template<int TB> DEVI void wg_ss128(float* d, uint64_t da, uint64_t db, int acc){
 asm volatile("{.reg .pred p; setp.ne.b32 p,%66,0;\n wgmma.mma_async.sync.aligned.m64n128k16.f32.bf16.bf16 {%0,%1,%2,%3,%4,%5,%6,%7,%8,%9,%10,%11,%12,%13,%14,%15,%16,%17,%18,%19,%20,%21,%22,%23,%24,%25,%26,%27,%28,%29,%30,%31,%32,%33,%34,%35,%36,%37,%38,%39,%40,%41,%42,%43,%44,%45,%46,%47,%48,%49,%50,%51,%52,%53,%54,%55,%56,%57,%58,%59,%60,%61,%62,%63},%64,%65,p,1,1,0,%67;}"
 : F32(d,0),F32(d,32) : "l"(da),"l"(db),"r"(acc),"n"(TB));}
template<int TB> DEVI void wg_ss192(float* d, uint64_t da, uint64_t db, int acc){
 asm volatile("{.reg .pred p; setp.ne.b32 p,%98,0;\n wgmma.mma_async.sync.aligned.m64n192k16.f32.bf16.bf16 {%0,%1,%2,%3,%4,%5,%6,%7,%8,%9,%10,%11,%12,%13,%14,%15,%16,%17,%18,%19,%20,%21,%22,%23,%24,%25,%26,%27,%28,%29,%30,%31,%32,%33,%34,%35,%36,%37,%38,%39,%40,%41,%42,%43,%44,%45,%46,%47,%48,%49,%50,%51,%52,%53,%54,%55,%56,%57,%58,%59,%60,%61,%62,%63,%64,%65,%66,%67,%68,%69,%70,%71,%72,%73,%74,%75,%76,%77,%78,%79,%80,%81,%82,%83,%84,%85,%86,%87,%88,%89,%90,%91,%92,%93,%94,%95},%96,%97,p,1,1,0,%99;}"
 : F32(d,0),F32(d,32),F32(d,64) : "l"(da),"l"(db),"r"(acc),"n"(TB));}
template<int TB> DEVI void wg_rs128(float* d, const uint32_t* a, uint64_t db, int acc){
 asm volatile("{.reg .pred p; setp.ne.b32 p,%69,0;\n wgmma.mma_async.sync.aligned.m64n128k16.f32.bf16.bf16 {%0,%1,%2,%3,%4,%5,%6,%7,%8,%9,%10,%11,%12,%13,%14,%15,%16,%17,%18,%19,%20,%21,%22,%23,%24,%25,%26,%27,%28,%29,%30,%31,%32,%33,%34,%35,%36,%37,%38,%39,%40,%41,%42,%43,%44,%45,%46,%47,%48,%49,%50,%51,%52,%53,%54,%55,%56,%57,%58,%59,%60,%61,%62,%63},{%64,%65,%66,%67},%68,p,1,1,%70;}"
 : F32(d,0),F32(d,32) : "r"(a[0]),"r"(a[1]),"r"(a[2]),"r"(a[3]),"l"(db),"r"(acc),"n"(TB));}
DEVI void wg_ss96t(float* d, uint64_t da, uint64_t db, int acc){
 asm volatile("{.reg .pred p; setp.ne.b32 p,%50,0;\n wgmma.mma_async.sync.aligned.m64n96k16.f32.bf16.bf16 {%0,%1,%2,%3,%4,%5,%6,%7,%8,%9,%10,%11,%12,%13,%14,%15,%16,%17,%18,%19,%20,%21,%22,%23,%24,%25,%26,%27,%28,%29,%30,%31,%32,%33,%34,%35,%36,%37,%38,%39,%40,%41,%42,%43,%44,%45,%46,%47},%48,%49,p,1,1,0,1;}"
 : F32(d,0),F8(d,32),F8(d,40) : "l"(da),"l"(db),"r"(acc));}
struct ProjItem { uint8_t pa, m, c0[2], n[2], s0, leave; };
struct ProjParams { CUtensorMap a[2], w[3], c[3]; ProjItem item[48]; };
constexpr int PST = 12, P_STG = PST * 16384, P_FULL = P_STG + 32768 + 256, P_EMPTY = P_FULL + 8 * PST, P_OF = P_EMPTY + 8 * PST, P_OE = P_OF + 16, P_END = P_OE + 16;
DEVI void proj_decode(const ProjItem& I, int t, int& pw, int& n) {
  const int g = t >= I.n[0], c = g ? I.c0[1] + t - I.n[0] : I.c0[0] + t;
  pw = I.pa ? 2 : c >> 4; n = (c & 15) + g * 16;
}
DEVI void proj_init(const ProjItem& I, uint32_t base) {
  for (int i = 0; i < PST; i++) { mbar_init(base + P_FULL + 8 * i, 1); mbar_init(base + P_EMPTY + 8 * i, 4); }
  for (int i = 0; i < 2; i++) { mbar_init(base + P_OF + 8 * i, 4); mbar_init(base + P_OE + 8 * i, 1); }
  mbar_init(base + P_END, 1);
  for (int i = 0; i < I.s0; i++) {
    mbar_arrive(base + P_FULL + 8 * i);
    asm volatile("mbarrier.arrive.shared::cta.b64 _,[%0],4;" ::"r"(base + P_EMPTY + 8 * i) : "memory");
  }
}
DEVI int proj_produce(const ProjParams& P, const ProjItem& I, uint32_t base) {
  const int nk = 8 + I.pa, r = blockIdx.x & 1;
  int s = I.s0, ph = 1;
  for (int t = -1; t < I.n[0] + I.n[1]; t++) {
    int pw, n; proj_decode(I, t, pw, n);
    if (t == I.n[0] + I.n[1] - 1) mbar_arrive(base + P_END);
    for (int k = 0; k < nk; k++) {
      if (t >= 0) mbar_wait(base + P_EMPTY + 8 * s, ph);
      mbar_expect(base + P_FULL + 8 * s, 16384);
      if (t < 0) tma_load(base + s * 16384, &P.a[I.pa], k * 64, (I.m * 2 + r) * 128, base + P_FULL + 8 * s);
      else tma_load_mc(base + s * 16384 + r * 8192, &P.w[pw], n * 128 + r * 64, k * 64, base + P_FULL + 8 * s, 3);
      if (++s == PST) { s = 0; ph ^= 1; }
    }
  }
  return ph;
}
DEVI void proj_store(const ProjParams& P, const ProjItem& I, uint32_t base, int g) {
  const int r0 = (I.m * 2 + (blockIdx.x & 1)) * 128 + g * 64;
  for (int t = 0; t < I.n[0] + I.n[1]; t++) {
    int pw, n; proj_decode(I, t, pw, n);
    mbar_wait(base + P_OF + 8 * g, t & 1);
    tma_store(&P.c[pw], base + P_STG + g * 16384, n * 128, r0);
    tma_store(&P.c[pw], base + P_STG + g * 16384 + 8192, n * 128 + 64, r0);
    bulk_commit();
    bulk_wait_read<0>();
    mbar_arrive(base + P_OE + 8 * g);
    if (t == 3 && !g) CT(0, 1)
    if (t == I.n[0] - 1) { bulk_wait<0>(); signal_after_bulk(S_PROJ + I.pa * (I.m + 1) * 2); }
  }
  bulk_wait<0>(); signal_after_bulk(S_PROJ + I.pa * (I.m + 1) * 2 + 1);
  if (!g) CT(0, 2)
}
DEVI void proj_consume(const ProjItem& I, uint32_t base, int tid, int wg) {
  const uint32_t full = base + P_FULL;
  uint32_t A[36][4];
  float acc[64];
  uint32_t s = I.s0, ph = 0, c = 1;
  const uint32_t row = ((tid >> 5) & 3) * 16 + (tid & 15);
  const uint32_t roff = row * 128 + ((((tid >> 4) & 1) ^ (row & 7)) << 4);
  const uint32_t rel = mapa(base + P_EMPTY, tid & 1);
  auto release = [&](uint32_t st) { asm volatile("{.reg .pred p; setp.lt.u32 p,%1,2; @p mbarrier.arrive.shared::cluster.b64 _,[%0];}" ::"r"(rel + 8 * st), "r"(tid & 127) : "memory"); };
  const int pa = I.pa, nt = I.n[0] + I.n[1];
#pragma unroll
  for (int k = 0; k < 9; k++) {
    if (k < 8 || pa) {
      mbar_wait(full + 8 * s, ph);
#pragma unroll
      for (int kk = 0; kk < 4; kk++) ldsm4(A[4 * k + kk], base + s * 16384 + wg * 8192 + (roff ^ (kk * 32)));
      bar_sync(1 + wg, 128);
      release(s);
      if (++s == PST) { s = 0; ph ^= 1; }
    }
  }
  if (tid == 0) CT(0, 0)
  if (wg) bar_sync(5, 256);
  bool ok = false;
  for (int t = 0; t < nt; t++, c ^= 1) {
    uint32_t p1 = 0;
#pragma unroll
    for (int k = 0; k < 9; k++) {
      if (k < 8 || pa) {
        if (!ok) mbar_wait(full + 8 * s, ph);
        const uint64_t db = desc_mn(base + s * 16384, 8192);
        wg_fence();
#pragma unroll
        for (int kk = 0; kk < 4; kk++) wg_rs128<1>(acc, A[4 * k + kk], db + kk * 128, k | kk);
        wg_commit();
        const uint32_t cur = s;
        if (++s == PST) { s = 0; ph ^= 1; }
        ok = mbar_test(full + 8 * s, ph);
        if (k) { wg_wait<1>(); release(p1); }
        if (k == 4 && t == 0 && !wg) bar_arrive(5, 256);
        p1 = cur;
      }
    }
    mwait(base + P_OE + 8 * wg, c);
    wg_wait<0>();
    release(p1);
#pragma unroll
    for (int i = 0; i < 8; i++) {
      const float* a = acc + i * 8;
      stsm4(base + P_STG + wg * 16384 + (i >> 2) * 8192 + (roff ^ ((i & 3) * 32)), pack2(a[0], a[1]), pack2(a[2], a[3]), pack2(a[4], a[5]), pack2(a[6], a[7]));
    }
    fence_async();
    __syncwarp();
    if ((tid & 31) == 0) mbar_arrive(base + P_OF + 8 * wg);
  }
}

struct OutMaps { CUtensorMap a, b, c; };
template <int NST, bool PAIR, int G> DEVI void out_produce(const OutMaps& M, uint32_t base, uint32_t full, int m, int n, int k0, int nk, int flag) {
  constexpr int SB = 16384 + 384 * G;
  constexpr bool MC = PAIR && G == 64;
  const int r = MC ? blockIdx.x & 1 : 0;
  int s = 0, ph = !PAIR;
#pragma unroll 1
  for (int k = 0; k < nk + (PAIR ? NST - 1 : 0); k++) {
    mbar_wait(full + 8 * (NST + s), ph);
    if (k < nk) {
      mbar_expect(full + 8 * s, SB);
      if (flag >= 0) tma_load3(base + s * SB + 16384, &M.b, (k0 + k) * 64, n * 3, full + 8 * s);
      else
#pragma unroll 1
      for (int j = 0; j < 3; j++) {
        if (MC) tma_load_mc(base + s * SB + 16384 + j * 128 * G + r * 64 * G, &M.b, (n * 3 + j) * G, k * 64 + r * 32, full + 8 * s, 3);
        else tma_load(base + s * SB + 16384 + j * 128 * G, &M.b, (n * 3 + j) * G, (k0 + k) * 64, full + 8 * s);
      }
      if (flag >= 0 && k == 0) flag_wait(flag, 64, 30);
      if (flag >= 0) tma_load(base + s * SB, &M.a, (k0 + k) * 64, m * 128, full + 8 * s);
    }
    if (++s == NST) { s = 0; ph ^= 1; }
  }
}
template <int NST, bool PAIR, int G> DEVI void out_rows(const OutMaps& M, uint32_t base, uint32_t full, int m, int flag, int cnt, int waiters) {
  flag_wait(flag, cnt, waiters);
  int s = 0, ph = !PAIR;
#pragma unroll 1
  for (int k = 0; k < 64; k++) {
    if (k == cnt) mbar_wait(full + 16 * NST, 0);
    mbar_wait(full + 8 * (NST + s), ph);
    if (PAIR && G == 32) tma_load_mc(base + s * (16384 + 384 * G) + (blockIdx.x & 1) * 8192, &M.a, k * 64, m * 128 + (blockIdx.x & 1) * 64, full + 8 * s, 3);
    else tma_load(base + s * (16384 + 384 * G), &M.a, k * 64, m * 128, full + 8 * s);
    if (++s == NST) { s = 0; ph ^= 1; }
  }
}
template <int NST, bool PAIR, int G> DEVI void out_consume(float* acc, uint32_t base, uint32_t full, int nk) {
  constexpr int SB = 16384 + 384 * G;
  const uint32_t empty = full + 8 * NST;
  const int wg = threadIdx.x >> 7;
  int s = 0, ph = 0, prev = 0;
#pragma unroll 1
  for (int k = 0; k < nk; k++) {
    mbar_wait(full + 8 * s, ph);
    const uint64_t da = desc_k(base + s * SB + wg * 8192), db = mkdesc(base + s * SB + 16384, 128 * G, 16 * G, G == 64 ? 1 : 2);
    wg_fence();
#pragma unroll
    for (int kk = 0; kk < 4; kk++) {
      if (G == 64) wg_ss192<1>(acc, da + kk * 2, db + kk * 128, k | kk);
      else wg_ss96t(acc, da + kk * 2, db + kk * 64, k | kk);
    }
    wg_commit();
    if (k) { wg_wait<1>(); if (PAIR) arrive_pair(empty + 8 * prev); else if ((threadIdx.x & 127) == 0) mbar_arrive(empty + 8 * prev); }
    prev = s;
    if (++s == NST) { s = 0; ph ^= 1; }
  }
  wg_wait<0>();
}
template <int NST, bool PAIR, int G> DEVI void out_tile(const OutMaps& M, uint32_t base, uint32_t full, int m, int n) {
  const int tid = threadIdx.x, wg = tid >> 7;
  float acc[G * 3 / 2];
  out_consume<NST, PAIR, G>(acc, base, full, 64);
  bar_sync(6, 256);
  const uint32_t row = ((tid >> 5) & 3) * 16 + (tid & 15);
  const uint32_t roff = row * 2 * G + ((((tid >> 4) & 1) ^ (G == 64 ? row & 7 : (row >> 1) & 3)) << 4);
#pragma unroll
  for (int i = 0; i < G * 3 / 16; i++) {
    const float* a = acc + i * 8;
    stsm4(base + wg * 384 * G + i / (G / 16) * 128 * G + (roff ^ (i % (G / 16) * 32)), pack2(a[0], a[1]), pack2(a[2], a[3]), pack2(a[4], a[5]), pack2(a[6], a[7]));
  }
  fence_async();
  bar_sync(1 + wg, 128);
  if ((tid & 127) == 0) {
#pragma unroll 1
    for (int c = 0; c < 3; c++) tma_store(&M.c, base + wg * 384 * G + c * 128 * G, (n * 3 + c) * G, m * 128 + wg * 64);
    bulk_commit();
    bulk_wait_read<0>();
  }
}
struct OutParams { OutMaps p[2]; int n, odd; uint8_t tile[64]; };
constexpr int SM_O = 6 * 28672 + 256;
__global__ void __launch_bounds__(384, 1) out_kernel(const __grid_constant__ OutParams P) {
  extern __shared__ __align__(1024) uint8_t smem_raw[];
  const uint32_t base = s2u(smem_raw), full = base + 6 * 28672;
  const int tid = threadIdx.x, t = P.tile[blockIdx.x], half = t >> 7, m = (t >> 3) & 15, n = t & 7;
  TL_START(4)
  pdl_trigger();
  if (tid == 0) {
    for (int i = 0; i < 12; i++) mbar_init(full + 8 * i, i >= 4 + 2 * half ? 2 : 1);
    asm volatile("fence.mbarrier_init.release.cluster;" ::: "memory");
  }
  __syncthreads();
  if (tid >= 256) {
    if (tid == 256) { if (half) out_produce<6, false, 32>(P.p[1], base, full, m, n, 0, 64, -1); else out_produce<4, false, 64>(P.p[0], base, full, m, n, 0, 64, -1); }
    if (tid == 288) { if (half) out_rows<6, false, 32>(P.p[1], base, full, m, S_CTXB + m, 64, 4); else out_rows<4, false, 64>(P.p[0], base, full, m, S_CTXB + m, 64, 3 + (m == P.odd)); }
  } else {
    if (tid == 0) CT(4, 0)
    if (half) out_tile<6, false, 32>(P.p[1], base, full, m, n); else out_tile<4, false, 64>(P.p[0], base, full, m, n);
    if (tid == 0) CT(4, 2)
    TL_END(4)
  }
}
struct FaParams { ProjParams p; CUtensorMap q, k, v, o; unsigned proj, nctas, ngroups; uint8_t nproj[12]; uint16_t order[512];
                  OutMaps om[3]; uint16_t tile[96]; };
constexpr int HST = 5, F_OUT = 7 * 32768 + 512, F_OUTH = F_OUT + 72, F_TILE = F_OUTH + 16 * HST, SM_F = F_OUT + 256;
constexpr float FA_C = 0.08838834764831845f * 1.4426950408889634f;
DEVI int fa_qt(int w) { return w >> 5; }
DEVI int fa_hc(int w) { return (w & 31) * 128; }

DEVI void fa_exp(const float* S, uint32_t* Pn, float mc0, float mc1, float& s0, float& s1) {
  float a0 = 0.f, a1 = 0.f, b0 = 0.f, b1 = 0.f;
#pragma unroll
  for (int j = 0; j < 16; j++) {
    const float e0 = ex2(fmaf(S[4 * j], FA_C, -mc0)), e1 = ex2(fmaf(S[4 * j + 1], FA_C, -mc0));
    const float e2 = ex2(fmaf(S[4 * j + 2], FA_C, -mc1)), e3 = ex2(fmaf(S[4 * j + 3], FA_C, -mc1));
    a0 += e0; a1 += e1; b0 += e2; b1 += e3;
    Pn[2 * j] = pack2(e0, e1); Pn[2 * j + 1] = pack2(e2, e3);
  }
  s0 = a0 + a1; s1 = b0 + b1;
}

struct FaState { float mc0, mc1, l0, l1; int w, j, qi; uint32_t dq; bool first; };
enum { F_Q = 0, F_K = 2 * 32768, F_V = 4 * 32768, F_O = 6 * 32768, F_QF = 7 * 32768, F_QE = F_QF + 16, F_KF = F_QF + 32, F_KE = F_QF + 48, F_VF = F_QF + 64, F_VE = F_QF + 80,
       F_OF = F_QF + 96, F_OE = F_QF + 112, F_INFO = F_QF + 128 };

DEVI void out_open(uint32_t base, int tid, uint32_t mask) {
  const int s = (tid & 127) >> 1;
  if (s < 4 + HST && ((mask >> s) & 1))
    asm volatile("mbarrier.arrive.shared::cluster.b64 _,[%0];" ::"r"(mapa(base + (s < 4 ? F_OUT + 32 : F_OUTH + 8 * HST - 32) + 8 * s, tid & 1)) : "memory");
}
template <int SC> DEVI bool fa_step(FaState& T, float* O, float* S, const uint32_t* Pc, uint32_t* Pn, uint32_t base, int tid, int wg, uint32_t ph) {
  const bool el = (tid & 127) == 0, fin = T.j == 0;
  int wn = T.w, jn = T.j - 1;
  const bool okk = mbar_try(base + F_KF + 8 * (SC ^ 1), ph), okv = mbar_try(base + F_VF + 8 * SC, ph ^ SC);
  if (fin) {
    T.qi++; T.dq ^= 2048;
    mbar_wait(base + F_QF + 8 * (T.qi & 1), (T.qi >> 1) & 1);
    asm volatile("ld.shared.b32 %0,[%1];" : "=r"(wn) : "r"(base + F_INFO + (T.qi & 1) * 4) : "memory");
    wn = __shfl_sync(~0u, wn, 0);
    jn = fa_qt(wn);
    if (wn < 0) out_open(base, tid, 0xf7);
  }
  if (!(okk && okv)) { mbar_wait(base + F_KF + 8 * (SC ^ 1), ph); mbar_wait(base + F_VF + 8 * SC, ph ^ SC); }
  const bool last = wn < 0;
  {
    const uint64_t dq = desc_k(0) | T.dq, dk = desc_k(base + F_K + (SC ^ 1) * 32768), dv = desc_mn(base + F_V + SC * 32768, 16384);
    bar_sync(3 + wg, 256);
    wg_fence();
#pragma unroll
    for (int kk = 0; kk < 8; kk++) wg_ss128<0>(S, dq + (kk & 3) * 2 + (kk >> 2) * 1024, dk + (kk & 3) * 2 + (kk >> 2) * 1024, kk);
    wg_commit();
#pragma unroll
    for (int kk = 0; kk < 8; kk++) wg_rs128<1>(O, Pc + 4 * kk, dv + kk * 128, kk || !T.first);
    wg_commit();
    bar_arrive(4 - wg, 256);
  }
  wg_wait<1>();
  asm volatile("{.reg .pred p,q; setp.ne.u32 p,%0,0; setp.eq.and.u32 q,%1,0,p; @p mbarrier.arrive.shared::cta.b64 _,[%2]; @q mbarrier.arrive.shared::cta.b64 _,[%3];}"
               ::"r"((uint32_t)el), "r"(jn), "r"(base + F_KE + 8 * (SC ^ 1)), "r"(base + F_QE + 8 * (T.qi & 1)) : "memory");
  const float lp0 = T.l0, lp1 = T.l1;
  float s0 = 0.f, s1 = 0.f, f0 = 1.f, f1 = 1.f;
  bool exact = fin;
  if (!fin) {
    fa_exp(S, Pn, T.mc0, T.mc1, s0, s1);
    exact = __any_sync(~0u, !(fmaxf(s0, s1) <= 1073741824.f));
  }
  if (exact && !last) {
    float a = -INFINITY, b = -INFINITY;
    if (fin) {
      const int row = (tid >> 5) * 16 + ((tid & 31) >> 2) - (tid & 3) * 2;
#pragma unroll
      for (int j = 0; j < 16; j++) {
        if (j * 8 > row) S[4 * j] = -INFINITY;
        if (j * 8 + 1 > row) S[4 * j + 1] = -INFINITY;
        if (j * 8 > row + 8) S[4 * j + 2] = -INFINITY;
        if (j * 8 + 1 > row + 8) S[4 * j + 3] = -INFINITY;
      }
      T.mc0 = T.mc1 = -INFINITY;
    }
#pragma unroll
    for (int j = 0; j < 16; j++) { a = fmaxf(a, fmaxf(S[4 * j], S[4 * j + 1])); b = fmaxf(b, fmaxf(S[4 * j + 2], S[4 * j + 3])); }
    a = fmaxf(a, __shfl_xor_sync(~0u, a, 1)); b = fmaxf(b, __shfl_xor_sync(~0u, b, 1));
    a = fmaxf(a, __shfl_xor_sync(~0u, a, 2)); b = fmaxf(b, __shfl_xor_sync(~0u, b, 2));
    a = fmaxf(a * FA_C, T.mc0); b = fmaxf(b * FA_C, T.mc1);
    f0 = ex2(T.mc0 - a); f1 = ex2(T.mc1 - b);
    T.mc0 = a; T.mc1 = b;
    T.l0 = fin ? 0.f : T.l0 * f0; T.l1 = fin ? 0.f : T.l1 * f1;
    fa_exp(S, Pn, a, b, s0, s1);
  }
  T.l0 += s0; T.l1 += s1;
  wg_wait<0>();
  if (el) mbar_arrive(base + F_VE + 8 * SC);
  if (exact) {
    if (fin) {
      f0 = lp0 + __shfl_xor_sync(~0u, lp0, 1); f1 = lp1 + __shfl_xor_sync(~0u, lp1, 1);
      f0 += __shfl_xor_sync(~0u, f0, 2); f1 += __shfl_xor_sync(~0u, f1, 2);
      f0 = 1.f / f0; f1 = 1.f / f1;
    }
#pragma unroll
    for (int i = 0; i < 16; i++) { O[4 * i] *= f0; O[4 * i + 1] *= f0; O[4 * i + 2] *= f1; O[4 * i + 3] *= f1; }
    if (fin && (T.qi || last)) {
      const uint32_t row = ((tid >> 5) & 3) * 16 + (tid & 15);
      const uint32_t o = base + F_O + wg * 16384 + row * 128 + ((((tid >> 4) & 1) ^ (row & 7)) << 4);
      if (T.qi) mbar_wait(base + F_OE + 8 * wg, (T.qi & 1) ^ 1);
#pragma unroll
      for (int i = 0; i < 8; i++) {
        const float* a = O + i * 8;
        stsm4((o ^ ((i & 3) * 32)) + (i >> 2) * 8192, pack2(a[0], a[1]), pack2(a[2], a[3]), pack2(a[4], a[5]), pack2(a[6], a[7]));
      }
      if (el) asm volatile("st.shared.b32 [%0],%1;" ::"r"(base + F_INFO + 8 + wg * 4), "r"(!T.qi ? -1 : T.w | (last ? 1024 : 0)) : "memory");
      fence_async();
      __syncwarp();
      if ((tid & 31) == 0) mbar_arrive(base + F_OF + 8 * wg);
    }
  }
  T.w = wn; T.j = jn; T.first = fin;
  return last;
}

__global__ void __launch_bounds__(384, 1) fa_kernel(const __grid_constant__ FaParams P) {
  extern __shared__ __align__(1024) uint8_t smem_raw[];
  const uint32_t base = __shfl_sync(~0u, s2u(smem_raw), 0);
  const uint32_t sQ = base, sK = base + 2 * 32768, sV = base + 4 * 32768, sO = base + 6 * 32768, bars = base + 7 * 32768;
  const uint32_t qf = bars, qe = bars + 16, kf = bars + 32, ke = bars + 48, vf = bars + 64, ve = bars + 80, of = bars + 96, oe = bars + 112;
  volatile int* info = (volatile int*)(smem_raw + 7 * 32768 + 128);
  const int tid = threadIdx.x, wg = tid >> 7;
  const ProjItem& I = P.p.item[blockIdx.x >> 1];
  const bool leave = P.proj && I.leave;
  auto my_tile = [&]() { mbar_wait(base + F_TILE, 0); return info[5]; };
  pdl_trigger();
  if (tid == 0) {
    if (P.proj) proj_init(I, base);
    for (int i = 0; i < 16; i++) mbar_init(bars + 8 * i, i >= 14 ? 1 : i >= 12 ? 4 : (i & 2) ? 2 : 1);
    for (int i = 0; i < 10 + 2 * HST; i++) mbar_init(base + F_OUT + 8 * i, (i >= 4 && i < 8) || (i >= 9 + HST && i < 9 + 2 * HST) ? 4 : 1);
    mbar_expect(base + F_TILE, 4);
    info[4] = 0;
    asm volatile("fence.mbarrier_init.release.cluster;" ::: "memory");
  }
  __syncthreads();
  cluster_sync_relaxed();
  if (wg == 2) {
    reg_dec<24>();
    if (tid == 256) {
      int it = 0, qi = 0, vc = 0, vr = -1, j = 0, hc = 0;
      int pph = P.proj ? proj_produce(P.p, I, base) : -1;
      auto drain = [&](int s0) { if (pph >= 0) for (int i = s0; i < s0 + 6; i++) mbar_wait(base + P_EMPTY + 8 * i, pph); };
      if (leave) { drain(0); drain(6); return; }
      CT(P.proj ? 3 : 6, 0)
      auto load_v = [&]() {
        if (vr < 0) return;
        const int s = (it - 1) & 1;
        drain(6); pph = -1;
        mbar_wait(ve + 8 * s, (((it - 1) >> 1) & 1) ^ 1 ^ s);
        mbar_expect(vf + 8 * s, 32768);
        tma_load(sV + s * 32768, &P.v, vc, vr, vf + 8 * s);
        tma_load(sV + s * 32768 + 16384, &P.v, vc + 64, vr, vf + 8 * s);
        vr = -1;
      };
      auto ready = [&](uint32_t m) { uint32_t v; asm volatile("ld.acquire.cta.shared.b32 %0,[%1];" : "=r"(v) : "r"(base + F_INFO + 16) : "memory"); return (v & m) == m; };
      for (it = -1;; it++) {
        if (it >= 0) {
          const int s = it & 1;
          if (it || j < 0) { drain(6); pph = -1; }
          mbar_wait(ke + 8 * s, ((it >> 1) & 1) ^ 1);
          if (j < 0) { mbar_arrive(kf + 8 * s); load_v(); break; }
          mbar_expect(kf + 8 * s, 32768);
          tma_load(sK + s * 32768, &P.k, hc, j * 128, kf + 8 * s);
          tma_load(sK + s * 32768 + 16384, &P.k, hc + 64, j * 128, kf + 8 * s);
        }
        int nc = hc, nr = it >= 0 ? j * 128 : -1;
        if (j-- == 0) {
          int w = atomicInc(&g_sync[S_QUEUE], 511 + P.nctas);
          w = w < 512 ? P.order[w] : -1;
          const uint32_t q = qi & 1, m = w < 0 ? 0x3ffff : (1u | (2u << (fa_qt(w) | 1))) << ((w >> 4) & 1);
          if (!ready(m) || !mbar_test(qe + 8 * q, ((qi >> 1) & 1) ^ 1)) {
            load_v(); it++; vc = nc; vr = nr; load_v(); it--; nr = -1;
            for (int n = 0; !ready(m) && n < WAIT_MAX; n++) __nanosleep(64);
            mbar_wait(qe + 8 * q, ((qi >> 1) & 1) ^ 1);
          }
          asm volatile("fence.proxy.async.global;" ::: "memory");
          if (it < 0) drain(0);
          info[q] = w;
          if (w < 0) mbar_arrive(qf + 8 * q);
          else {
            j = fa_qt(w); hc = fa_hc(w);
            mbar_expect(qf + 8 * q, 32768);
            tma_load(sQ + q * 32768, &P.q, hc, j * 128, qf + 8 * q);
            tma_load(sQ + q * 32768 + 16384, &P.q, hc + 64, j * 128, qf + 8 * q);
          }
          qi++;
        }
        load_v();
        vc = nc; vr = nr;
      }
      const int tile = my_tile(), kind = tile >> 7, tm = (tile >> 3) & 15, tn = tile & 7;
      if (atomicInc(&g_sync[S_EXIT], P.nctas - 1) == P.nctas - 1) {
#pragma unroll 1
        for (int i = S_LIST; i < S_PROJ + 18; i++) g_sync[i] = 0;
#pragma unroll 1
        for (int i = 0; i < 16; i++) ((uint4*)g_group)[i] = make_uint4(0, 0, 0, 0);
      }
      if (kind == 2) out_produce<HST, true, 32>(P.om[2], base, base + F_OUTH, tm, tn, 0, 64, -1);
      else if (kind < 2) out_produce<4, true, 64>(P.om[kind], base, base + F_OUT, tm, tn, 0, 64, -1);
      else { mbar_wait(base + F_OUT + 56, 0); mbar_wait(base + F_TILE - 8, 0); }
    } else if (tid >= 352) {
      const int l = tid - 352;
      if (P.proj) mbar_wait(base + P_END, 0);
#pragma unroll 1
      for (int n = 0; n < WAIT_MAX && !leave; n++) {
        unsigned v = 255;
        if (l < 18) asm volatile("ld.acquire.gpu.global.u32 %0, [%1];" : "=r"(v) : "l"(g_sync + S_PROJ + l) : "memory");
        const uint32_t m = __ballot_sync(~0u, v >= P.nproj[(l >> 1) % 9]);
        __syncwarp();
        if (l == 0) asm volatile("st.release.cta.shared.b32 [%0],%1;" ::"r"(base + F_INFO + 16), "r"(m) : "memory");
        if (m == ~0u) break;
        __nanosleep(300);
      }
      if (l == 0 && !(blockIdx.x & 1) && !leave) {
        unsigned sm; asm("mov.u32 %0,%%smid;" : "=r"(sm));
        unsigned g = *(volatile uint8_t*)&g_group[sm & 255] - 1u, i;
        if (g > P.ngroups) g = P.ngroups;
        while ((i = g * 8 + atomicAdd(&g_sync[S_LIST + g], 1)) >= (g < P.ngroups ? g * 8 + 8 : P.nctas / 2)) g = g ? g - 1 : P.ngroups;
        for (int r = 0; r < 2; r++)
          asm volatile("st.async.weak.shared::cluster.mbarrier::complete_tx::bytes.b32 [%0],%1,[%2];" ::"r"(mapa(base + F_INFO + 20, r)), "r"((int)P.tile[i * 2 + r]), "r"(mapa(base + F_TILE, r)) : "memory");
      }
      if (l == 0 && !leave) {
        const int tile = my_tile(), kind = tile >> 7, tm = (tile >> 3) & 15;
        mbar_wait(base + (kind == 2 ? F_OUTH + 8 * HST : F_OUT + 32), 0);
        if (kind == 2) out_rows<HST, true, 32>(P.om[2], base, base + F_OUTH, tm, S_CTXB + tm, 64, 6);
        else if (kind < 2) out_rows<4, true, 64>(P.om[kind], base, base + F_OUT, tm, (kind ? S_CTXB : S_CTXA) + tm, kind ? 64 : 32, 3);
      }
    } else if (tid == 288 || tid == 320) {
      const int g = tid == 320;
      if (P.proj) proj_store(P.p, I, base, g);
      if (leave) return;
      mbar_arrive(oe + 8 * g);
        for (int n = 0;; n++) {
          mbar_wait(of + 8 * g, n & 1);
          const int v = info[2 + g], w = v & 1023, qt = fa_qt(w), hc = fa_hc(w);
          if (v < 0) break;
          tma_store(&P.o, sO + g * 16384, hc, qt * 128 + g * 64);
          tma_store(&P.o, sO + g * 16384 + 8192, hc + 64, qt * 128 + g * 64);
          bulk_commit();
          bulk_wait_read<0>();
          mbar_arrive(oe + 8 * g);
          bulk_wait<0>();
          signal_after_bulk(S_CTXA + (w & 16) + qt);
          if (v & 1024) break;
        }
      if (!g && my_tile() < 128) { flag_wait(S_CTXA + 16 + (info[5] >> 3), 32, 3); mbar_arrive(base + F_OUT + 64); }
    }
  } else {
    reg_inc<240>();
    const uint32_t ub = base;
    const int uw = __shfl_sync(~0u, wg, 0);
    if (wg == 1 && !leave) bar_arrive(3, 256);
    if (P.proj) proj_consume(I, ub, tid, uw);
    if (leave) return;
    float O[64], S[64];
    uint32_t PA[32], PB[32];
#pragma unroll
    for (int i = 0; i < 32; i++) PA[i] = 0;
#pragma unroll
    for (int i = 0; i < 64; i++) O[i] = 0.f;
    FaState T = {0.f, 0.f, 1.f, 1.f, 0, 0, -1, ((ub + 32768 + uw * 8192) >> 4) & 0x3fff, true};
    for (uint32_t ph = 0;; ph ^= 1) {
      if (fa_step<1>(T, O, S, PA, PB, ub, tid, uw, ph)) break;
      if (fa_step<0>(T, O, S, PB, PA, ub, tid, uw, ph)) break;
    }
    if (wg == 0) bar_sync(3, 256);
    out_open(ub, tid, ~0xf7u);
    const int tile = __shfl_sync(~0u, my_tile(), 0), kind = tile >> 7, tm = (tile >> 3) & 15, tn = tile & 7;
    if (tid == 0) CT(P.proj ? 5 : 2, 0)
    TL_START(5)
    if (kind == 2) out_tile<HST, true, 32>(P.om[2], ub, ub + F_OUTH, tm, tn);
    else if (kind < 2) out_tile<4, true, 64>(P.om[kind], ub, ub + F_OUT, tm, tn);
    if (tid == 0) CT(P.proj ? 5 : 2, 2)
    TL_END(kind == 2 ? 2 : 5)
  }
}
#define PS 20
#define PT(i)
#define YD 200
#define NPF 4
#define NRES 6
#define RP 208
#define PD 2
#define VR "............rrrrrr.................."
#define VP "222222222222111111111111------------"
constexpr int vr_index(int k) { int n = 0; for (int i = 0; i < k; i++) n += VR[i] == 'r'; return n; }
constexpr int VB = vr_index(36);
template <int K> struct VIdx { static constexpr int v = vr_index(K); static constexpr char r = VR[K], p = VP[K]; };
#define XG 6
#define XW 2
#define WOD 2000
#define KA 26
constexpr int R_WV = 0, R_WO = 73728, R_H = 147456, R_OX = R_H + 46080, R_Q = R_OX + 4096, R_K = R_Q + 5120, R_SX = R_K + 5120, R_P = R_SX + 3200, R_U = R_P + 3200,
              R_BAR = R_H + 73728, R_PROF = R_BAR + 256, R_END = R_PROF + 3072;
constexpr int B_W0 = R_BAR, B_W1 = R_BAR + 8, B_XA = R_BAR + 16, B_XB = R_BAR + 24, B_XF = R_BAR + 32, B_Z0 = R_BAR + 40, B_Z1 = R_BAR + 48, B_R = R_BAR + 56,
              B_SM = R_BAR + 64, B_SX = R_BAR + 72, B_U = R_BAR + 80, B_V = R_BAR + 88, B_W2 = R_BAR + 96, B_W3 = R_BAR + 104, B_O = R_BAR + 112;
static_assert(R_U + 4096 <= R_BAR, "");
enum { N_P1 = 1, N_PM, N_PX, N_SUM, N_O, N_INIT, N_INIT1, N_INIT2, N_WO, N_S };
constexpr int YSLOT = 9 * 16 * 1024;
struct RecParams { CUtensorMap wq, wk, wv, wo, x, ctx; OutMaps o; const bf16 *mem0, *x_raw; bf16* out; };
constexpr int TAIL0 = 14;
constexpr int TST = 6, R_RED = TST * 28672;

DEVI void wg_rs32(float* d, const uint32_t* a, uint64_t db, int acc) {
  asm volatile("{.reg .pred p; setp.ne.b32 p,%21,0;\n wgmma.mma_async.sync.aligned.m64n32k16.f32.bf16.bf16 {%0,%1,%2,%3,%4,%5,%6,%7,%8,%9,%10,%11,%12,%13,%14,%15},{%16,%17,%18,%19},%20,p,1,1,0;}"
               : F8(d, 0), F8(d, 8) : "r"(a[0]), "r"(a[1]), "r"(a[2]), "r"(a[3]), "l"(db), "r"(acc));
}
DEVI void wg_rs40(float* d, const uint32_t* a, uint64_t db, int acc) {
  asm volatile("{.reg .pred p; setp.ne.b32 p,%25,0;\n wgmma.mma_async.sync.aligned.m64n40k16.f32.bf16.bf16 {%0,%1,%2,%3,%4,%5,%6,%7,%8,%9,%10,%11,%12,%13,%14,%15,%16,%17,%18,%19},{%20,%21,%22,%23},%24,p,1,1,0;}"
               : F8(d, 0), F8(d, 8), "+f"(d[16]), "+f"(d[17]), "+f"(d[18]), "+f"(d[19]) : "r"(a[0]), "r"(a[1]), "r"(a[2]), "r"(a[3]), "l"(db), "r"(acc));
}
template <int TB> DEVI void wg_ss40(float* d, uint64_t da, uint64_t db, int acc) {
  asm volatile("{.reg .pred p; setp.ne.b32 p,%22,0;\n wgmma.mma_async.sync.aligned.m64n40k16.f32.bf16.bf16 {%0,%1,%2,%3,%4,%5,%6,%7,%8,%9,%10,%11,%12,%13,%14,%15,%16,%17,%18,%19},%20,%21,p,1,1,1,%23;}"
               : F8(d, 0), F8(d, 8), "+f"(d[16]), "+f"(d[17]), "+f"(d[18]), "+f"(d[19]) : "l"(da), "l"(db), "r"(acc), "n"(TB));
}
DEVI void mma8(float* d, uint32_t a0, uint32_t a1, uint32_t b0) {
  asm volatile("mma.sync.aligned.m16n8k8.row.col.f32.bf16.bf16.f32 {%0,%1,%2,%3},{%4,%5},{%6},{%0,%1,%2,%3};" : "+f"(d[0]), "+f"(d[1]), "+f"(d[2]), "+f"(d[3]) : "r"(a0), "r"(a1), "r"(b0));
}
DEVI void stsm4t(uint32_t a, uint32_t r0, uint32_t r1, uint32_t r2, uint32_t r3) {
  asm volatile("stmatrix.sync.aligned.m8n8.x4.trans.shared.b16 [%0],{%1,%2,%3,%4};" ::"r"(a), "r"(r0), "r"(r1), "r"(r2), "r"(r3) : "memory");
}
DEVI uint32_t movm(uint32_t a) { uint32_t d; asm volatile("movmatrix.sync.aligned.m8n8.trans.b16 %0,%1;" : "=r"(d) : "r"(a)); return d; }
DEVI void sts1(uint32_t a, uint32_t v) { asm volatile("st.shared.b32 [%0],%1;" ::"r"(a), "r"(v) : "memory"); }
DEVI uint32_t lds1(uint32_t a) { uint32_t v; asm volatile("ld.shared.b32 %0,[%1];" : "=r"(v) : "r"(a) : "memory"); return v; }
DEVI void sta1(uint32_t d, uint32_t a, uint32_t bar) { asm volatile("st.async.weak.shared::cluster.mbarrier::complete_tx::bytes.b32 [%0],%1,[%2];" ::"r"(d), "r"(a), "r"(bar) : "memory"); }
DEVI void sta2(uint32_t d, uint32_t a, uint32_t b, uint32_t bar) { asm volatile("st.async.weak.shared::cluster.mbarrier::complete_tx::bytes.v2.b32 [%0],{%1,%2},[%3];" ::"r"(d), "r"(a), "r"(b), "r"(bar) : "memory"); }
DEVI uint32_t clk32() { uint64_t c; asm volatile("mov.u64 %0,%%clock64;" : "=l"(c)::"memory"); return (uint32_t)c; }
DEVI int opq(int x) { asm volatile("" : "+r"(x)); return x; }
DEVI int pin(int x) { return __shfl_sync(~0u, x, threadIdx.x & 31); }
DEVI void x_load(const RecParams& P, uint32_t sb, int c, int seg) {
  asm volatile("cp.async.bulk.tensor.2d.shared::cluster.global.mbarrier::complete_tx::bytes.multicast::cluster [%0],[%1,{%3,%4}],[%2],%5;"
               ::"r"(sb + R_H + c * 5120 + 1024), "l"(&P.x), "r"(sb + (c < XG ? B_XA : B_XB)), "r"(c * 64), "r"(seg * 32), "h"((uint16_t)0xffff) : "memory");
  if (seg + 2 < NSEG) asm volatile("cp.async.bulk.prefetch.tensor.2d.L2.global [%0,{%1,%2}];" ::"l"(&P.x), "r"(c * 64), "r"(seg * 32 + 64) : "memory");
}
DEVI uint32_t hadd2(uint32_t a, uint32_t b) { uint32_t r; asm("add.rn.bf16x2 %0,%1,%2;" : "=r"(r) : "r"(a), "r"(b)); return r; }
DEVI uint32_t hmax2(uint32_t a, uint32_t b) { uint32_t r; asm("max.bf16x2 %0,%1,%2;" : "=r"(r) : "r"(a), "r"(b)); return r; }
DEVI float rcp(float x) { float y; asm("rcp.approx.ftz.f32 %0,%1;" : "=f"(y) : "f"(x)); return y; }
constexpr float SCL = 0.08838834764831845f * 1.4426950408889634f;

DEVI void y_store(const float* a, uint32_t off, int s) {
  const uint32_t x = movm(pack2(a[0], a[1])), y = movm(pack2(a[2], a[3]));
  const uint32_t tag = ((s >> 1) & 1) ^ 1;
  asm volatile("st.relaxed.gpu.global.b64 [%0],%1;" ::"l"((uint8_t*)g_Y + (s & 1) * YSLOT + off), "l"((uint64_t)((x & ~1u) | tag) | ((uint64_t)y << 32)) : "memory");
}
DEVI void y_load(uint32_t* w, const uint8_t* p) {
#pragma unroll
  for (int i = 0; i < 4; i++) asm volatile("{.reg .b64 t; ld.relaxed.gpu.global.b64 t,[%2]; mov.b64 {%0,%1},t;}" : "=r"(w[2 * i]), "=r"(w[2 * i + 1]) : "l"(p + i * 256) : "memory");
}
DEVI bool y_missing(const uint32_t* w, uint32_t tag) {
  uint32_t r;
  asm volatile("{.reg .b32 a,b; .reg .pred p; lop3.b32 a,%1,%2,%5,0x7e; lop3.b32 b,%3,%4,%5,0x7e; lop3.b32 a,a,b,1,0xa8; setp.ne.u32 p,a,0; vote.sync.any.pred p,p,0xffffffff; selp.u32 %0,1,0,p;}"
               : "=r"(r) : "r"(w[0]), "r"(w[2]), "r"(w[4]), "r"(w[6]), "r"(tag));
  return r;
}
DEVI void y_reload(uint32_t* w, const uint8_t* p, uint32_t tag) {
#pragma unroll
  for (int i = 0; i < 4; i++)
    asm volatile("{.reg .b64 t; .reg .b32 a; .reg .pred q; lop3.b32 a,%0,%3,1,0x28; setp.ne.u32 q,a,0; mov.b64 t,{%0,%1}; @q ld.relaxed.gpu.global.b64 t,[%2]; mov.b64 {%0,%1},t;}"
                 : "+r"(w[2 * i]), "+r"(w[2 * i + 1]) : "l"(p + i * 256), "r"(tag) : "memory");
}
DEVI void y_sum(uint32_t* r, const uint32_t* w, uint32_t sel) {
  float d0[4] = {0, 0, 0, 0}, d1[4] = {0, 0, 0, 0};
  mma16(d0, w[0], w[1], w[2], w[3], sel, sel); mma16(d1, w[4], w[5], w[6], w[7], sel, sel);
  r[0] = pack2(d0[0] + d1[0], d0[1] + d1[1]); r[1] = pack2(d0[2] + d1[2], d0[3] + d1[3]);
}
DEVI void y_send(const uint32_t* r, uint32_t sb, uint32_t dst, uint32_t bar, int lane) {
#pragma unroll
  for (int i = 0; i < 4; i++) { const uint32_t rs = mapa(sb, (lane & 3) + i * 4); sta2(rs + dst, r[0], r[1], rs + bar); }
}
DEVI void wo_convert(uint32_t sb, int lane, int warp) {
  TL_END(11)
  mbar_wait(sb + B_W3, 0);
  TL_END(9)
#pragma unroll 1
  for (uint32_t a = sb + R_WO + warp * 4608; a < sb + R_H; a += 8 * 4608) {
    uint32_t r[9][4];
#pragma unroll
    for (int k = 0; k < 9; k++) ldsm4t(r[k], a + k * 32 + ((lane & 7) + (lane >> 4) * 8) * 288 + ((lane >> 3) & 1) * 16);
    __syncwarp();
#pragma unroll
    for (int k = 0; k < 9; k++) stsm4(a + k * 512 + ((lane >> 4) * 2 + ((lane >> 1) & 1)) * 128 + (((lane >> 2) & 3) * 2 + (lane & 1)) * 16, r[k][0], r[k][1], r[k][2], r[k][3]);
  }
  __syncwarp();
}
DEVI uint32_t y_offset(int cta, int tile, int lane) {
  const int T = (cta & 3) * 9 + tile;
  return (((T >> 2) * 8 + (lane >> 2)) * 2 + ((T >> 1) & 1)) * 1024 + (cta >> 4) * 256 + (T & 1) * 128 + ((cta >> 2) & 3) * 32 + (lane & 3) * 8;
}
template <int NR, int NP> DEVI void wo_tile(const uint32_t (*A0)[4], uint32_t sb, int tile, int lane, uint32_t yo, int s) {
  uint32_t u[8][4], A[16][4];
  const uint32_t wa = sb + R_WO + tile * 512 + lane * 16, ua = sb + R_U + lane * 16;
  float a[4] = {0, 0, 0, 0}, b[4] = {0, 0, 0, 0};
  auto fetch = [&](int i) { if (i < 16 - NR) ldsm4(A[i], wa + i * 4608); };
  auto uload = [&](int i) { if (i < 8) ldsm4t(u[i], ua + i * 512); };
#pragma unroll
  for (int i = 0; i < NP; i++) fetch(i);
  mwait(sb + B_V, s & 1);
  PT(6)
  uload(0); uload(1);
#pragma unroll
  for (int i = 0; i < 16; i++) {
    if (i == 4) {
      mwait(sb + B_U, s & 1);
      PT(7)
      uload(2); uload(3);
    }
    const uint32_t* f = i >= 16 - NR ? A0[i >= 16 - NR ? i - 16 + NR : 0] : A[i];
    mma16(i & 1 ? b : a, f[0], f[1], f[2], f[3], u[i >> 1][(i & 1) * 2], u[i >> 1][(i & 1) * 2 + 1]);
    fetch(i + NP);
    if (i >= 4 && (i & 1)) uload((i >> 1) + 2);
  }
#pragma unroll
  for (int i = 0; i < 4; i++) a[i] += b[i];
  y_store(a, yo, s);
}
template <bool X> DEVI void softmax8(const uint32_t* h, uint32_t a4, uint32_t a1) {
  uint32_t y[5];
  lds4(y, a4 + R_SX);
  y[4] = lds1(a1 + R_SX);
#pragma unroll
  for (int j = 0; j < 5; j++) y[j] = hadd2(h[j], y[j]);
  const uint32_t m2 = hmax2(hmax2(hmax2(y[0], y[1]), hmax2(y[2], y[3])), y[4]);
  const float mc = fmaxf(blo(m2), bhi(m2)) * SCL;
  const float m1 = __shfl_xor_sync(~0u, mc, 1), m3 = __shfl_xor_sync(~0u, mc, 2), m4 = __shfl_xor_sync(~0u, mc, 3);
  float e[10];
#pragma unroll
  for (int j = 0; j < 5; j++) { e[2 * j] = ex2(fmaf(blo(y[j]), SCL, -mc)); e[2 * j + 1] = ex2(fmaf(bhi(y[j]), SCL, -mc)); }
  const float c = ex2(mc - fmaxf(fmaxf(mc, m1), fmaxf(m3, m4)));
  const float l = c * ((((e[0] + e[1]) + (e[2] + e[3])) + ((e[4] + e[5]) + (e[6] + e[7]))) + (e[8] + e[9]));
  const float r = c * rcp((l + __shfl_xor_sync(~0u, l, 1)) + (__shfl_xor_sync(~0u, l, 2) + __shfl_xor_sync(~0u, l, 3)));
#pragma unroll
  for (int j = 0; j < 5; j++) y[j] = pack2(e[2 * j] * r, e[2 * j + 1] * r);
  if (!X) sts4(a4 + R_P, y[0], y[1], y[2], y[3]);
  else stsm4(a4 + R_P, y[0], y[1], y[2], y[3]);
  sts1(a1 + R_P, y[4]);
  if (X) fence_async();
}

DEVI void arm_step(uint32_t sb, int s) {
  mbar_expect(sb + B_SM, 640); mbar_expect(sb + B_SX, 2560);
  if (s < NSEG - 1) {
    mbar_expect(sb + B_U, 3072); mbar_expect(sb + B_Z0, 4096); mbar_expect(sb + B_Z1, 5120);
    mbar_expect(sb + B_XA, XG * 4096); mbar_expect(sb + B_XB, (9 - XG) * 4096);
  }
}
DEVI void rec_proj(const RecParams& P, const uint32_t sb, const int cta) {
  uint32_t W[36][4], A0[NRES ? NRES : 1][4];
  const int tid = pin(threadIdx.x);
  const uint32_t yo = pin(y_offset(cta, threadIdx.x >> 5, threadIdx.x & 31));
  const int warp = __shfl_sync(~0u, threadIdx.x >> 5, 0), role = warp >> 2;
  const uint32_t qk = sb + R_Q + warp * 1280;
  {
    const int lane = threadIdx.x & 31, w4 = (threadIdx.x >> 5) & 3;
    const uint32_t a = sb + role * R_H + ((lane & 7) + (lane >> 4) * 8) * 128 + (((w4 * 2 + ((lane >> 3) & 1)) ^ (lane & 7)) << 4);
    mbar_wait(sb + B_W0 + role * 8, 0);
    TL_END(8)
#pragma unroll
    for (int k = 0; k < 36; k++) ldsm4t(W[k], a + k * 2048);
    if (role) bar_arrive(N_INIT1, 256); else bar_sync(N_INIT, 128);
    cluster_sync_relaxed();
    wo_convert(sb, lane, warp);
    bar_sync(N_INIT2, 256);
#pragma unroll
    for (int i = 0; i < NRES; i++) ldsm4(A0[i], sb + R_WO + warp * 512 + lane * 16 + (16 - NRES + i) * 4608);
  }
  for (int s = -1; s < NSEG; s++) {
    if (s >= 0) {
      PT(0)
      {
        const int lane = opq(tid) & 31;
        const uint32_t hb = sb + R_H + (lane & 7) * 128 + (((lane >> 3) ^ (lane & 7)) << 4);
        float a[4] = {0, 0, 0, 0}, b[4] = {0, 0, 0, 0};
        mwait(sb + B_Z0, (s - 1) & 1);
        PT(1)
        uint32_t f[18][4];
#pragma unroll
        for (int c = -PD; c < 18; c++) {
          if (c + PD == 8) mwait(sb + B_Z1, (s - 1) & 1);
          if (c + PD < 18) ldsm4(f[c + PD], (hb ^ (((c + PD) & 1) * 64)) + ((c + PD) >> 1) * 5120);
          if (c >= 0) {
            mma16(a, W[2 * c][0], W[2 * c][1], W[2 * c][2], W[2 * c][3], f[c][0], f[c][1]);
            mma16(b, W[2 * c + 1][0], W[2 * c + 1][1], W[2 * c + 1][2], W[2 * c + 1][3], f[c][2], f[c][3]);
          }
        }
        sts1(qk + 512 + lane * 4, pack2(a[0] + b[0], a[1] + b[1]));
        sts1(qk + 1152 + lane * 4, pack2(a[2] + b[2], a[3] + b[3]));
        fence_async();
      }
      PT(2)
      const int lane = opq(tid) & 31;
      if (role) {
        bar_arrive(N_P1, 256);
        if (tid == 128) arm_step(sb, s);
        const uint32_t o4 = sb + (warp - 4) * 640 + lane * 16, o1 = sb + (warp - 4) * 640 + 512 + lane * 4;
        uint32_t h[5];
        bar_sync(N_PX, 192);
        lds4(h, o4 + R_P); h[4] = lds1(o1 + R_P);
        mwait(sb + B_SX, s & 1);
        PT(4)
        softmax8<true>(h, o4, o1);
        PT(5)
      } else {
        float S[20];
        const uint64_t da = mkdesc(sb + R_Q, 640, 128, 0), db = mkdesc(sb + R_K, 640, 128, 0);
        const uint32_t rs = mapa(sb, (cta & 15) ^ 1);
        const uint32_t o4 = warp * 1280 + lane * 16, o1 = warp * 1280 + 512 + lane * 4;
        bar_sync(N_P1, 256);
        wg_fence();
#pragma unroll
        for (int k = 0; k < 4; k++) wg_ss40<1>(S, da + k * 80, db + k * 80, k);
        wg_commit();
        bar_arrive(N_S, 256);
        wg_wait<0>();
        PT(3)
        uint32_t h[2][5];
        if (warp == 2) {
#pragma unroll
          for (int j = 0; j < 5; j++) h[0][j] = pack2(S[4 * j], S[4 * j + 1]);
          sta4(rs + R_SX + o4, h[0][0], h[0][1], h[0][2], h[0][3], rs + B_SM); sta1(rs + R_SX + o1, h[0][4], rs + B_SM);
          mwait(sb + B_SM, s & 1);
          PT(4)
          softmax8<false>(h[0], sb + o4, sb + o1);
          bar_arrive(N_PM, 160);
        } else if (warp < 2) {
          const int row = warp * 16 + (lane >> 2) - (lane & 3) * 2;
#pragma unroll
          for (int g = 0; g < 2; g++) {
#pragma unroll
            for (int j = 0; j < 5; j++) h[g][j] = pack2(j < 4 && j * 8 > row + g * 8 ? -INFINITY : S[4 * j + 2 * g], j < 4 && j * 8 + 1 > row + g * 8 ? -INFINITY : S[4 * j + 2 * g + 1]);
            sts4(sb + R_P + o4 + g * 640, h[g][0], h[g][1], h[g][2], h[g][3]); sts1(sb + R_P + o1 + g * 640, h[g][4]);
            sta4(rs + R_SX + o4 + g * 640, h[g][0], h[g][1], h[g][2], h[g][3], rs + B_SX);
            sta1(rs + R_SX + o1 + g * 640, h[g][4], rs + B_SX);
          }
          bar_arrive(N_PX, 192);
        } else {
          if (s) bar_sync(N_O, 160);
          if (tid == 96) {
            if (s) {
              bulk_wait<0>();
              tma_store(&P.ctx, sb + R_OX, cta * 64, s * 32 - 32); bulk_commit();
              if ((s & 3) == 1 && s > 1) signal_after_bulk(S_CTXB + (s >> 2) - 1);
              bulk_wait_read<0>();
            }
          }
        }
        __syncwarp();
        PT(5)
      }
      {
        if (s == NSEG - 1) break;
        wo_tile<NRES, NPF>(A0, sb, warp, lane, yo, s);

        PT(8)
        bar_sync(N_WO, 384);
      }
    }
    {
      float acc[16];
      const uint64_t db = mkdesc(sb + R_H + 1024, 16, 1024, 1);
      mwait(sb + B_XA, (s + 1) & 1);
      PT(9)
      wg_fence();
#pragma unroll
      for (int k = 0; k < XG * 4; k++) wg_rs32(acc, W[k], db + (k >> 2) * 320 + (k & 3) * 2, k);
      wg_commit();
      mwait(sb + B_XB, (s + 1) & 1);
      wg_fence();
#pragma unroll
      for (int k = XG * 4; k < KA; k++) wg_rs32(acc, W[k], db + (k >> 2) * 320 + (k & 3) * 2, 1);
      wg_commit();
      wg_wait<0>();
      PT(10)
      bar_sync(N_SUM, 384);
      wg_fence();
#pragma unroll
      for (int k = KA; k < 36; k++) wg_rs32(acc, W[k], db + (k >> 2) * 320 + (k & 3) * 2, 1);
      wg_commit();
      const uint32_t o = qk + (opq(tid) & 31) * 16;
      wg_wait<0>();
      PT(11)
      stsm4(o, pack2(acc[0], acc[1]), pack2(acc[4], acc[5]), pack2(acc[8], acc[9]), pack2(acc[12], acc[13]));
      stsm4(o + 640, pack2(acc[2], acc[3]), pack2(acc[6], acc[7]), pack2(acc[10], acc[11]), pack2(acc[14], acc[15]));
    }
  }
  bar_arrive(N_WO, 384);
  for (int i = 0; i < (warp ? 1 : 2); i++)
    asm volatile("st.relaxed.gpu.global.b64 [%0],%1;" ::"l"((uint8_t*)g_Y + YSLOT + yo + i * 2 * 16384), "l"(0ull) : "memory");
  TL_END(6)
  if (tid == 0) CT(1, 0)
  if (warp == 3) {
    if (tid == 96) { bulk_wait<0>(); asm volatile("fence.proxy.async.global;" ::: "memory"); }
    __syncwarp();
    bar_arrive(N_O, 160);
  }
  asm volatile("barrier.cluster.arrive.relaxed.aligned;" ::: "memory");
  float acc[48];
  const int rk = opq(cta) & 15, n = rk / 5, q = rk - n * 5;
  out_consume<TST, false, 32>(acc, sb, sb + B_O, rk == 15 ? 0 : q == 4 ? 12 : 13);
  if (tid == 0) CT(7, 1)
  if (tid == 0) CT(1, 1)
  asm volatile("barrier.cluster.wait.aligned;" ::: "memory");
  bar_sync(N_P1, 256);
  {
#pragma unroll
    for (int u = 0; u < 6; u++) {
      const int d = u % 5;
      const float* a = acc + u * 8;
      const uint32_t x = pack2(a[0], a[1]), y = pack2(a[2], a[3]), z = pack2(a[4], a[5]), w = pack2(a[6], a[7]);
      const uint32_t rs = mapa(sb, rk == 15 ? 15 : n * 5 + d);
      if (d == q) sts4(sb + R_RED - 8192 + (u / 5) * 4096 + tid * 16, x, y, z, w);
      else sta4(rs + R_RED + (q < d ? q : q - 1) * 8192 + (u / 5) * 4096 + tid * 16, x, y, z, w, rs + B_R);
    }
    mbar_wait(sb + B_R, 0);
    if (tid == 0) CT(1, 2)
    const int lane = tid & 31;
    const uint32_t st = sb + warp * 1024 + (lane & 15) * 48 + (lane >> 4) * 16, ld = sb + warp * 1024 + (lane >> 1) * 48 + (lane & 1) * 16;
    bf16* out = P.out + (size_t)((TAIL0 + (cta >> 5)) * 128 + warp * 16 + (lane >> 1)) * (2 * DM) + DM + ((cta >> 4) & 1) * 288 + n * 96 + q * 16 + (lane & 1) * 8;
#pragma unroll 1
    for (int i = 0; i < (q ? 1 : 2); i++) {
      uint32_t v[5][4], r[4];
#pragma unroll
      for (int p = 0; p < 5; p++) lds4(v[p], sb + R_RED + (p - 1) * 8192 + i * 4096 + tid * 16);
#pragma unroll
      for (int j = 0; j < 4; j++)
        r[j] = pack2((blo(v[0][j]) + blo(v[1][j])) + (blo(v[2][j]) + blo(v[3][j])) + blo(v[4][j]), (bhi(v[0][j]) + bhi(v[1][j])) + (bhi(v[2][j]) + bhi(v[3][j])) + bhi(v[4][j]));
      stsm4(st + i * 8192, r[0], r[1], r[2], r[3]);
      __syncwarp();
      lds4(r, ld + i * 8192);
      asm volatile("{.reg .pred p; setp.ne.s32 p,%5,15; @p st.global.v4.b32 [%0],{%1,%2,%3,%4};}" ::"l"(out + i * 80), "r"(r[0]), "r"(r[1]), "r"(r[2]), "r"(r[3]), "r"(rk) : "memory");
    }
  }
}

template <int K> DEVI void v_resident(uint32_t (*F)[4], uint32_t wv) {
  if constexpr (K < 36) { if (VIdx<K>::r == 'r') ldsm4t(F[VIdx<K>::v], wv + K * 2048); v_resident<K + 1>(F, wv); }
}
template <int K> DEVI void v_pass(float* acc, const uint32_t (*F)[4], uint64_t da, uint64_t db, uint32_t xf, uint32_t t, uint32_t nrel) {
  if constexpr (K < 36) {
    wg_fence();
    if (VIdx<K>::r == 'r') wg_rs40(acc, F[VIdx<K>::v], db + (K >> 2) * 320 + (K & 3) * 2, K);
    else wg_ss40<0>(acc, da + K * 128, db + (K >> 2) * 320 + (K & 3) * 2, K);
    wg_commit();
    if constexpr (VIdx<K>::p != '-') wg_wait<VIdx<K>::p - '0'>();
    if (K == XG * 4 - 1 + XW) { wg_wait<XW>(); asm volatile("{.reg .pred p; .reg .b32 a; setp.lt.u32 p,%1,%2; @p mapa.shared::cluster.u32 a,%0,%1; @p mbarrier.arrive.shared::cluster.b64 _,[a];}" ::"r"(xf), "r"(t), "r"(nrel) : "memory"); }
    v_pass<K + 1>(acc, F, da, db, xf, t, nrel);
  }
}
DEVI void rec_aux(const RecParams& P, const uint32_t sb, const int cta) {
  const int tid = pin(threadIdx.x);
  {
    uint4 v[5];
#pragma unroll
    for (int j = 0; j < 5; j++) if (j * 128 + tid - 256 < 576) v[j] = ((const uint4*)P.mem0)[j * 128 + tid - 256];
    if (tid == 288) {
      const uint32_t t0 = clk32();
      while (clk32() - t0 < (uint32_t)WOD) {}
#pragma unroll 1
      for (int i = 0; i < 4; i++) tma_load(sb + R_WO + i * 18432, &P.wo, (cta & 3) * 144, (cta ^ i) * 64, sb + B_W3);
      for (int i = 0; i < 3; i++) asm volatile("cp.async.bulk.prefetch.tensor.2d.L2.global [%0,{%1,%2}];" ::"l"(&P.wv), "r"(cta * 64), "r"(i * 192) : "memory");
    }
    __syncwarp();
    bar_sync(N_INIT1, 256);
#pragma unroll
    for (int j = 0; j < 5; j++) {
      const int i = j * 128 + tid - 256, t = i / 72, c = i - t * 72;
      if (i < 576) sts4(sb + R_H + (c >> 3) * 5120 + t * 128 + (((c & 7) ^ t) << 4), v[j].x, v[j].y, v[j].z, v[j].w);
    }
    fence_async();
    bar_arrive(N_SUM, 384);
    cluster_sync_relaxed();
    if (tid == 288) {
      if ((cta & 15) < 9) x_load(P, sb, cta & 15, 0);
#pragma unroll 1
      for (int i = 0; i < 3; i++) tma_load(sb + R_WV + i * 24576, &P.wv, cta * 64, i * 192, sb + B_W2);
    }
    __syncwarp();
    TL_END(12)
    TL_END(10)
  }
  const int rk = cta & 15, w4 = __shfl_sync(~0u, (threadIdx.x >> 5) & 3, 0);
  const uint32_t yg = pin((((threadIdx.x >> 5) & 3) * 16 + rk) * 1024 + ((threadIdx.x >> 4) & 1) * 128 + (threadIdx.x & 3) * 32 + ((threadIdx.x >> 2) & 3) * 8);
  uint32_t F[VB][4];
  mbar_wait(sb + B_W2, 0);
  TL_END(7)
  v_resident<0>(F, sb + R_WV + ((tid & 7) + ((tid >> 4) & 1) * 8) * 128 + (((w4 * 2 + ((tid >> 3) & 1)) ^ (tid & 7)) << 4));
  LT(0)
  for (int s = 0; s < NSEG; s++) {
    const bool last = s == NSEG - 1;
    uint32_t va[12], p[5];
    int lane = opq(tid) & 31;
    {
      float acc[20];
      const uint64_t da = mkdesc(sb + R_WV, 0, 1024, 1), db = mkdesc(sb + R_H, 16, 1024, 1);
      PT(0)
      bar_sync(N_S, 256);
      asm volatile("fence.proxy.async::generic.acquire.sync_restrict::shared::cluster.cluster;" ::: "memory");
      v_pass<0>(acc, F, da, db, sb + B_XF, tid - 256, last ? 0 : XG);
      PT(13)
      bar_sync(N_PM, 160);
      lds4(p, sb + R_P + 2560 + lane * 16); p[4] = lds1(sb + R_P + 3072 + lane * 4);
      wg_wait<0>();
      PT(1)
#pragma unroll
      for (int i = 0; i < 10; i++) va[i < 2 ? i + 8 : i - 2] = pack2(acc[2 * i], acc[2 * i + 1]);
      va[10] = va[11] = 0;
    }
    lane = opq(tid) & 31;
    if (!last) {
      const uint32_t uo = R_U + w4 * 256 + lane * 4;
      float a[4] = {0, 0, 0, 0}, b[4] = {0, 0, 0, 0}, c[4] = {0, 0, 0, 0};
      mma16(a, va[0], va[1], va[2], va[3], p[0], p[1]); mma16(b, va[4], va[5], va[6], va[7], p[2], p[3]); mma8(c, va[8], va[9], p[4]);
      const uint32_t u0 = pack2(a[0] + b[0] + c[0], a[1] + b[1] + c[1]), u1 = pack2(a[2] + b[2] + c[2], a[3] + b[3] + c[3]);
      sts1(sb + uo, u0); sts1(sb + uo + 128, u1);
      __syncwarp();
      if (lane == 0) mbar_arrive(sb + B_V);
#pragma unroll
      for (int q = 1; q < 4; q++) { const uint32_t rs = mapa(sb, rk ^ q); sta1(rs + uo + q * 1024, u0, rs + B_U); sta1(rs + uo + q * 1024 + 128, u1, rs + B_U); }
      asm volatile("{.reg .pred p; .reg .b32 a; setp.lt.u32 p,%1,%3; @p mapa.shared::cluster.u32 a,%0,%2; @p mbarrier.arrive.shared::cluster.b64 _,[a];}" ::"r"(sb + B_XF), "r"(tid - 256 - XG), "r"(tid - 256), "n"(9 - XG) : "memory");
      PT(4)
      if (w4 == 3) {
        wo_tile<0, 4>(nullptr, sb, 8, lane, y_offset(cta, 8, lane), s);
      } else if (tid == 288 && rk < 9) { mbar_wait(sb + B_XF, s & 1); x_load(P, sb, rk, s + 1); }
      PT(2)
    }
    lane = opq(tid) & 31;
    uint32_t ox[8], tu;
    {
      float o[16];
      const uint64_t dp = mkdesc(sb + R_P, 128, 640, 0);
      bar_sync(N_WO, 384);
      wg_fence();
      wg_rs32(o, va, dp, 0); wg_rs32(o, va + 4, dp + 16, 1); wg_rs32(o, va + 8, mkdesc(sb + R_P + 512, 0, 640, 0), 1);
      wg_commit();
      tu = clk32();
      wg_wait<0>();
      PT(3)
#pragma unroll
      for (int i = 0; i < 8; i++) ox[i] = pack2(o[2 * i], o[2 * i + 1]);
    }
    if (!last) {
      const uint8_t* y = (const uint8_t*)g_Y + (s & 1) * YSLOT + yg;
      uint32_t w0[8], w1[8], w2[8];
      while (clk32() - tu < (uint32_t)YD) {}
      y_load(w0, y); y_load(w1, y + 4 * 16384);
      if (w4 == 0) y_load(w2, y + 8 * 16384);
      else {
#pragma unroll
        for (int i = 0; i < 8; i++) w2[i] = ((s >> 1) & 1) ^ 1;
      }
      PT(5)
      const uint32_t dst = R_H + w4 * 5120 + (rk >> 1) * 128 + ((((rk & 1) * 4 + (lane >> 3)) ^ (rk >> 1)) << 4) + (lane & 4) * 2;
      const uint32_t tag = ((s >> 1) & 1) ^ 1, sel = (lane & 4) ? 0x3f800000u : 0x3f80u;
      uint32_t r0[2], r1[2], r2[2];
#pragma unroll 1
      for (int it = 0; (y_missing(w0, tag) | y_missing(w1, tag) | y_missing(w2, tag)) && it < (1 << 20); it++) {
        y_reload(w0, y, tag); y_reload(w1, y + 4 * 16384, tag); y_reload(w2, y + 8 * 16384, tag);
      }
      PT(7)
      y_sum(r0, w0, sel); y_sum(r1, w1, sel); y_sum(r2, w2, sel);
      y_send(r0, sb, dst, B_Z0, lane);
      bar_arrive(N_SUM, 384);
      y_send(r1, sb, dst + 4 * 5120, B_Z1, lane);
      if (w4 == 0) y_send(r2, sb, dst + 8 * 5120, B_Z1, lane);
      PT(9)
    }
#pragma unroll
    for (int h = 0; h < 2; h++) stsm4t(sb + R_OX + lane * 128 + (((w4 * 2 + h) ^ (lane & 7)) << 4), ox[h], ox[2 + h], ox[4 + h], ox[6 + h]);
    if (last) break;
    fence_async();
    bar_arrive(N_O, 160);
    PT(11)
  }
  fence_async();
  bar_sync(N_O, 160);
  if (tid == 256) {
    tma_store(&P.ctx, sb + R_OX, cta * 64, SEQ - 32); bulk_commit(); bulk_wait<0>(); signal_after_bulk(S_CTXB + 15);
  }
  __syncwarp();
  LT(1)
  asm volatile("barrier.cluster.arrive.relaxed.aligned;" ::: "memory");
  if (tid == 256) {
    const int m = TAIL0 + (cta >> 5), n = rk / 5, q = rk - n * 5;
    mbar_expect(sb + B_R, q || rk == 15 ? 4 * 4096 : 8 * 4096);
    if (rk < 15) out_produce<TST, false, 32>(P.o, sb, sb + B_O, m, ((cta >> 4) & 1) * 3 + n, q * 13, q == 4 ? 12 : 13, S_CTXB + m);
  }
  __syncwarp();
  asm volatile("barrier.cluster.wait.aligned;" ::: "memory");
}

__global__ void __launch_bounds__(384, 1) rec_kernel(const __grid_constant__ RecParams P) {
  extern __shared__ __align__(1024) uint8_t smem_raw[];
  const uint32_t sb = s2u(smem_raw);
  const int tid = threadIdx.x, cta = blockIdx.x;
  pdl_trigger();
  if (cta >= 64) {
    unsigned sm; asm("mov.u32 %0,%%smid;" : "=r"(sm));
    if (tid == 0) g_group[sm & 255] = (cta >> 4) - 3;
    return;
  }
  TL_START(1)
  if (tid == 0) {
    for (int i = 0; i < 14 + 2 * TST; i++) mbar_init(sb + R_BAR + 8 * i, 8 * i == B_XF - R_BAR ? 16 : 8 * i == B_V - R_BAR ? 4 : i >= 14 + TST ? 2 : 1);
    asm volatile("fence.mbarrier_init.release.cluster;" ::: "memory");
    asm volatile("cp.async.bulk.prefetch.L2.global [%0],%1;" ::"l"(P.x_raw + cta * DM), "r"(DM * 2) : "memory");
    mbar_expect(sb + B_W0, 73728); mbar_expect(sb + B_W1, 73728); mbar_expect(sb + B_W2, 73728); mbar_expect(sb + B_W3, 73728);
#pragma unroll 1
    for (int i = 0; i < 3; i++) { tma_load(sb + R_WV + i * 24576, &P.wq, cta * 64, i * 192, sb + B_W0); tma_load(sb + R_H + i * 24576, &P.wk, cta * 64, i * 192, sb + B_W1); }
    mbar_expect(sb + B_XA, XG * 4096); mbar_expect(sb + B_XB, (9 - XG) * 4096);
  }
  __syncthreads();
  if (tid >= 256) { reg_dec<504 - 2 * RP>(); rec_aux(P, sb, cta); }
  else { reg_inc<RP>(); rec_proj(P, sb, cta); }
  TL_END(1)
  if (tid == 0) CT(7, 2)
  cluster_sync_relaxed();
}
typedef CUresult (*EncFn)(CUtensorMap*, CUtensorMapDataType, cuuint32_t, void*, const cuuint64_t*, const cuuint64_t*, const cuuint32_t*, const cuuint32_t*,
                          CUtensorMapInterleave, CUtensorMapSwizzle, CUtensorMapL2promotion, CUtensorMapFloatOOBfill);
static EncFn g_enc;
static CUtensorMap mk(const void* p, uint64_t cols, uint64_t rows, uint64_t pitch_elems, uint32_t box_rows, uint32_t box_cols = 64) {
  CUtensorMap m;
  cuuint64_t dim[2] = {cols, rows}, str[1] = {pitch_elems * 2};
  cuuint32_t box[2] = {box_cols, box_rows}, es[2] = {1, 1};
  g_enc(&m, CU_TENSOR_MAP_DATA_TYPE_BFLOAT16, 2, (void*)p, dim, str, box, es, CU_TENSOR_MAP_INTERLEAVE_NONE, box_cols == 64 ? CU_TENSOR_MAP_SWIZZLE_128B : box_cols == 32 ? CU_TENSOR_MAP_SWIZZLE_64B : CU_TENSOR_MAP_SWIZZLE_NONE,
        CU_TENSOR_MAP_L2_PROMOTION_L2_256B, CU_TENSOR_MAP_FLOAT_OOB_FILL_NONE);
  return m;
}
static CUtensorMap mk3(const void* p, uint32_t g, uint32_t box_rows) {
  CUtensorMap m;
  cuuint64_t dim[3] = {g, HD, DM / g}, str[2] = {DM * 2, g * 2};
  cuuint32_t box[3] = {g, box_rows, 3}, es[3] = {1, 1, 1};
  g_enc(&m, CU_TENSOR_MAP_DATA_TYPE_BFLOAT16, 3, (void*)p, dim, str, box, es, CU_TENSOR_MAP_INTERLEAVE_NONE, g == 64 ? CU_TENSOR_MAP_SWIZZLE_128B : CU_TENSOR_MAP_SWIZZLE_64B,
        CU_TENSOR_MAP_L2_PROMOTION_L2_256B, CU_TENSOR_MAP_FLOAT_OOB_FILL_NONE);
  return m;
}
template <class T> static void* sym(T& s) { void* p; cudaGetSymbolAddress(&p, s); return p; }

#define FE 6
#define STG 10
#define FHC 24
#define FSL 5
#define NF2 20
template <class K, class A> static void launch(K k, int grid, int smem, int cluster, bool pdl, const A& arg) {
  cudaLaunchConfig_t c = {};
  cudaLaunchAttribute at[2];
  int n = 0;
  if (cluster > 1) { at[n].id = cudaLaunchAttributeClusterDimension; at[n].val.clusterDim.x = cluster; at[n].val.clusterDim.y = at[n].val.clusterDim.z = 1; n++; }
  if (pdl) { at[n].id = cudaLaunchAttributeProgrammaticStreamSerialization; at[n].val.programmaticStreamSerializationAllowed = 1; n++; }
  c.gridDim = grid; c.blockDim = 384; c.dynamicSmemBytes = smem; c.stream = cudaStreamPerThread; c.attrs = at; c.numAttrs = n;
  cudaLaunchKernelEx(&c, k, arg);
}

extern "C" void kernel_launch(void* const* d_in, const int* in_sizes, int n_in, void* d_out, int out_size) {
  static int nb, ng;
  if (!g_enc) {
    cudaDriverEntryPointQueryResult qr;
    cudaGetDriverEntryPoint("cuTensorMapEncodeTiled", (void**)&g_enc, cudaEnableDefault, &qr);
    cudaDeviceGetAttribute(&nb, cudaDevAttrMultiProcessorCount, 0);
    nb = nb - 64 < 54 ? 54 : nb - 64 > 96 ? 96 : (nb - 64) & ~1;
    cudaFuncSetAttribute(out_kernel, cudaFuncAttributeMaxDynamicSharedMemorySize, SM_O);
    cudaFuncSetAttribute(fa_kernel, cudaFuncAttributeMaxDynamicSharedMemorySize, SM_F);
    cudaFuncSetAttribute(rec_kernel, cudaFuncAttributeMaxDynamicSharedMemorySize, R_END);
    cudaFuncSetAttribute(rec_kernel, cudaFuncAttributeNonPortableClusterSizeAllowed, 1);
    cudaLaunchConfig_t c = {};
    cudaLaunchAttribute at; at.id = cudaLaunchAttributeClusterDimension; at.val.clusterDim.x = 16; at.val.clusterDim.y = at.val.clusterDim.z = 1;
    c.gridDim = 128; c.blockDim = 384; c.dynamicSmemBytes = R_END; c.attrs = &at; c.numAttrs = 1;
    cudaOccupancyMaxActiveClusters(&ng, rec_kernel, &c);
    ng = ng < 4 ? 0 : ng - 4 > nb / 16 ? nb / 16 : ng - 4;
  }
  const bf16 *Ax = (const bf16*)d_in[0], *Ac = (const bf16*)d_in[1], *Awq = (const bf16*)d_in[2], *Awk = (const bf16*)d_in[3], *Awv = (const bf16*)d_in[4],
             *Awo = (const bf16*)d_in[5], *Bx = (const bf16*)d_in[6], *Bm = (const bf16*)d_in[7], *Bwq = (const bf16*)d_in[8], *Bwk = (const bf16*)d_in[9],
             *Bwv = (const bf16*)d_in[10], *Bwo = (const bf16*)d_in[11];
  bf16* out = (bf16*)d_out;
  FaParams f;
  ProjParams& p = f.p;
  int nitems = 0;
  p.a[0] = mk(Ac, 512, SEQ, 512, 128); p.a[1] = mk(Ax, DM, SEQ, DM, 128);
  p.w[0] = mk(Awk, HD, 512, HD, 64); p.w[1] = mk(Awv, HD, 512, HD, 64); p.w[2] = mk(Awq, HD, DM, HD, 64);
  p.c[0] = mk(sym(g_kA), HD, SEQ, HD, 64); p.c[1] = mk(sym(g_vA), HD, SEQ, HD, 64); p.c[2] = mk(sym(g_qA), HD, SEQ, HD, 64);
  {
    int parts[16];
    for (int i = 0; i < 16; i++) parts[i] = 1;
    for (int e = 0; e < nb / 2 - 16; e++) parts[e % 24 < 16 ? e % 8 : 15 - (e % 24 - 16)]++;
    for (int i = 15; i >= 0; i--)
      for (int j = 0, nc = i < 8 ? 32 : 16, a = parts[i]; j < a; j++) {
        ProjItem& I = p.item[nitems++];
        I.pa = i >> 3; I.m = i & 7;
        I.c0[0] = j * nc / a; I.n[0] = (j + 1) * nc / a - I.c0[0];
        I.c0[1] = (j * nc + a - 1) / a; I.n[1] = ((j + 1) * nc + a - 1) / a - I.c0[1];
        if (i < 8 && a == 3) { const int d = STG * (i + 4) / 11, b1 = 11 - d, b2 = 22 - d + (i - 4) * STG / 16; I.c0[1] = j == 0 ? 0 : j == 1 ? b1 : b2; I.n[1] = (j == 0 ? b1 : j == 1 ? b2 : 32) - I.c0[1]; }
      }
  }
  for (int i = 0; i < nitems; i++) {
    auto len = [&](int j) { return (8 + p.item[j].pa) * (1 + p.item[j].n[0] + p.item[j].n[1]); };
    int longer = 0;
    for (int j = 0; j < nitems; j++) longer += len(j) > len(i) || (len(j) == len(i) && j < i);
    p.item[i].leave = longer < NF2 / 2;
    p.item[i].s0 = (PST - len(i) % PST) % PST;
  }
  OutParams o;
  for (int i = 0; i < 3; i++) {
    f.om[i].a = mk(i ? sym(g_ctxB) : sym(g_qA), HD, SEQ, HD, 128);
    f.om[i].b = i < 2 ? mk(i ? Bwo : Awo, DM, HD, DM, 32) : mk(Bwo, DM, HD, DM, 64, 32);
    f.om[i].c = mk(out + (i ? DM : 0), DM, SEQ, 2 * DM, 64, i < 2 ? 64 : 32);
  }
  o.p[0] = f.om[1]; o.p[0].b = mk(Bwo, DM, HD, DM, 64); o.p[1] = f.om[2];
  f.q = mk(sym(g_qA), HD, SEQ, HD, 128); f.k = mk(sym(g_kA), HD, SEQ, HD, 128); f.v = mk(sym(g_vA), HD, SEQ, HD, 128); f.o = mk(sym(g_qA), HD, SEQ, HD, 64);
  f.nctas = nb; f.ngroups = ng;
  for (int i = 0; i < 9; i++) f.nproj[i] = 0;
  for (int i = 0; i < nitems; i++) f.nproj[p.item[i].pa * (p.item[i].m + 1)] += 4;
  for (int key = -90, n = 0; n < 512; key++)
    for (int h = 0; h < 32; h++)
      for (int qt = 0; qt < 16; qt++)
        if ((h < FHC ? h : FHC) * FSL - qt * 2 - (qt >= 12 && h < FE ? 60 : 0) == key) f.order[n++] = qt * 32 + h;
  RecParams r;
  r.wq = mk(Bwq, HD, DM, HD, 192); r.wk = mk(Bwk, HD, DM, HD, 192); r.wv = mk(Bwv, HD, DM, HD, 192); r.wo = mk(Bwo, DM, HD, DM, 64, 144);
  r.x_raw = Bx;
  r.x = mk(Bx, DM, SEQ, DM, 32); r.ctx = mk(sym(g_ctxB), HD, SEQ, HD, 32); r.mem0 = Bm; r.o = f.om[2]; r.o.b = mk3(Bwo, 32, 64); r.out = out;

  f.om[2].a = mk(sym(g_ctxB), HD, SEQ, HD, 64);
  uint16_t* last = f.tile;
  int nl = 0;
  for (int m = 14; m >= 0; m -= 2)
    for (int n = 0; n < 3; n++) { last[nl++] = m * 8 + n; last[nl++] = m * 8 + 8 + n; }
  for (int n = 0; n < 6; n++) last[nl++] = 256 + (TAIL0 - 1) * 8 + n;
  bool done[16][3] = {};
  for (int m = TAIL0 - 3; m >= 0; m -= 2)
    for (int n = 2; n >= 0 && nl < nb; n--) { last[nl++] = 128 + m * 8 + n; last[nl++] = 128 + m * 8 + 8 + n; done[m][n] = done[m + 1][n] = true; }
  while (nl < nb) last[nl++] = 384;
  o.n = 2; o.odd = 0; o.tile[0] = 128; o.tile[1] = 129; done[0][0] = true;
  for (int m = 0; m < TAIL0 - 1; m++)
    for (int n = 0; n < 3; n++) if (!done[m][n]) o.tile[o.n++] = m * 8 + n;
  launch(rec_kernel, 64 + 16 * ng, R_END, 16, false, r);
  f.proj = 1;
  launch(fa_kernel, nb, SM_F, 2, true, f);
  launch(out_kernel, o.n, SM_O, 2, true, o);
  f.proj = 0;
  launch(fa_kernel, NF2, SM_F, 2, true, f);
}
```

```cpp
#include <cuda_runtime.h>
#include <cuda_bf16.h>
#include <cuda.h>
#include <stdint.h>

typedef __nv_bfloat16 bf16;
#define DEVI __device__ __forceinline__
#define WAIT_FAIL(code) break
#define WAIT_MAX (1 << 22)

constexpr int SEQ = 2048, HD = 4096, DM = 576, NSEG = 64;

__device__ __align__(1024) bf16 g_qA[SEQ * HD], g_kA[SEQ * HD], g_vA[SEQ * HD];
__device__ __align__(1024) bf16 g_ctxB[SEQ * HD];
__device__ __align__(1024) uint4 g_Y[2 * 9 * 16 * 64];
enum { S_QUEUE = 0, S_EXIT = 1, S_LIST = 8, S_PROJ = 32, S_CTXA = 64, S_CTXB = 96 };
__device__ unsigned g_sync[128];
__device__ __align__(16) uint8_t g_group[256];
#define LT(i)
#define CT(k, i) {}
#define TL_START(i)
#define TL_END(i)

DEVI uint32_t s2u(const void* p) { return (uint32_t)__cvta_generic_to_shared(p); }
DEVI void mbar_init(uint32_t b, uint32_t c) { asm volatile("mbarrier.init.shared::cta.b64 [%0],%1;" ::"r"(b), "r"(c)); }
DEVI void mbar_expect(uint32_t b, uint32_t n) { asm volatile("mbarrier.arrive.expect_tx.shared::cta.b64 _,[%0],%1;" ::"r"(b), "r"(n) : "memory"); }
DEVI void mbar_arrive(uint32_t b) { asm volatile("mbarrier.arrive.shared::cta.b64 _,[%0];" ::"r"(b) : "memory"); }
DEVI void mbar_wait(uint32_t b, uint32_t ph) {
  uint32_t ok; int it = 0;
  do {
    asm volatile("{.reg .pred p; mbarrier.try_wait.parity.shared::cta.b64 p,[%1],%2; selp.u32 %0,1,0,p;}" : "=r"(ok) : "r"(b), "r"(ph) : "memory");
    if (!ok && ++it > WAIT_MAX) WAIT_FAIL(b & 0xffffff);
  } while (!ok);
}
DEVI bool mbar_try(uint32_t b, uint32_t ph) {
  uint32_t ok;
  asm volatile("{.reg .pred p; mbarrier.try_wait.parity.shared::cta.b64 p,[%1],%2; selp.u32 %0,1,0,p;}" : "=r"(ok) : "r"(b), "r"(ph) : "memory");
  return ok;
}
DEVI bool mbar_test(uint32_t b, uint32_t ph) {
  uint32_t ok;
  asm volatile("{.reg .pred p; mbarrier.test_wait.parity.shared::cta.b64 p,[%1],%2; selp.u32 %0,1,0,p;}" : "=r"(ok) : "r"(b), "r"(ph) : "memory");
  return ok;
}
DEVI void mwait(uint32_t b, uint32_t ph) { if (__builtin_expect(!mbar_try(b, ph), 0)) mbar_wait(b, ph); }
DEVI void tma_load(uint32_t dst, const CUtensorMap* tm, int c0, int c1, uint32_t bar) {
  asm volatile("cp.async.bulk.tensor.2d.shared::cluster.global.mbarrier::complete_tx::bytes [%0],[%1,{%3,%4}],[%2];" ::"r"(dst), "l"(tm), "r"(bar), "r"(c0), "r"(c1) : "memory");
}
DEVI void tma_store(const CUtensorMap* tm, uint32_t src, int c0, int c1) {
  asm volatile("cp.async.bulk.tensor.2d.global.shared::cta.bulk_group [%0,{%2,%3}],[%1];" ::"l"(tm), "r"(src), "r"(c0), "r"(c1) : "memory");
}
DEVI void bulk_commit() { asm volatile("cp.async.bulk.commit_group;" ::: "memory"); }
template <int N> DEVI void bulk_wait_read() { asm volatile("cp.async.bulk.wait_group.read %0;" ::"n"(N) : "memory"); }
template <int N> DEVI void bulk_wait() { asm volatile("cp.async.bulk.wait_group %0;" ::"n"(N) : "memory"); }
DEVI void fence_async() { asm volatile("fence.proxy.async.shared::cta;" ::: "memory"); }
DEVI void bar_sync(int id, int n) { asm volatile("bar.sync %0,%1;" ::"r"(id), "r"(n) : "memory"); }
DEVI void bar_arrive(int id, int n) { asm volatile("bar.arrive %0,%1;" ::"r"(id), "r"(n) : "memory"); }
template <int R> DEVI void reg_inc() { asm volatile("setmaxnreg.inc.sync.aligned.u32 %0;" ::"n"(R)); }
template <int R> DEVI void reg_dec() { asm volatile("setmaxnreg.dec.sync.aligned.u32 %0;" ::"n"(R)); }
DEVI void wg_fence() { asm volatile("wgmma.fence.sync.aligned;" ::: "memory"); }
DEVI void wg_commit() { asm volatile("wgmma.commit_group.sync.aligned;" ::: "memory"); }
template <int N> DEVI void wg_wait() { asm volatile("wgmma.wait_group.sync.aligned %0;" ::"n"(N) : "memory"); }
DEVI uint64_t desc_k(uint32_t a) { return (uint64_t)((a >> 4) & 0x3fff) | (1ull << 16) | (64ull << 32) | (1ull << 62); }
DEVI uint64_t desc_mn(uint32_t a, uint32_t lbo) { return (uint64_t)((a >> 4) & 0x3fff) | ((uint64_t)(lbo >> 4) << 16) | (64ull << 32) | (1ull << 62); }
DEVI uint64_t mkdesc(uint32_t a, uint32_t lbo, uint32_t sbo, int sw) { return (uint64_t)((a >> 4) & 0x3fff) | ((uint64_t)(lbo >> 4) << 16) | ((uint64_t)(sbo >> 4) << 32) | ((uint64_t)sw << 62); }
DEVI uint32_t pack2(float lo, float hi) { uint32_t r; asm("cvt.rn.bf16x2.f32 %0,%1,%2;" : "=r"(r) : "f"(hi), "f"(lo)); return r; }
DEVI float ex2(float x) { float y; asm("ex2.approx.ftz.f32 %0,%1;" : "=f"(y) : "f"(x)); return y; }
DEVI void stsm4(uint32_t a, uint32_t r0, uint32_t r1, uint32_t r2, uint32_t r3) {
  asm volatile("stmatrix.sync.aligned.m8n8.x4.shared.b16 [%0],{%1,%2,%3,%4};" ::"r"(a), "r"(r0), "r"(r1), "r"(r2), "r"(r3) : "memory");
}
DEVI void ldsm4(uint32_t* r, uint32_t a) {
  asm volatile("ldmatrix.sync.aligned.m8n8.x4.shared.b16 {%0,%1,%2,%3},[%4];" : "=r"(r[0]), "=r"(r[1]), "=r"(r[2]), "=r"(r[3]) : "r"(a) : "memory");
}
DEVI void ldsm4t(uint32_t* r, uint32_t a) {
  asm volatile("ldmatrix.sync.aligned.m8n8.x4.trans.shared.b16 {%0,%1,%2,%3},[%4];" : "=r"(r[0]), "=r"(r[1]), "=r"(r[2]), "=r"(r[3]) : "r"(a) : "memory");
}
DEVI void mma16(float* d, uint32_t a0, uint32_t a1, uint32_t a2, uint32_t a3, uint32_t b0, uint32_t b1) {
  asm volatile("mma.sync.aligned.m16n8k16.row.col.f32.bf16.bf16.f32 {%0,%1,%2,%3},{%4,%5,%6,%7},{%8,%9},{%0,%1,%2,%3};"
               : "+f"(d[0]), "+f"(d[1]), "+f"(d[2]), "+f"(d[3]) : "r"(a0), "r"(a1), "r"(a2), "r"(a3), "r"(b0), "r"(b1));
}

DEVI void pdl_trigger() { asm volatile("griddepcontrol.launch_dependents;" ::: "memory"); }
DEVI void signal_after_bulk(int f) {
  asm volatile("fence.proxy.async.global;" ::: "memory");
  asm volatile("red.release.gpu.global.add.u32 [%0], 1;" ::"l"(g_sync + f) : "memory");
}
DEVI void flag_wait(int f, unsigned n, unsigned waiters) {
  for (int it = 0;; it++) {
    if (it > WAIT_MAX) WAIT_FAIL(f);
    unsigned v; asm volatile("ld.acquire.gpu.global.u32 %0, [%1];" : "=r"(v) : "l"(g_sync + f) : "memory");
    if (v >= n) break;
    __nanosleep(64);
  }
  if (waiters) asm volatile("red.relaxed.gpu.global.inc.u32 [%0], %1;" ::"l"(g_sync + f), "r"(n + waiters - 1) : "memory");
  asm volatile("fence.proxy.async.global;" ::: "memory");
}
DEVI uint32_t mapa(uint32_t a, uint32_t r) { uint32_t o; asm("mapa.shared::cluster.u32 %0,%1,%2;" : "=r"(o) : "r"(a), "r"(r)); return o; }
DEVI void tma_load_mc(uint32_t dst, const CUtensorMap* tm, int c0, int c1, uint32_t bar, uint16_t mask) {
  asm volatile("cp.async.bulk.tensor.2d.shared::cluster.global.mbarrier::complete_tx::bytes.multicast::cluster [%0],[%1,{%3,%4}],[%2],%5;" ::"r"(dst), "l"(tm), "r"(bar), "r"(c0), "r"(c1), "h"(mask) : "memory");
}
DEVI void tma_load3(uint32_t dst, const CUtensorMap* tm, int c1, int c2, uint32_t bar) {
  asm volatile("cp.async.bulk.tensor.3d.shared::cluster.global.mbarrier::complete_tx::bytes [%0],[%1,{0,%3,%4}],[%2];" ::"r"(dst), "l"(tm), "r"(bar), "r"(c1), "r"(c2) : "memory");
}
DEVI void arrive_pair(uint32_t b) { if ((threadIdx.x & 127) < 2) asm volatile("mbarrier.arrive.shared::cluster.b64 _,[%0];" ::"r"(mapa(b, threadIdx.x & 1)) : "memory"); }
DEVI void cluster_sync_relaxed() { asm volatile("barrier.cluster.arrive.relaxed.aligned; barrier.cluster.wait.aligned;" ::: "memory"); }
DEVI void cluster_sync() { asm volatile("barrier.cluster.arrive.aligned; barrier.cluster.wait.aligned;" ::: "memory"); }
DEVI void sts4(uint32_t a, uint32_t x, uint32_t y, uint32_t z, uint32_t w) { asm volatile("st.shared.v4.b32 [%0],{%1,%2,%3,%4};" ::"r"(a), "r"(x), "r"(y), "r"(z), "r"(w) : "memory"); }
DEVI void lds4(uint32_t* r, uint32_t a) { asm volatile("ld.shared.v4.b32 {%0,%1,%2,%3},[%4];" : "=r"(r[0]), "=r"(r[1]), "=r"(r[2]), "=r"(r[3]) : "r"(a) : "memory"); }
DEVI void sta4(uint32_t d, uint32_t a, uint32_t b, uint32_t c, uint32_t e, uint32_t bar) {
  asm volatile("st.async.weak.shared::cluster.mbarrier::complete_tx::bytes.v4.b32 [%0],{%1,%2,%3,%4},[%5];" ::"r"(d), "r"(a), "r"(b), "r"(c), "r"(e), "r"(bar) : "memory");
}
DEVI float blo(uint32_t u) { return __uint_as_float(u << 16); }
DEVI float bhi(uint32_t u) { return __uint_as_float(u & 0xffff0000u); }

#define F8(a, o) "+f"(a[o]), "+f"(a[o + 1]), "+f"(a[o + 2]), "+f"(a[o + 3]), "+f"(a[o + 4]), "+f"(a[o + 5]), "+f"(a[o + 6]), "+f"(a[o + 7])
#define F32(a, o) F8(a, o), F8(a, o + 8), F8(a, o + 16), F8(a, o + 24)
template<int TB> DEVI void wg_ss128(float* d, uint64_t da, uint64_t db, int acc){
 asm volatile("{.reg .pred p; setp.ne.b32 p,%66,0;\n wgmma.mma_async.sync.aligned.m64n128k16.f32.bf16.bf16 {%0,%1,%2,%3,%4,%5,%6,%7,%8,%9,%10,%11,%12,%13,%14,%15,%16,%17,%18,%19,%20,%21,%22,%23,%24,%25,%26,%27,%28,%29,%30,%31,%32,%33,%34,%35,%36,%37,%38,%39,%40,%41,%42,%43,%44,%45,%46,%47,%48,%49,%50,%51,%52,%53,%54,%55,%56,%57,%58,%59,%60,%61,%62,%63},%64,%65,p,1,1,0,%67;}"
 : F32(d,0),F32(d,32) : "l"(da),"l"(db),"r"(acc),"n"(TB));}
template<int TB> DEVI void wg_ss192(float* d, uint64_t da, uint64_t db, int acc){
 asm volatile("{.reg .pred p; setp.ne.b32 p,%98,0;\n wgmma.mma_async.sync.aligned.m64n192k16.f32.bf16.bf16 {%0,%1,%2,%3,%4,%5,%6,%7,%8,%9,%10,%11,%12,%13,%14,%15,%16,%17,%18,%19,%20,%21,%22,%23,%24,%25,%26,%27,%28,%29,%30,%31,%32,%33,%34,%35,%36,%37,%38,%39,%40,%41,%42,%43,%44,%45,%46,%47,%48,%49,%50,%51,%52,%53,%54,%55,%56,%57,%58,%59,%60,%61,%62,%63,%64,%65,%66,%67,%68,%69,%70,%71,%72,%73,%74,%75,%76,%77,%78,%79,%80,%81,%82,%83,%84,%85,%86,%87,%88,%89,%90,%91,%92,%93,%94,%95},%96,%97,p,1,1,0,%99;}"
 : F32(d,0),F32(d,32),F32(d,64) : "l"(da),"l"(db),"r"(acc),"n"(TB));}
template<int TB> DEVI void wg_rs128(float* d, const uint32_t* a, uint64_t db, int acc){
 asm volatile("{.reg .pred p; setp.ne.b32 p,%69,0;\n wgmma.mma_async.sync.aligned.m64n128k16.f32.bf16.bf16 {%0,%1,%2,%3,%4,%5,%6,%7,%8,%9,%10,%11,%12,%13,%14,%15,%16,%17,%18,%19,%20,%21,%22,%23,%24,%25,%26,%27,%28,%29,%30,%31,%32,%33,%34,%35,%36,%37,%38,%39,%40,%41,%42,%43,%44,%45,%46,%47,%48,%49,%50,%51,%52,%53,%54,%55,%56,%57,%58,%59,%60,%61,%62,%63},{%64,%65,%66,%67},%68,p,1,1,%70;}"
 : F32(d,0),F32(d,32) : "r"(a[0]),"r"(a[1]),"r"(a[2]),"r"(a[3]),"l"(db),"r"(acc),"n"(TB));}
DEVI void wg_ss96t(float* d, uint64_t da, uint64_t db, int acc){
 asm volatile("{.reg .pred p; setp.ne.b32 p,%50,0;\n wgmma.mma_async.sync.aligned.m64n96k16.f32.bf16.bf16 {%0,%1,%2,%3,%4,%5,%6,%7,%8,%9,%10,%11,%12,%13,%14,%15,%16,%17,%18,%19,%20,%21,%22,%23,%24,%25,%26,%27,%28,%29,%30,%31,%32,%33,%34,%35,%36,%37,%38,%39,%40,%41,%42,%43,%44,%45,%46,%47},%48,%49,p,1,1,0,1;}"
 : F32(d,0),F8(d,32),F8(d,40) : "l"(da),"l"(db),"r"(acc));}
struct ProjItem { uint8_t pa, m, c0[2], n[2], s0, leave; };
struct ProjParams { CUtensorMap a[2], w[3], c[3]; ProjItem item[48]; };
constexpr int PST = 12, P_STG = PST * 16384, P_FULL = P_STG + 32768 + 256, P_EMPTY = P_FULL + 8 * PST, P_OF = P_EMPTY + 8 * PST, P_OE = P_OF + 16, P_END = P_OE + 16;
DEVI void proj_decode(const ProjItem& I, int t, int& pw, int& n) {
  const int g = t >= I.n[0], c = g ? I.c0[1] + t - I.n[0] : I.c0[0] + t;
  pw = I.pa ? 2 : c >> 4; n = (c & 15) + g * 16;
}
DEVI void proj_init(const ProjItem& I, uint32_t base) {
  for (int i = 0; i < PST; i++) { mbar_init(base + P_FULL + 8 * i, 1); mbar_init(base + P_EMPTY + 8 * i, 4); }
  for (int i = 0; i < 2; i++) { mbar_init(base + P_OF + 8 * i, 4); mbar_init(base + P_OE + 8 * i, 1); }
  mbar_init(base + P_END, 1);
  for (int i = 0; i < I.s0; i++) {
    mbar_arrive(base + P_FULL + 8 * i);
    asm volatile("mbarrier.arrive.shared::cta.b64 _,[%0],4;" ::"r"(base + P_EMPTY + 8 * i) : "memory");
  }
}
DEVI int proj_produce(const ProjParams& P, const ProjItem& I, uint32_t base) {
  const int nk = 8 + I.pa, r = blockIdx.x & 1;
  int s = I.s0, ph = 1;
  for (int t = -1; t < I.n[0] + I.n[1]; t++) {
    int pw, n; proj_decode(I, t, pw, n);
    if (t == I.n[0] + I.n[1] - 1) mbar_arrive(base + P_END);
    for (int k = 0; k < nk; k++) {
      if (t >= 0) mbar_wait(base + P_EMPTY + 8 * s, ph);
      mbar_expect(base + P_FULL + 8 * s, 16384);
      if (t < 0) tma_load(base + s * 16384, &P.a[I.pa], k * 64, (I.m * 2 + r) * 128, base + P_FULL + 8 * s);
      else tma_load_mc(base + s * 16384 + r * 8192, &P.w[pw], n * 128 + r * 64, k * 64, base + P_FULL + 8 * s, 3);
      if (++s == PST) { s = 0; ph ^= 1; }
    }
  }
  return ph;
}
DEVI void proj_store(const ProjParams& P, const ProjItem& I, uint32_t base, int g) {
  const int r0 = (I.m * 2 + (blockIdx.x & 1)) * 128 + g * 64;
  for (int t = 0; t < I.n[0] + I.n[1]; t++) {
    int pw, n; proj_decode(I, t, pw, n);
    mbar_wait(base + P_OF + 8 * g, t & 1);
    tma_store(&P.c[pw], base + P_STG + g * 16384, n * 128, r0);
    tma_store(&P.c[pw], base + P_STG + g * 16384 + 8192, n * 128 + 64, r0);
    bulk_commit();
    bulk_wait_read<0>();
    mbar_arrive(base + P_OE + 8 * g);
    if (t == 3 && !g) CT(0, 1)
    if (t == I.n[0] - 1) { bulk_wait<0>(); signal_after_bulk(S_PROJ + I.pa * (I.m + 1) * 2); }
  }
  bulk_wait<0>(); signal_after_bulk(S_PROJ + I.pa * (I.m + 1) * 2 + 1);
  if (!g) CT(0, 2)
}
DEVI void proj_consume(const ProjItem& I, uint32_t base, int tid, int wg) {
  const uint32_t full = base + P_FULL;
  uint32_t A[36][4];
  float acc[64];
  uint32_t s = I.s0, ph = 0, c = 1;
  const uint32_t row = ((tid >> 5) & 3) * 16 + (tid & 15);
  const uint32_t roff = row * 128 + ((((tid >> 4) & 1) ^ (row & 7)) << 4);
  const uint32_t rel = mapa(base + P_EMPTY, tid & 1);
  auto release = [&](uint32_t st) { asm volatile("{.reg .pred p; setp.lt.u32 p,%1,2; @p mbarrier.arrive.shared::cluster.b64 _,[%0];}" ::"r"(rel + 8 * st), "r"(tid & 127) : "memory"); };
  const int pa = I.pa, nt = I.n[0] + I.n[1];
#pragma unroll
  for (int k = 0; k < 9; k++) {
    if (k < 8 || pa) {
      mbar_wait(full + 8 * s, ph);
#pragma unroll
      for (int kk = 0; kk < 4; kk++) ldsm4(A[4 * k + kk], base + s * 16384 + wg * 8192 + (roff ^ (kk * 32)));
      bar_sync(1 + wg, 128);
      release(s);
      if (++s == PST) { s = 0; ph ^= 1; }
    }
  }
  if (tid == 0) CT(0, 0)
  if (wg) bar_sync(5, 256);
  bool ok = false;
  for (int t = 0; t < nt; t++, c ^= 1) {
    uint32_t p1 = 0;
#pragma unroll
    for (int k = 0; k < 9; k++) {
      if (k < 8 || pa) {
        if (!ok) mbar_wait(full + 8 * s, ph);
        const uint64_t db = desc_mn(base + s * 16384, 8192);
        wg_fence();
#pragma unroll
        for (int kk = 0; kk < 4; kk++) wg_rs128<1>(acc, A[4 * k + kk], db + kk * 128, k | kk);
        wg_commit();
        const uint32_t cur = s;
        if (++s == PST) { s = 0; ph ^= 1; }
        ok = mbar_test(full + 8 * s, ph);
        if (k) { wg_wait<1>(); release(p1); }
        if (k == 4 && t == 0 && !wg) bar_arrive(5, 256);
        p1 = cur;
      }
    }
    mwait(base + P_OE + 8 * wg, c);
    wg_wait<0>();
    release(p1);
#pragma unroll
    for (int i = 0; i < 8; i++) {
      const float* a = acc + i * 8;
      stsm4(base + P_STG + wg * 16384 + (i >> 2) * 8192 + (roff ^ ((i & 3) * 32)), pack2(a[0], a[1]), pack2(a[2], a[3]), pack2(a[4], a[5]), pack2(a[6], a[7]));
    }
    fence_async();
    __syncwarp();
    if ((tid & 31) == 0) mbar_arrive(base + P_OF + 8 * wg);
  }
}

struct OutMaps { CUtensorMap a, b, c; };
template <int NST, bool PAIR, int G> DEVI void out_produce(const OutMaps& M, uint32_t base, uint32_t full, int m, int n, int k0, int nk, int flag) {
  constexpr int SB = 16384 + 384 * G;
  constexpr bool MC = PAIR && G == 64;
  const int r = MC ? blockIdx.x & 1 : 0;
  int s = 0, ph = !PAIR;
#pragma unroll 1
  for (int k = 0; k < nk + (PAIR ? NST - 1 : 0); k++) {
    mbar_wait(full + 8 * (NST + s), ph);
    if (k < nk) {
      mbar_expect(full + 8 * s, SB);
      if (flag >= 0) tma_load3(base + s * SB + 16384, &M.b, (k0 + k) * 64, n * 3, full + 8 * s);
      else
#pragma unroll 1
      for (int j = 0; j < 3; j++) {
        if (MC) tma_load_mc(base + s * SB + 16384 + j * 128 * G + r * 64 * G, &M.b, (n * 3 + j) * G, k * 64 + r * 32, full + 8 * s, 3);
        else tma_load(base + s * SB + 16384 + j * 128 * G, &M.b, (n * 3 + j) * G, (k0 + k) * 64, full + 8 * s);
      }
      if (flag >= 0 && k == 0) flag_wait(flag, 64, 30);
      if (flag >= 0) tma_load(base + s * SB, &M.a, (k0 + k) * 64, m * 128, full + 8 * s);
    }
    if (++s == NST) { s = 0; ph ^= 1; }
  }
}
template <int NST, bool PAIR, int G> DEVI void out_rows(const OutMaps& M, uint32_t base, uint32_t full, int m, int flag, int cnt, int waiters) {
  flag_wait(flag, cnt, waiters);
  int s = 0, ph = !PAIR;
#pragma unroll 1
  for (int k = 0; k < 64; k++) {
    if (k == cnt) mbar_wait(full + 16 * NST, 0);
    mbar_wait(full + 8 * (NST + s), ph);
    if (PAIR && G == 32) tma_load_mc(base + s * (16384 + 384 * G) + (blockIdx.x & 1) * 8192, &M.a, k * 64, m * 128 + (blockIdx.x & 1) * 64, full + 8 * s, 3);
    else tma_load(base + s * (16384 + 384 * G), &M.a, k * 64, m * 128, full + 8 * s);
    if (++s == NST) { s = 0; ph ^= 1; }
  }
}
template <int NST, bool PAIR, int G> DEVI void out_consume(float* acc, uint32_t base, uint32_t full, int nk) {
  constexpr int SB = 16384 + 384 * G;
  const uint32_t empty = full + 8 * NST;
  const int wg = threadIdx.x >> 7;
  int s = 0, ph = 0, prev = 0;
#pragma unroll 1
  for (int k = 0; k < nk; k++) {
    mbar_wait(full + 8 * s, ph);
    const uint64_t da = desc_k(base + s * SB + wg * 8192), db = mkdesc(base + s * SB + 16384, 128 * G, 16 * G, G == 64 ? 1 : 2);
    wg_fence();
#pragma unroll
    for (int kk = 0; kk < 4; kk++) {
      if (G == 64) wg_ss192<1>(acc, da + kk * 2, db + kk * 128, k | kk);
      else wg_ss96t(acc, da + kk * 2, db + kk * 64, k | kk);
    }
    wg_commit();
    if (k) { wg_wait<1>(); if (PAIR) arrive_pair(empty + 8 * prev); else if ((threadIdx.x & 127) == 0) mbar_arrive(empty + 8 * prev); }
    prev = s;
    if (++s == NST) { s = 0; ph ^= 1; }
  }
  wg_wait<0>();
}
template <int NST, bool PAIR, int G> DEVI void out_tile(const OutMaps& M, uint32_t base, uint32_t full, int m, int n) {
  const int tid = threadIdx.x, wg = tid >> 7;
  float acc[G * 3 / 2];
  out_consume<NST, PAIR, G>(acc, base, full, 64);
  bar_sync(6, 256);
  const uint32_t row = ((tid >> 5) & 3) * 16 + (tid & 15);
  const uint32_t roff = row * 2 * G + ((((tid >> 4) & 1) ^ (G == 64 ? row & 7 : (row >> 1) & 3)) << 4);
#pragma unroll
  for (int i = 0; i < G * 3 / 16; i++) {
    const float* a = acc + i * 8;
    stsm4(base + wg * 384 * G + i / (G / 16) * 128 * G + (roff ^ (i % (G / 16) * 32)), pack2(a[0], a[1]), pack2(a[2], a[3]), pack2(a[4], a[5]), pack2(a[6], a[7]));
  }
  fence_async();
  bar_sync(1 + wg, 128);
  if ((tid & 127) == 0) {
#pragma unroll 1
    for (int c = 0; c < 3; c++) tma_store(&M.c, base + wg * 384 * G + c * 128 * G, (n * 3 + c) * G, m * 128 + wg * 64);
    bulk_commit();
    bulk_wait_read<0>();
  }
}
struct OutParams { OutMaps p[2]; int n, odd; uint8_t tile[64]; };
constexpr int SM_O = 6 * 28672 + 256;
__global__ void __launch_bounds__(384, 1) out_kernel(const __grid_constant__ OutParams P) {
  extern __shared__ __align__(1024) uint8_t smem_raw[];
  const uint32_t base = s2u(smem_raw), full = base + 6 * 28672;
  const int tid = threadIdx.x, t = P.tile[blockIdx.x], half = t >> 7, m = (t >> 3) & 15, n = t & 7;
  TL_START(4)
  pdl_trigger();
  if (tid == 0) {
    for (int i = 0; i < 12; i++) mbar_init(full + 8 * i, i >= 4 + 2 * half ? 2 : 1);
    asm volatile("fence.mbarrier_init.release.cluster;" ::: "memory");
  }
  __syncthreads();
  if (tid >= 256) {
    if (tid == 256) { if (half) out_produce<6, false, 32>(P.p[1], base, full, m, n, 0, 64, -1); else out_produce<4, false, 64>(P.p[0], base, full, m, n, 0, 64, -1); }
    if (tid == 288) { if (half) out_rows<6, false, 32>(P.p[1], base, full, m, S_CTXB + m, 64, 4); else out_rows<4, false, 64>(P.p[0], base, full, m, S_CTXB + m, 64, 3 + (m == P.odd)); }
  } else {
    if (tid == 0) CT(4, 0)
    if (half) out_tile<6, false, 32>(P.p[1], base, full, m, n); else out_tile<4, false, 64>(P.p[0], base, full, m, n);
    if (tid == 0) CT(4, 2)
    TL_END(4)
  }
}
struct FaParams { ProjParams p; CUtensorMap q, k, v, o; unsigned proj, nctas, ngroups; uint8_t nproj[12]; uint16_t order[512];
                  OutMaps om[3]; uint16_t tile[96]; };
constexpr int HST = 5, F_OUT = 7 * 32768 + 512, F_OUTH = F_OUT + 72, F_TILE = F_OUTH + 16 * HST, SM_F = F_OUT + 256;
constexpr float FA_C = 0.08838834764831845f * 1.4426950408889634f;
DEVI int fa_qt(int w) { return w >> 5; }
DEVI int fa_hc(int w) { return (w & 31) * 128; }

DEVI void fa_exp(const float* S, uint32_t* Pn, float mc0, float mc1, float& s0, float& s1) {
  float a0 = 0.f, a1 = 0.f, b0 = 0.f, b1 = 0.f;
#pragma unroll
  for (int j = 0; j < 16; j++) {
    const float e0 = ex2(fmaf(S[4 * j], FA_C, -mc0)), e1 = ex2(fmaf(S[4 * j + 1], FA_C, -mc0));
    const float e2 = ex2(fmaf(S[4 * j + 2], FA_C, -mc1)), e3 = ex2(fmaf(S[4 * j + 3], FA_C, -mc1));
    a0 += e0; a1 += e1; b0 += e2; b1 += e3;
    Pn[2 * j] = pack2(e0, e1); Pn[2 * j + 1] = pack2(e2, e3);
  }
  s0 = a0 + a1; s1 = b0 + b1;
}

struct FaState { float mc0, mc1, l0, l1; int w, j, qi; uint32_t dq; bool first; };
enum { F_Q = 0, F_K = 2 * 32768, F_V = 4 * 32768, F_O = 6 * 32768, F_QF = 7 * 32768, F_QE = F_QF + 16, F_KF = F_QF + 32, F_KE = F_QF + 48, F_VF = F_QF + 64, F_VE = F_QF + 80,
       F_OF = F_QF + 96, F_OE = F_QF + 112, F_INFO = F_QF + 128 };

DEVI void out_open(uint32_t base, int tid, uint32_t mask) {
  const int s = (tid & 127) >> 1;
  if (s < 4 + HST && ((mask >> s) & 1))
    asm volatile("mbarrier.arrive.shared::cluster.b64 _,[%0];" ::"r"(mapa(base + (s < 4 ? F_OUT + 32 : F_OUTH + 8 * HST - 32) + 8 * s, tid & 1)) : "memory");
}
template <int SC> DEVI bool fa_step(FaState& T, float* O, float* S, const uint32_t* Pc, uint32_t* Pn, uint32_t base, int tid, int wg, uint32_t ph) {
  const bool el = (tid & 127) == 0, fin = T.j == 0;
  int wn = T.w, jn = T.j - 1;
  const bool okk = mbar_try(base + F_KF + 8 * (SC ^ 1), ph), okv = mbar_try(base + F_VF + 8 * SC, ph ^ SC);
  if (fin) {
    T.qi++; T.dq ^= 2048;
    mbar_wait(base + F_QF + 8 * (T.qi & 1), (T.qi >> 1) & 1);
    asm volatile("ld.shared.b32 %0,[%1];" : "=r"(wn) : "r"(base + F_INFO + (T.qi & 1) * 4) : "memory");
    wn = __shfl_sync(~0u, wn, 0);
    jn = fa_qt(wn);
    if (wn < 0) out_open(base, tid, 0xf7);
  }
  if (!(okk && okv)) { mbar_wait(base + F_KF + 8 * (SC ^ 1), ph); mbar_wait(base + F_VF + 8 * SC, ph ^ SC); }
  const bool last = wn < 0;
  {
    const uint64_t dq = desc_k(0) | T.dq, dk = desc_k(base + F_K + (SC ^ 1) * 32768), dv = desc_mn(base + F_V + SC * 32768, 16384);
    bar_sync(3 + wg, 256);
    wg_fence();
#pragma unroll
    for (int kk = 0; kk < 8; kk++) wg_ss128<0>(S, dq + (kk & 3) * 2 + (kk >> 2) * 1024, dk + (kk & 3) * 2 + (kk >> 2) * 1024, kk);
    wg_commit();
#pragma unroll
    for (int kk = 0; kk < 8; kk++) wg_rs128<1>(O, Pc + 4 * kk, dv + kk * 128, kk || !T.first);
    wg_commit();
    bar_arrive(4 - wg, 256);
  }
  wg_wait<1>();
  asm volatile("{.reg .pred p,q; setp.ne.u32 p,%0,0; setp.eq.and.u32 q,%1,0,p; @p mbarrier.arrive.shared::cta.b64 _,[%2]; @q mbarrier.arrive.shared::cta.b64 _,[%3];}"
               ::"r"((uint32_t)el), "r"(jn), "r"(base + F_KE + 8 * (SC ^ 1)), "r"(base + F_QE + 8 * (T.qi & 1)) : "memory");
  const float lp0 = T.l0, lp1 = T.l1;
  float s0 = 0.f, s1 = 0.f, f0 = 1.f, f1 = 1.f;
  bool exact = fin;
  if (!fin) {
    fa_exp(S, Pn, T.mc0, T.mc1, s0, s1);
    exact = __any_sync(~0u, !(fmaxf(s0, s1) <= 1073741824.f));
  }
  if (exact && !last) {
    float a = -INFINITY, b = -INFINITY;
    if (fin) {
      const int row = (tid >> 5) * 16 + ((tid & 31) >> 2) - (tid & 3) * 2;
#pragma unroll
      for (int j = 0; j < 16; j++) {
        if (j * 8 > row) S[4 * j] = -INFINITY;
        if (j * 8 + 1 > row) S[4 * j + 1] = -INFINITY;
        if (j * 8 > row + 8) S[4 * j + 2] = -INFINITY;
        if (j * 8 + 1 > row + 8) S[4 * j + 3] = -INFINITY;
      }
      T.mc0 = T.mc1 = -INFINITY;
    }
#pragma unroll
    for (int j = 0; j < 16; j++) { a = fmaxf(a, fmaxf(S[4 * j], S[4 * j + 1])); b = fmaxf(b, fmaxf(S[4 * j + 2], S[4 * j + 3])); }
    a = fmaxf(a, __shfl_xor_sync(~0u, a, 1)); b = fmaxf(b, __shfl_xor_sync(~0u, b, 1));
    a = fmaxf(a, __shfl_xor_sync(~0u, a, 2)); b = fmaxf(b, __shfl_xor_sync(~0u, b, 2));
    a = fmaxf(a * FA_C, T.mc0); b = fmaxf(b * FA_C, T.mc1);
    f0 = ex2(T.mc0 - a); f1 = ex2(T.mc1 - b);
    T.mc0 = a; T.mc1 = b;
    T.l0 = fin ? 0.f : T.l0 * f0; T.l1 = fin ? 0.f : T.l1 * f1;
    fa_exp(S, Pn, a, b, s0, s1);
  }
  T.l0 += s0; T.l1 += s1;
  wg_wait<0>();
  if (el) mbar_arrive(base + F_VE + 8 * SC);
  if (exact) {
    if (fin) {
      f0 = lp0 + __shfl_xor_sync(~0u, lp0, 1); f1 = lp1 + __shfl_xor_sync(~0u, lp1, 1);
      f0 += __shfl_xor_sync(~0u, f0, 2); f1 += __shfl_xor_sync(~0u, f1, 2);
      f0 = 1.f / f0; f1 = 1.f / f1;
    }
#pragma unroll
    for (int i = 0; i < 16; i++) { O[4 * i] *= f0; O[4 * i + 1] *= f0; O[4 * i + 2] *= f1; O[4 * i + 3] *= f1; }
    if (fin && (T.qi || last)) {
      const uint32_t row = ((tid >> 5) & 3) * 16 + (tid & 15);
      const uint32_t o = base + F_O + wg * 16384 + row * 128 + ((((tid >> 4) & 1) ^ (row & 7)) << 4);
      if (T.qi) mbar_wait(base + F_OE + 8 * wg, (T.qi & 1) ^ 1);
#pragma unroll
      for (int i = 0; i < 8; i++) {
        const float* a = O + i * 8;
        stsm4((o ^ ((i & 3) * 32)) + (i >> 2) * 8192, pack2(a[0], a[1]), pack2(a[2], a[3]), pack2(a[4], a[5]), pack2(a[6], a[7]));
      }
      if (el) asm volatile("st.shared.b32 [%0],%1;" ::"r"(base + F_INFO + 8 + wg * 4), "r"(!T.qi ? -1 : T.w | (last ? 1024 : 0)) : "memory");
      fence_async();
      __syncwarp();
      if ((tid & 31) == 0) mbar_arrive(base + F_OF + 8 * wg);
    }
  }
  T.w = wn; T.j = jn; T.first = fin;
  return last;
}

__global__ void __launch_bounds__(384, 1) fa_kernel(const __grid_constant__ FaParams P) {
  extern __shared__ __align__(1024) uint8_t smem_raw[];
  const uint32_t base = __shfl_sync(~0u, s2u(smem_raw), 0);
  const uint32_t sQ = base, sK = base + 2 * 32768, sV = base + 4 * 32768, sO = base + 6 * 32768, bars = base + 7 * 32768;
  const uint32_t qf = bars, qe = bars + 16, kf = bars + 32, ke = bars + 48, vf = bars + 64, ve = bars + 80, of = bars + 96, oe = bars + 112;
  volatile int* info = (volatile int*)(smem_raw + 7 * 32768 + 128);
  const int tid = threadIdx.x, wg = tid >> 7;
  const ProjItem& I = P.p.item[blockIdx.x >> 1];
  const bool leave = P.proj && I.leave;
  auto my_tile = [&]() { mbar_wait(base + F_TILE, 0); return info[5]; };
  pdl_trigger();
  if (tid == 0) {
    if (P.proj) proj_init(I, base);
    for (int i = 0; i < 16; i++) mbar_init(bars + 8 * i, i >= 14 ? 1 : i >= 12 ? 4 : (i & 2) ? 2 : 1);
    for (int i = 0; i < 10 + 2 * HST; i++) mbar_init(base + F_OUT + 8 * i, (i >= 4 && i < 8) || (i >= 9 + HST && i < 9 + 2 * HST) ? 4 : 1);
    mbar_expect(base + F_TILE, 4);
    info[4] = 0;
    asm volatile("fence.mbarrier_init.release.cluster;" ::: "memory");
  }
  __syncthreads();
  cluster_sync_relaxed();
  if (wg == 2) {
    reg_dec<24>();
    if (tid == 256) {
      int it = 0, qi = 0, vc = 0, vr = -1, j = 0, hc = 0;
      int pph = P.proj ? proj_produce(P.p, I, base) : -1;
      auto drain = [&](int s0) { if (pph >= 0) for (int i = s0; i < s0 + 6; i++) mbar_wait(base + P_EMPTY + 8 * i, pph); };
      if (leave) { drain(0); drain(6); return; }
      CT(P.proj ? 3 : 6, 0)
      auto load_v = [&]() {
        if (vr < 0) return;
        const int s = (it - 1) & 1;
        drain(6); pph = -1;
        mbar_wait(ve + 8 * s, (((it - 1) >> 1) & 1) ^ 1 ^ s);
        mbar_expect(vf + 8 * s, 32768);
        tma_load(sV + s * 32768, &P.v, vc, vr, vf + 8 * s);
        tma_load(sV + s * 32768 + 16384, &P.v, vc + 64, vr, vf + 8 * s);
        vr = -1;
      };
      auto ready = [&](uint32_t m) { uint32_t v; asm volatile("ld.acquire.cta.shared.b32 %0,[%1];" : "=r"(v) : "r"(base + F_INFO + 16) : "memory"); return (v & m) == m; };
      for (it = -1;; it++) {
        if (it >= 0) {
          const int s = it & 1;
          if (it || j < 0) { drain(6); pph = -1; }
          mbar_wait(ke + 8 * s, ((it >> 1) & 1) ^ 1);
          if (j < 0) { mbar_arrive(kf + 8 * s); load_v(); break; }
          mbar_expect(kf + 8 * s, 32768);
          tma_load(sK + s * 32768, &P.k, hc, j * 128, kf + 8 * s);
          tma_load(sK + s * 32768 + 16384, &P.k, hc + 64, j * 128, kf + 8 * s);
        }
        int nc = hc, nr = it >= 0 ? j * 128 : -1;
        if (j-- == 0) {
          int w = atomicInc(&g_sync[S_QUEUE], 511 + P.nctas);
          w = w < 512 ? P.order[w] : -1;
          const uint32_t q = qi & 1, m = w < 0 ? 0x3ffff : (1u | (2u << (fa_qt(w) | 1))) << ((w >> 4) & 1);
          if (!ready(m) || !mbar_test(qe + 8 * q, ((qi >> 1) & 1) ^ 1)) {
            load_v(); it++; vc = nc; vr = nr; load_v(); it--; nr = -1;
            for (int n = 0; !ready(m) && n < WAIT_MAX; n++) __nanosleep(64);
            mbar_wait(qe + 8 * q, ((qi >> 1) & 1) ^ 1);
          }
          asm volatile("fence.proxy.async.global;" ::: "memory");
          if (it < 0) drain(0);
          info[q] = w;
          if (w < 0) mbar_arrive(qf + 8 * q);
          else {
            j = fa_qt(w); hc = fa_hc(w);
            mbar_expect(qf + 8 * q, 32768);
            tma_load(sQ + q * 32768, &P.q, hc, j * 128, qf + 8 * q);
            tma_load(sQ + q * 32768 + 16384, &P.q, hc + 64, j * 128, qf + 8 * q);
          }
          qi++;
        }
        load_v();
        vc = nc; vr = nr;
      }
      const int tile = my_tile(), kind = tile >> 7, tm = (tile >> 3) & 15, tn = tile & 7;
      if (atomicInc(&g_sync[S_EXIT], P.nctas - 1) == P.nctas - 1) {
#pragma unroll 1
        for (int i = S_LIST; i < S_PROJ + 18; i++) g_sync[i] = 0;
#pragma unroll 1
        for (int i = 0; i < 16; i++) ((uint4*)g_group)[i] = make_uint4(0, 0, 0, 0);
      }
      if (kind == 2) out_produce<HST, true, 32>(P.om[2], base, base + F_OUTH, tm, tn, 0, 64, -1);
      else if (kind < 2) out_produce<4, true, 64>(P.om[kind], base, base + F_OUT, tm, tn, 0, 64, -1);
      else { mbar_wait(base + F_OUT + 56, 0); mbar_wait(base + F_TILE - 8, 0); }
    } else if (tid >= 352) {
      const int l = tid - 352;
      if (P.proj) mbar_wait(base + P_END, 0);
#pragma unroll 1
      for (int n = 0; n < WAIT_MAX && !leave; n++) {
        unsigned v = 255;
        if (l < 18) asm volatile("ld.acquire.gpu.global.u32 %0, [%1];" : "=r"(v) : "l"(g_sync + S_PROJ + l) : "memory");
        const uint32_t m = __ballot_sync(~0u, v >= P.nproj[(l >> 1) % 9]);
        __syncwarp();
        if (l == 0) asm volatile("st.release.cta.shared.b32 [%0],%1;" ::"r"(base + F_INFO + 16), "r"(m) : "memory");
        if (m == ~0u) break;
        __nanosleep(300);
      }
      if (l == 0 && !(blockIdx.x & 1) && !leave) {
        unsigned sm; asm("mov.u32 %0,%%smid;" : "=r"(sm));
        unsigned g = *(volatile uint8_t*)&g_group[sm & 255] - 1u, i;
        if (g > P.ngroups) g = P.ngroups;
        while ((i = g * 8 + atomicAdd(&g_sync[S_LIST + g], 1)) >= (g < P.ngroups ? g * 8 + 8 : P.nctas / 2)) g = g ? g - 1 : P.ngroups;
        for (int r = 0; r < 2; r++)
          asm volatile("st.async.weak.shared::cluster.mbarrier::complete_tx::bytes.b32 [%0],%1,[%2];" ::"r"(mapa(base + F_INFO + 20, r)), "r"((int)P.tile[i * 2 + r]), "r"(mapa(base + F_TILE, r)) : "memory");
      }
      if (l == 0 && !leave) {
        const int tile = my_tile(), kind = tile >> 7, tm = (tile >> 3) & 15;
        mbar_wait(base + (kind == 2 ? F_OUTH + 8 * HST : F_OUT + 32), 0);
        if (kind == 2) out_rows<HST, true, 32>(P.om[2], base, base + F_OUTH, tm, S_CTXB + tm, 64, 6);
        else if (kind < 2) out_rows<4, true, 64>(P.om[kind], base, base + F_OUT, tm, (kind ? S_CTXB : S_CTXA) + tm, kind ? 64 : 32, 3);
      }
    } else if (tid == 288 || tid == 320) {
      const int g = tid == 320;
      if (P.proj) proj_store(P.p, I, base, g);
      if (leave) return;
      mbar_arrive(oe + 8 * g);
        for (int n = 0;; n++) {
          mbar_wait(of + 8 * g, n & 1);
          const int v = info[2 + g], w = v & 1023, qt = fa_qt(w), hc = fa_hc(w);
          if (v < 0) break;
          tma_store(&P.o, sO + g * 16384, hc, qt * 128 + g * 64);
          tma_store(&P.o, sO + g * 16384 + 8192, hc + 64, qt * 128 + g * 64);
          bulk_commit();
          bulk_wait_read<0>();
          mbar_arrive(oe + 8 * g);
          bulk_wait<0>();
          signal_after_bulk(S_CTXA + (w & 16) + qt);
          if (v & 1024) break;
        }
      if (!g && my_tile() < 128) { flag_wait(S_CTXA + 16 + (info[5] >> 3), 32, 3); mbar_arrive(base + F_OUT + 64); }
    }
  } else {
    reg_inc<240>();
    const uint32_t ub = base;
    const int uw = __shfl_sync(~0u, wg, 0);
    if (wg == 1 && !leave) bar_arrive(3, 256);
    if (P.proj) proj_consume(I, ub, tid, uw);
    if (leave) return;
    float O[64], S[64];
    uint32_t PA[32], PB[32];
#pragma unroll
    for (int i = 0; i < 32; i++) PA[i] = 0;
#pragma unroll
    for (int i = 0; i < 64; i++) O[i] = 0.f;
    FaState T = {0.f, 0.f, 1.f, 1.f, 0, 0, -1, ((ub + 32768 + uw * 8192) >> 4) & 0x3fff, true};
    for (uint32_t ph = 0;; ph ^= 1) {
      if (fa_step<1>(T, O, S, PA, PB, ub, tid, uw, ph)) break;
      if (fa_step<0>(T, O, S, PB, PA, ub, tid, uw, ph)) break;
    }
    if (wg == 0) bar_sync(3, 256);
    out_open(ub, tid, ~0xf7u);
    const int tile = __shfl_sync(~0u, my_tile(), 0), kind = tile >> 7, tm = (tile >> 3) & 15, tn = tile & 7;
    if (tid == 0) CT(P.proj ? 5 : 2, 0)
    TL_START(5)
    if (kind == 2) out_tile<HST, true, 32>(P.om[2], ub, ub + F_OUTH, tm, tn);
    else if (kind < 2) out_tile<4, true, 64>(P.om[kind], ub, ub + F_OUT, tm, tn);
    if (tid == 0) CT(P.proj ? 5 : 2, 2)
    TL_END(kind == 2 ? 2 : 5)
  }
}
#define PS 20
#define PT(i)
#define YD 200
#define NPF 4
#define NRES 6
#define RP 208
#define PD 2
#define VR "............rrrrrr.................."
#define VP "222222222222111111111111------------"
constexpr int vr_index(int k) { int n = 0; for (int i = 0; i < k; i++) n += VR[i] == 'r'; return n; }
constexpr int VB = vr_index(36);
template <int K> struct VIdx { static constexpr int v = vr_index(K); static constexpr char r = VR[K], p = VP[K]; };
#define XG 6
#define XW 2
#define WOD 2000
#define KA 26
constexpr int R_WV = 0, R_WO = 73728, R_H = 147456, R_OX = R_H + 46080, R_Q = R_OX + 4096, R_K = R_Q + 5120, R_SX = R_K + 5120, R_P = R_SX + 3200, R_U = R_P + 3200,
              R_BAR = R_H + 73728, R_PROF = R_BAR + 256, R_END = R_PROF + 3072;
constexpr int B_W0 = R_BAR, B_W1 = R_BAR + 8, B_XA = R_BAR + 16, B_XB = R_BAR + 24, B_XF = R_BAR + 32, B_Z0 = R_BAR + 40, B_Z1 = R_BAR + 48, B_R = R_BAR + 56,
              B_SM = R_BAR + 64, B_SX = R_BAR + 72, B_U = R_BAR + 80, B_V = R_BAR + 88, B_W2 = R_BAR + 96, B_W3 = R_BAR + 104, B_O = R_BAR + 112;
static_assert(R_U + 4096 <= R_BAR, "");
enum { N_P1 = 1, N_PM, N_PX, N_SUM, N_O, N_INIT, N_INIT1, N_INIT2, N_WO, N_S };
constexpr int YSLOT = 9 * 16 * 1024;
struct RecParams { CUtensorMap wq, wk, wv, wo, x, ctx; OutMaps o; const bf16 *mem0, *x_raw; bf16* out; };
constexpr int TAIL0 = 14;
constexpr int TST = 6, R_RED = TST * 28672;

DEVI void wg_rs32(float* d, const uint32_t* a, uint64_t db, int acc) {
  asm volatile("{.reg .pred p; setp.ne.b32 p,%21,0;\n wgmma.mma_async.sync.aligned.m64n32k16.f32.bf16.bf16 {%0,%1,%2,%3,%4,%5,%6,%7,%8,%9,%10,%11,%12,%13,%14,%15},{%16,%17,%18,%19},%20,p,1,1,0;}"
               : F8(d, 0), F8(d, 8) : "r"(a[0]), "r"(a[1]), "r"(a[2]), "r"(a[3]), "l"(db), "r"(acc));
}
DEVI void wg_rs40(float* d, const uint32_t* a, uint64_t db, int acc) {
  asm volatile("{.reg .pred p; setp.ne.b32 p,%25,0;\n wgmma.mma_async.sync.aligned.m64n40k16.f32.bf16.bf16 {%0,%1,%2,%3,%4,%5,%6,%7,%8,%9,%10,%11,%12,%13,%14,%15,%16,%17,%18,%19},{%20,%21,%22,%23},%24,p,1,1,0;}"
               : F8(d, 0), F8(d, 8), "+f"(d[16]), "+f"(d[17]), "+f"(d[18]), "+f"(d[19]) : "r"(a[0]), "r"(a[1]), "r"(a[2]), "r"(a[3]), "l"(db), "r"(acc));
}
template <int TB> DEVI void wg_ss40(float* d, uint64_t da, uint64_t db, int acc) {
  asm volatile("{.reg .pred p; setp.ne.b32 p,%22,0;\n wgmma.mma_async.sync.aligned.m64n40k16.f32.bf16.bf16 {%0,%1,%2,%3,%4,%5,%6,%7,%8,%9,%10,%11,%12,%13,%14,%15,%16,%17,%18,%19},%20,%21,p,1,1,1,%23;}"
               : F8(d, 0), F8(d, 8), "+f"(d[16]), "+f"(d[17]), "+f"(d[18]), "+f"(d[19]) : "l"(da), "l"(db), "r"(acc), "n"(TB));
}
DEVI void mma8(float* d, uint32_t a0, uint32_t a1, uint32_t b0) {
  asm volatile("mma.sync.aligned.m16n8k8.row.col.f32.bf16.bf16.f32 {%0,%1,%2,%3},{%4,%5},{%6},{%0,%1,%2,%3};" : "+f"(d[0]), "+f"(d[1]), "+f"(d[2]), "+f"(d[3]) : "r"(a0), "r"(a1), "r"(b0));
}
DEVI void stsm4t(uint32_t a, uint32_t r0, uint32_t r1, uint32_t r2, uint32_t r3) {
  asm volatile("stmatrix.sync.aligned.m8n8.x4.trans.shared.b16 [%0],{%1,%2,%3,%4};" ::"r"(a), "r"(r0), "r"(r1), "r"(r2), "r"(r3) : "memory");
}
DEVI uint32_t movm(uint32_t a) { uint32_t d; asm volatile("movmatrix.sync.aligned.m8n8.trans.b16 %0,%1;" : "=r"(d) : "r"(a)); return d; }
DEVI void sts1(uint32_t a, uint32_t v) { asm volatile("st.shared.b32 [%0],%1;" ::"r"(a), "r"(v) : "memory"); }
DEVI uint32_t lds1(uint32_t a) { uint32_t v; asm volatile("ld.shared.b32 %0,[%1];" : "=r"(v) : "r"(a) : "memory"); return v; }
DEVI void sta1(uint32_t d, uint32_t a, uint32_t bar) { asm volatile("st.async.weak.shared::cluster.mbarrier::complete_tx::bytes.b32 [%0],%1,[%2];" ::"r"(d), "r"(a), "r"(bar) : "memory"); }
DEVI void sta2(uint32_t d, uint32_t a, uint32_t b, uint32_t bar) { asm volatile("st.async.weak.shared::cluster.mbarrier::complete_tx::bytes.v2.b32 [%0],{%1,%2},[%3];" ::"r"(d), "r"(a), "r"(b), "r"(bar) : "memory"); }
DEVI uint32_t clk32() { uint64_t c; asm volatile("mov.u64 %0,%%clock64;" : "=l"(c)::"memory"); return (uint32_t)c; }
DEVI int opq(int x) { asm volatile("" : "+r"(x)); return x; }
DEVI int pin(int x) { return __shfl_sync(~0u, x, threadIdx.x & 31); }
DEVI void x_load(const RecParams& P, uint32_t sb, int c, int seg) {
  asm volatile("cp.async.bulk.tensor.2d.shared::cluster.global.mbarrier::complete_tx::bytes.multicast::cluster [%0],[%1,{%3,%4}],[%2],%5;"
               ::"r"(sb + R_H + c * 5120 + 1024), "l"(&P.x), "r"(sb + (c < XG ? B_XA : B_XB)), "r"(c * 64), "r"(seg * 32), "h"((uint16_t)0xffff) : "memory");
  if (seg + 2 < NSEG) asm volatile("cp.async.bulk.prefetch.tensor.2d.L2.global [%0,{%1,%2}];" ::"l"(&P.x), "r"(c * 64), "r"(seg * 32 + 64) : "memory");
}
DEVI uint32_t hadd2(uint32_t a, uint32_t b) { uint32_t r; asm("add.rn.bf16x2 %0,%1,%2;" : "=r"(r) : "r"(a), "r"(b)); return r; }
DEVI uint32_t hmax2(uint32_t a, uint32_t b) { uint32_t r; asm("max.bf16x2 %0,%1,%2;" : "=r"(r) : "r"(a), "r"(b)); return r; }
DEVI float rcp(float x) { float y; asm("rcp.approx.ftz.f32 %0,%1;" : "=f"(y) : "f"(x)); return y; }
constexpr float SCL = 0.08838834764831845f * 1.4426950408889634f;

DEVI void y_store(const float* a, uint32_t off, int s) {
  const uint32_t x = movm(pack2(a[0], a[1])), y = movm(pack2(a[2], a[3]));
  const uint32_t tag = ((s >> 1) & 1) ^ 1;
  asm volatile("st.relaxed.gpu.global.b64 [%0],%1;" ::"l"((uint8_t*)g_Y + (s & 1) * YSLOT + off), "l"((uint64_t)((x & ~1u) | tag) | ((uint64_t)y << 32)) : "memory");
}
DEVI void y_load(uint32_t* w, const uint8_t* p) {
#pragma unroll
  for (int i = 0; i < 4; i++) asm volatile("{.reg .b64 t; ld.relaxed.gpu.global.b64 t,[%2]; mov.b64 {%0,%1},t;}" : "=r"(w[2 * i]), "=r"(w[2 * i + 1]) : "l"(p + i * 256) : "memory");
}
DEVI bool y_missing(const uint32_t* w, uint32_t tag) {
  uint32_t r;
  asm volatile("{.reg .b32 a,b; .reg .pred p; lop3.b32 a,%1,%2,%5,0x7e; lop3.b32 b,%3,%4,%5,0x7e; lop3.b32 a,a,b,1,0xa8; setp.ne.u32 p,a,0; vote.sync.any.pred p,p,0xffffffff; selp.u32 %0,1,0,p;}"
               : "=r"(r) : "r"(w[0]), "r"(w[2]), "r"(w[4]), "r"(w[6]), "r"(tag));
  return r;
}
DEVI void y_reload(uint32_t* w, const uint8_t* p, uint32_t tag) {
#pragma unroll
  for (int i = 0; i < 4; i++)
    asm volatile("{.reg .b64 t; .reg .b32 a; .reg .pred q; lop3.b32 a,%0,%3,1,0x28; setp.ne.u32 q,a,0; mov.b64 t,{%0,%1}; @q ld.relaxed.gpu.global.b64 t,[%2]; mov.b64 {%0,%1},t;}"
                 : "+r"(w[2 * i]), "+r"(w[2 * i + 1]) : "l"(p + i * 256), "r"(tag) : "memory");
}
DEVI void y_sum(uint32_t* r, const uint32_t* w, uint32_t sel) {
  float d0[4] = {0, 0, 0, 0}, d1[4] = {0, 0, 0, 0};
  mma16(d0, w[0], w[1], w[2], w[3], sel, sel); mma16(d1, w[4], w[5], w[6], w[7], sel, sel);
  r[0] = pack2(d0[0] + d1[0], d0[1] + d1[1]); r[1] = pack2(d0[2] + d1[2], d0[3] + d1[3]);
}
DEVI void y_send(const uint32_t* r, uint32_t sb, uint32_t dst, uint32_t bar, int lane) {
#pragma unroll
  for (int i = 0; i < 4; i++) { const uint32_t rs = mapa(sb, (lane & 3) + i * 4); sta2(rs + dst, r[0], r[1], rs + bar); }
}
DEVI void wo_convert(uint32_t sb, int lane, int warp) {
  TL_END(11)
  mbar_wait(sb + B_W3, 0);
  TL_END(9)
#pragma unroll 1
  for (uint32_t a = sb + R_WO + warp * 4608; a < sb + R_H; a += 8 * 4608) {
    uint32_t r[9][4];
#pragma unroll
    for (int k = 0; k < 9; k++) ldsm4t(r[k], a + k * 32 + ((lane & 7) + (lane >> 4) * 8) * 288 + ((lane >> 3) & 1) * 16);
    __syncwarp();
#pragma unroll
    for (int k = 0; k < 9; k++) stsm4(a + k * 512 + ((lane >> 4) * 2 + ((lane >> 1) & 1)) * 128 + (((lane >> 2) & 3) * 2 + (lane & 1)) * 16, r[k][0], r[k][1], r[k][2], r[k][3]);
  }
  __syncwarp();
}
DEVI uint32_t y_offset(int cta, int tile, int lane) {
  const int T = (cta & 3) * 9 + tile;
  return (((T >> 2) * 8 + (lane >> 2)) * 2 + ((T >> 1) & 1)) * 1024 + (cta >> 4) * 256 + (T & 1) * 128 + ((cta >> 2) & 3) * 32 + (lane & 3) * 8;
}
template <int NR, int NP> DEVI void wo_tile(const uint32_t (*A0)[4], uint32_t sb, int tile, int lane, uint32_t yo, int s) {
  uint32_t u[8][4], A[16][4];
  const uint32_t wa = sb + R_WO + tile * 512 + lane * 16, ua = sb + R_U + lane * 16;
  float a[4] = {0, 0, 0, 0}, b[4] = {0, 0, 0, 0};
  auto fetch = [&](int i) { if (i < 16 - NR) ldsm4(A[i], wa + i * 4608); };
  auto uload = [&](int i) { if (i < 8) ldsm4t(u[i], ua + i * 512); };
#pragma unroll
  for (int i = 0; i < NP; i++) fetch(i);
  mwait(sb + B_V, s & 1);
  PT(6)
  uload(0); uload(1);
#pragma unroll
  for (int i = 0; i < 16; i++) {
    if (i == 4) {
      mwait(sb + B_U, s & 1);
      PT(7)
      uload(2); uload(3);
    }
    const uint32_t* f = i >= 16 - NR ? A0[i >= 16 - NR ? i - 16 + NR : 0] : A[i];
    mma16(i & 1 ? b : a, f[0], f[1], f[2], f[3], u[i >> 1][(i & 1) * 2], u[i >> 1][(i & 1) * 2 + 1]);
    fetch(i + NP);
    if (i >= 4 && (i & 1)) uload((i >> 1) + 2);
  }
#pragma unroll
  for (int i = 0; i < 4; i++) a[i] += b[i];
  y_store(a, yo, s);
}
template <bool X> DEVI void softmax8(const uint32_t* h, uint32_t a4, uint32_t a1) {
  uint32_t y[5];
  lds4(y, a4 + R_SX);
  y[4] = lds1(a1 + R_SX);
#pragma unroll
  for (int j = 0; j < 5; j++) y[j] = hadd2(h[j], y[j]);
  const uint32_t m2 = hmax2(hmax2(hmax2(y[0], y[1]), hmax2(y[2], y[3])), y[4]);
  const float mc = fmaxf(blo(m2), bhi(m2)) * SCL;
  const float m1 = __shfl_xor_sync(~0u, mc, 1), m3 = __shfl_xor_sync(~0u, mc, 2), m4 = __shfl_xor_sync(~0u, mc, 3);
  float e[10];
#pragma unroll
  for (int j = 0; j < 5; j++) { e[2 * j] = ex2(fmaf(blo(y[j]), SCL, -mc)); e[2 * j + 1] = ex2(fmaf(bhi(y[j]), SCL, -mc)); }
  const float c = ex2(mc - fmaxf(fmaxf(mc, m1), fmaxf(m3, m4)));
  const float l = c * ((((e[0] + e[1]) + (e[2] + e[3])) + ((e[4] + e[5]) + (e[6] + e[7]))) + (e[8] + e[9]));
  const float r = c * rcp((l + __shfl_xor_sync(~0u, l, 1)) + (__shfl_xor_sync(~0u, l, 2) + __shfl_xor_sync(~0u, l, 3)));
#pragma unroll
  for (int j = 0; j < 5; j++) y[j] = pack2(e[2 * j] * r, e[2 * j + 1] * r);
  if (!X) sts4(a4 + R_P, y[0], y[1], y[2], y[3]);
  else stsm4(a4 + R_P, y[0], y[1], y[2], y[3]);
  sts1(a1 + R_P, y[4]);
  if (X) fence_async();
}

DEVI void arm_step(uint32_t sb, int s) {
  mbar_expect(sb + B_SM, 640); mbar_expect(sb + B_SX, 2560);
  if (s < NSEG - 1) {
    mbar_expect(sb + B_U, 3072); mbar_expect(sb + B_Z0, 4096); mbar_expect(sb + B_Z1, 5120);
    mbar_expect(sb + B_XA, XG * 4096); mbar_expect(sb + B_XB, (9 - XG) * 4096);
  }
}
DEVI void rec_proj(const RecParams& P, const uint32_t sb, const int cta) {
  uint32_t W[36][4], A0[NRES ? NRES : 1][4];
  const int tid = pin(threadIdx.x);
  const uint32_t yo = pin(y_offset(cta, threadIdx.x >> 5, threadIdx.x & 31));
  const int warp = __shfl_sync(~0u, threadIdx.x >> 5, 0), role = warp >> 2;
  const uint32_t qk = sb + R_Q + warp * 1280;
  {
    const int lane = threadIdx.x & 31, w4 = (threadIdx.x >> 5) & 3;
    const uint32_t a = sb + role * R_H + ((lane & 7) + (lane >> 4) * 8) * 128 + (((w4 * 2 + ((lane >> 3) & 1)) ^ (lane & 7)) << 4);
    mbar_wait(sb + B_W0 + role * 8, 0);
    TL_END(8)
#pragma unroll
    for (int k = 0; k < 36; k++) ldsm4t(W[k], a + k * 2048);
    if (role) bar_arrive(N_INIT1, 256); else bar_sync(N_INIT, 128);
    cluster_sync_relaxed();
    wo_convert(sb, lane, warp);
    bar_sync(N_INIT2, 256);
#pragma unroll
    for (int i = 0; i < NRES; i++) ldsm4(A0[i], sb + R_WO + warp * 512 + lane * 16 + (16 - NRES + i) * 4608);
  }
  for (int s = -1; s < NSEG; s++) {
    if (s >= 0) {
      PT(0)
      {
        const int lane = opq(tid) & 31;
        const uint32_t hb = sb + R_H + (lane & 7) * 128 + (((lane >> 3) ^ (lane & 7)) << 4);
        float a[4] = {0, 0, 0, 0}, b[4] = {0, 0, 0, 0};
        mwait(sb + B_Z0, (s - 1) & 1);
        PT(1)
        uint32_t f[18][4];
#pragma unroll
        for (int c = -PD; c < 18; c++) {
          if (c + PD == 8) mwait(sb + B_Z1, (s - 1) & 1);
          if (c + PD < 18) ldsm4(f[c + PD], (hb ^ (((c + PD) & 1) * 64)) + ((c + PD) >> 1) * 5120);
          if (c >= 0) {
            mma16(a, W[2 * c][0], W[2 * c][1], W[2 * c][2], W[2 * c][3], f[c][0], f[c][1]);
            mma16(b, W[2 * c + 1][0], W[2 * c + 1][1], W[2 * c + 1][2], W[2 * c + 1][3], f[c][2], f[c][3]);
          }
        }
        sts1(qk + 512 + lane * 4, pack2(a[0] + b[0], a[1] + b[1]));
        sts1(qk + 1152 + lane * 4, pack2(a[2] + b[2], a[3] + b[3]));
        fence_async();
      }
      PT(2)
      const int lane = opq(tid) & 31;
      if (role) {
        bar_arrive(N_P1, 256);
        if (tid == 128) arm_step(sb, s);
        const uint32_t o4 = sb + (warp - 4) * 640 + lane * 16, o1 = sb + (warp - 4) * 640 + 512 + lane * 4;
        uint32_t h[5];
        bar_sync(N_PX, 192);
        lds4(h, o4 + R_P); h[4] = lds1(o1 + R_P);
        mwait(sb + B_SX, s & 1);
        PT(4)
        softmax8<true>(h, o4, o1);
        PT(5)
      } else {
        float S[20];
        const uint64_t da = mkdesc(sb + R_Q, 640, 128, 0), db = mkdesc(sb + R_K, 640, 128, 0);
        const uint32_t rs = mapa(sb, (cta & 15) ^ 1);
        const uint32_t o4 = warp * 1280 + lane * 16, o1 = warp * 1280 + 512 + lane * 4;
        bar_sync(N_P1, 256);
        wg_fence();
#pragma unroll
        for (int k = 0; k < 4; k++) wg_ss40<1>(S, da + k * 80, db + k * 80, k);
        wg_commit();
        bar_arrive(N_S, 256);
        wg_wait<0>();
        PT(3)
        uint32_t h[2][5];
        if (warp == 2) {
#pragma unroll
          for (int j = 0; j < 5; j++) h[0][j] = pack2(S[4 * j], S[4 * j + 1]);
          sta4(rs + R_SX + o4, h[0][0], h[0][1], h[0][2], h[0][3], rs + B_SM); sta1(rs + R_SX + o1, h[0][4], rs + B_SM);
          mwait(sb + B_SM, s & 1);
          PT(4)
          softmax8<false>(h[0], sb + o4, sb + o1);
          bar_arrive(N_PM, 160);
        } else if (warp < 2) {
          const int row = warp * 16 + (lane >> 2) - (lane & 3) * 2;
#pragma unroll
          for (int g = 0; g < 2; g++) {
#pragma unroll
            for (int j = 0; j < 5; j++) h[g][j] = pack2(j < 4 && j * 8 > row + g * 8 ? -INFINITY : S[4 * j + 2 * g], j < 4 && j * 8 + 1 > row + g * 8 ? -INFINITY : S[4 * j + 2 * g + 1]);
            sts4(sb + R_P + o4 + g * 640, h[g][0], h[g][1], h[g][2], h[g][3]); sts1(sb + R_P + o1 + g * 640, h[g][4]);
            sta4(rs + R_SX + o4 + g * 640, h[g][0], h[g][1], h[g][2], h[g][3], rs + B_SX);
            sta1(rs + R_SX + o1 + g * 640, h[g][4], rs + B_SX);
          }
          bar_arrive(N_PX, 192);
        } else {
          if (s) { bar_sync(N_O, 160); fence_async(); }
          if (tid == 96) {
            if (s) {
              bulk_wait<0>();
              tma_store(&P.ctx, sb + R_OX, cta * 64, s * 32 - 32); bulk_commit();
              if ((s & 3) == 1 && s > 1) signal_after_bulk(S_CTXB + (s >> 2) - 1);
              bulk_wait_read<0>();
            }
          }
        }
        __syncwarp();
        PT(5)
      }
      {
        if (s == NSEG - 1) break;
        wo_tile<NRES, NPF>(A0, sb, warp, lane, yo, s);

        PT(8)
        bar_sync(N_WO, 384);
      }
    }
    {
      float acc[16];
      const uint64_t db = mkdesc(sb + R_H + 1024, 16, 1024, 1);
      mwait(sb + B_XA, (s + 1) & 1);
      PT(9)
      wg_fence();
#pragma unroll
      for (int k = 0; k < XG * 4; k++) wg_rs32(acc, W[k], db + (k >> 2) * 320 + (k & 3) * 2, k);
      wg_commit();
      mwait(sb + B_XB, (s + 1) & 1);
      wg_fence();
#pragma unroll
      for (int k = XG * 4; k < KA; k++) wg_rs32(acc, W[k], db + (k >> 2) * 320 + (k & 3) * 2, 1);
      wg_commit();
      wg_wait<0>();
      PT(10)
      bar_sync(N_SUM, 384);
      wg_fence();
#pragma unroll
      for (int k = KA; k < 36; k++) wg_rs32(acc, W[k], db + (k >> 2) * 320 + (k & 3) * 2, 1);
      wg_commit();
      const uint32_t o = qk + (opq(tid) & 31) * 16;
      wg_wait<0>();
      PT(11)
      stsm4(o, pack2(acc[0], acc[1]), pack2(acc[4], acc[5]), pack2(acc[8], acc[9]), pack2(acc[12], acc[13]));
      stsm4(o + 640, pack2(acc[2], acc[3]), pack2(acc[6], acc[7]), pack2(acc[10], acc[11]), pack2(acc[14], acc[15]));
    }
  }
  bar_arrive(N_WO, 384);
  for (int i = 0; i < (warp ? 1 : 2); i++)
    asm volatile("st.relaxed.gpu.global.b64 [%0],%1;" ::"l"((uint8_t*)g_Y + YSLOT + yo + i * 2 * 16384), "l"(0ull) : "memory");
  TL_END(6)
  if (tid == 0) CT(1, 0)
  if (warp == 3) {
    if (tid == 96) { bulk_wait<0>(); asm volatile("fence.proxy.async.global;" ::: "memory"); }
    __syncwarp();
    bar_arrive(N_O, 160);
  }
  asm volatile("barrier.cluster.arrive.relaxed.aligned;" ::: "memory");
  float acc[48];
  const int rk = opq(cta) & 15, n = rk / 5, q = rk - n * 5;
  out_consume<TST, false, 32>(acc, sb, sb + B_O, rk == 15 ? 0 : q == 4 ? 12 : 13);
  if (tid == 0) CT(7, 1)
  if (tid == 0) CT(1, 1)
  asm volatile("barrier.cluster.wait.aligned;" ::: "memory");
  bar_sync(N_P1, 256);
  {
#pragma unroll
    for (int u = 0; u < 6; u++) {
      const int d = u % 5;
      const float* a = acc + u * 8;
      const uint32_t x = pack2(a[0], a[1]), y = pack2(a[2], a[3]), z = pack2(a[4], a[5]), w = pack2(a[6], a[7]);
      const uint32_t rs = mapa(sb, rk == 15 ? 15 : n * 5 + d);
      if (d == q) sts4(sb + R_RED - 8192 + (u / 5) * 4096 + tid * 16, x, y, z, w);
      else sta4(rs + R_RED + (q < d ? q : q - 1) * 8192 + (u / 5) * 4096 + tid * 16, x, y, z, w, rs + B_R);
    }
    mbar_wait(sb + B_R, 0);
    if (tid == 0) CT(1, 2)
    const int lane = tid & 31;
    const uint32_t st = sb + warp * 1024 + (lane & 15) * 48 + (lane >> 4) * 16, ld = sb + warp * 1024 + (lane >> 1) * 48 + (lane & 1) * 16;
    bf16* out = P.out + (size_t)((TAIL0 + (cta >> 5)) * 128 + warp * 16 + (lane >> 1)) * (2 * DM) + DM + ((cta >> 4) & 1) * 288 + n * 96 + q * 16 + (lane & 1) * 8;
#pragma unroll 1
    for (int i = 0; i < (q ? 1 : 2); i++) {
      uint32_t v[5][4], r[4];
#pragma unroll
      for (int p = 0; p < 5; p++) lds4(v[p], sb + R_RED + (p - 1) * 8192 + i * 4096 + tid * 16);
#pragma unroll
      for (int j = 0; j < 4; j++)
        r[j] = pack2((blo(v[0][j]) + blo(v[1][j])) + (blo(v[2][j]) + blo(v[3][j])) + blo(v[4][j]), (bhi(v[0][j]) + bhi(v[1][j])) + (bhi(v[2][j]) + bhi(v[3][j])) + bhi(v[4][j]));
      stsm4(st + i * 8192, r[0], r[1], r[2], r[3]);
      __syncwarp();
      lds4(r, ld + i * 8192);
      asm volatile("{.reg .pred p; setp.ne.s32 p,%5,15; @p st.global.v4.b32 [%0],{%1,%2,%3,%4};}" ::"l"(out + i * 80), "r"(r[0]), "r"(r[1]), "r"(r[2]), "r"(r[3]), "r"(rk) : "memory");
    }
  }
}

template <int K> DEVI void v_resident(uint32_t (*F)[4], uint32_t wv) {
  if constexpr (K < 36) { if (VIdx<K>::r == 'r') ldsm4t(F[VIdx<K>::v], wv + K * 2048); v_resident<K + 1>(F, wv); }
}
template <int K> DEVI void v_pass(float* acc, const uint32_t (*F)[4], uint64_t da, uint64_t db, uint32_t xf, uint32_t t, uint32_t nrel) {
  if constexpr (K < 36) {
    wg_fence();
    if (VIdx<K>::r == 'r') wg_rs40(acc, F[VIdx<K>::v], db + (K >> 2) * 320 + (K & 3) * 2, K);
    else wg_ss40<0>(acc, da + K * 128, db + (K >> 2) * 320 + (K & 3) * 2, K);
    wg_commit();
    if constexpr (VIdx<K>::p != '-') wg_wait<VIdx<K>::p - '0'>();
    if (K == XG * 4 - 1 + XW) { wg_wait<XW>(); asm volatile("{.reg .pred p; .reg .b32 a; setp.lt.u32 p,%1,%2; @p mapa.shared::cluster.u32 a,%0,%1; @p mbarrier.arrive.shared::cluster.b64 _,[a];}" ::"r"(xf), "r"(t), "r"(nrel) : "memory"); }
    v_pass<K + 1>(acc, F, da, db, xf, t, nrel);
  }
}
DEVI void rec_aux(const RecParams& P, const uint32_t sb, const int cta) {
  const int tid = pin(threadIdx.x);
  {
    uint4 v[5];
#pragma unroll
    for (int j = 0; j < 5; j++) if (j * 128 + tid - 256 < 576) v[j] = ((const uint4*)P.mem0)[j * 128 + tid - 256];
    if (tid == 288) {
      const uint32_t t0 = clk32();
      while (clk32() - t0 < (uint32_t)WOD) {}
#pragma unroll 1
      for (int i = 0; i < 4; i++) tma_load(sb + R_WO + i * 18432, &P.wo, (cta & 3) * 144, (cta ^ i) * 64, sb + B_W3);
      for (int i = 0; i < 3; i++) asm volatile("cp.async.bulk.prefetch.tensor.2d.L2.global [%0,{%1,%2}];" ::"l"(&P.wv), "r"(cta * 64), "r"(i * 192) : "memory");
    }
    __syncwarp();
    bar_sync(N_INIT1, 256);
#pragma unroll
    for (int j = 0; j < 5; j++) {
      const int i = j * 128 + tid - 256, t = i / 72, c = i - t * 72;
      if (i < 576) sts4(sb + R_H + (c >> 3) * 5120 + t * 128 + (((c & 7) ^ t) << 4), v[j].x, v[j].y, v[j].z, v[j].w);
    }
    fence_async();
    bar_arrive(N_SUM, 384);
    cluster_sync_relaxed();
    if (tid == 288) {
      if ((cta & 15) < 9) x_load(P, sb, cta & 15, 0);
#pragma unroll 1
      for (int i = 0; i < 3; i++) tma_load(sb + R_WV + i * 24576, &P.wv, cta * 64, i * 192, sb + B_W2);
    }
    __syncwarp();
    TL_END(12)
    TL_END(10)
  }
  const int rk = cta & 15, w4 = __shfl_sync(~0u, (threadIdx.x >> 5) & 3, 0);
  const uint32_t yg = pin((((threadIdx.x >> 5) & 3) * 16 + rk) * 1024 + ((threadIdx.x >> 4) & 1) * 128 + (threadIdx.x & 3) * 32 + ((threadIdx.x >> 2) & 3) * 8);
  uint32_t F[VB][4];
  mbar_wait(sb + B_W2, 0);
  TL_END(7)
  v_resident<0>(F, sb + R_WV + ((tid & 7) + ((tid >> 4) & 1) * 8) * 128 + (((w4 * 2 + ((tid >> 3) & 1)) ^ (tid & 7)) << 4));
  LT(0)
  for (int s = 0; s < NSEG; s++) {
    const bool last = s == NSEG - 1;
    uint32_t va[12], p[5];
    int lane = opq(tid) & 31;
    {
      float acc[20];
      const uint64_t da = mkdesc(sb + R_WV, 0, 1024, 1), db = mkdesc(sb + R_H, 16, 1024, 1);
      PT(0)
      bar_sync(N_S, 256);
      asm volatile("fence.proxy.async::generic.acquire.sync_restrict::shared::cluster.cluster;" ::: "memory");
      v_pass<0>(acc, F, da, db, sb + B_XF, tid - 256, last ? 0 : XG);
      PT(13)
      bar_sync(N_PM, 160);
      lds4(p, sb + R_P + 2560 + lane * 16); p[4] = lds1(sb + R_P + 3072 + lane * 4);
      wg_wait<0>();
      PT(1)
#pragma unroll
      for (int i = 0; i < 10; i++) va[i < 2 ? i + 8 : i - 2] = pack2(acc[2 * i], acc[2 * i + 1]);
      va[10] = va[11] = 0;
    }
    lane = opq(tid) & 31;
    if (!last) {
      const uint32_t uo = R_U + w4 * 256 + lane * 4;
      float a[4] = {0, 0, 0, 0}, b[4] = {0, 0, 0, 0}, c[4] = {0, 0, 0, 0};
      mma16(a, va[0], va[1], va[2], va[3], p[0], p[1]); mma16(b, va[4], va[5], va[6], va[7], p[2], p[3]); mma8(c, va[8], va[9], p[4]);
      const uint32_t u0 = pack2(a[0] + b[0] + c[0], a[1] + b[1] + c[1]), u1 = pack2(a[2] + b[2] + c[2], a[3] + b[3] + c[3]);
      sts1(sb + uo, u0); sts1(sb + uo + 128, u1);
      __syncwarp();
      if (lane == 0) mbar_arrive(sb + B_V);
#pragma unroll
      for (int q = 1; q < 4; q++) { const uint32_t rs = mapa(sb, rk ^ q); sta1(rs + uo + q * 1024, u0, rs + B_U); sta1(rs + uo + q * 1024 + 128, u1, rs + B_U); }
      asm volatile("{.reg .pred p; .reg .b32 a; setp.lt.u32 p,%1,%3; @p mapa.shared::cluster.u32 a,%0,%2; @p mbarrier.arrive.shared::cluster.b64 _,[a];}" ::"r"(sb + B_XF), "r"(tid - 256 - XG), "r"(tid - 256), "n"(9 - XG) : "memory");
      PT(4)
      if (w4 == 3) {
        wo_tile<0, 4>(nullptr, sb, 8, lane, y_offset(cta, 8, lane), s);
      } else if (tid == 288 && rk < 9) { mbar_wait(sb + B_XF, s & 1); x_load(P, sb, rk, s + 1); }
      PT(2)
    }
    lane = opq(tid) & 31;
    uint32_t tu;
    {
      float o[16];
      const uint64_t dp = mkdesc(sb + R_P, 128, 640, 0);
      bar_sync(N_WO, 384);
      wg_fence();
      wg_rs32(o, va, dp, 0); wg_rs32(o, va + 4, dp + 16, 1); wg_rs32(o, va + 8, mkdesc(sb + R_P + 512, 0, 640, 0), 1);
      wg_commit();
      tu = clk32();
      wg_wait<0>();
      PT(3)
#pragma unroll
      for (int h = 0; h < 2; h++)
        stsm4t(sb + R_OX + lane * 128 + (((w4 * 2 + h) ^ (lane & 7)) << 4), pack2(o[2 * h], o[2 * h + 1]), pack2(o[4 + 2 * h], o[5 + 2 * h]), pack2(o[8 + 2 * h], o[9 + 2 * h]), pack2(o[12 + 2 * h], o[13 + 2 * h]));
      if (last) break;
      bar_arrive(N_O, 160);
    }
    {
      const uint8_t* y = (const uint8_t*)g_Y + (s & 1) * YSLOT + yg;
      uint32_t w0[8], w1[8], w2[8];
      while (clk32() - tu < (uint32_t)YD) {}
      y_load(w0, y); y_load(w1, y + 4 * 16384);
      if (w4 == 0) y_load(w2, y + 8 * 16384);
      else {
#pragma unroll
        for (int i = 0; i < 8; i++) w2[i] = ((s >> 1) & 1) ^ 1;
      }
      PT(5)
      const uint32_t dst = R_H + w4 * 5120 + (rk >> 1) * 128 + ((((rk & 1) * 4 + (lane >> 3)) ^ (rk >> 1)) << 4) + (lane & 4) * 2;
      const uint32_t tag = ((s >> 1) & 1) ^ 1, sel = (lane & 4) ? 0x3f800000u : 0x3f80u;
      uint32_t r0[2], r1[2], r2[2];
#pragma unroll 1
      for (int it = 0; (y_missing(w0, tag) | y_missing(w1, tag) | y_missing(w2, tag)) && it < (1 << 20); it++) {
        y_reload(w0, y, tag); y_reload(w1, y + 4 * 16384, tag); y_reload(w2, y + 8 * 16384, tag);
      }
      PT(7)
      y_sum(r0, w0, sel); y_sum(r1, w1, sel); y_sum(r2, w2, sel);
      y_send(r0, sb, dst, B_Z0, lane);
      bar_arrive(N_SUM, 384);
      y_send(r1, sb, dst + 4 * 5120, B_Z1, lane);
      if (w4 == 0) y_send(r2, sb, dst + 8 * 5120, B_Z1, lane);
      PT(9)
    }
    PT(11)
  }
  fence_async();
  bar_sync(N_O, 160);
  if (tid == 256) {
    tma_store(&P.ctx, sb + R_OX, cta * 64, SEQ - 32); bulk_commit(); bulk_wait<0>(); signal_after_bulk(S_CTXB + 15);
  }
  __syncwarp();
  LT(1)
  asm volatile("barrier.cluster.arrive.relaxed.aligned;" ::: "memory");
  if (tid == 256) {
    const int m = TAIL0 + (cta >> 5), n = rk / 5, q = rk - n * 5;
    mbar_expect(sb + B_R, q || rk == 15 ? 4 * 4096 : 8 * 4096);
    if (rk < 15) out_produce<TST, false, 32>(P.o, sb, sb + B_O, m, ((cta >> 4) & 1) * 3 + n, q * 13, q == 4 ? 12 : 13, S_CTXB + m);
  }
  __syncwarp();
  asm volatile("barrier.cluster.wait.aligned;" ::: "memory");
}

__global__ void __launch_bounds__(384, 1) rec_kernel(const __grid_constant__ RecParams P) {
  extern __shared__ __align__(1024) uint8_t smem_raw[];
  const uint32_t sb = s2u(smem_raw);
  const int tid = threadIdx.x, cta = blockIdx.x;
  pdl_trigger();
  if (cta >= 64) {
    unsigned sm; asm("mov.u32 %0,%%smid;" : "=r"(sm));
    if (tid == 0) g_group[sm & 255] = (cta >> 4) - 3;
    return;
  }
  TL_START(1)
  if (tid == 0) {
    for (int i = 0; i < 14 + 2 * TST; i++) mbar_init(sb + R_BAR + 8 * i, 8 * i == B_XF - R_BAR ? 16 : 8 * i == B_V - R_BAR ? 4 : i >= 14 + TST ? 2 : 1);
    asm volatile("fence.mbarrier_init.release.cluster;" ::: "memory");
    asm volatile("cp.async.bulk.prefetch.L2.global [%0],%1;" ::"l"(P.x_raw + cta * DM), "r"(DM * 2) : "memory");
    mbar_expect(sb + B_W0, 73728); mbar_expect(sb + B_W1, 73728); mbar_expect(sb + B_W2, 73728); mbar_expect(sb + B_W3, 73728);
#pragma unroll 1
    for (int i = 0; i < 3; i++) { tma_load(sb + R_WV + i * 24576, &P.wq, cta * 64, i * 192, sb + B_W0); tma_load(sb + R_H + i * 24576, &P.wk, cta * 64, i * 192, sb + B_W1); }
    mbar_expect(sb + B_XA, XG * 4096); mbar_expect(sb + B_XB, (9 - XG) * 4096);
  }
  __syncthreads();
  if (tid >= 256) { reg_dec<504 - 2 * RP>(); rec_aux(P, sb, cta); }
  else { reg_inc<RP>(); rec_proj(P, sb, cta); }
  TL_END(1)
  if (tid == 0) CT(7, 2)
  cluster_sync_relaxed();
}
typedef CUresult (*EncFn)(CUtensorMap*, CUtensorMapDataType, cuuint32_t, void*, const cuuint64_t*, const cuuint64_t*, const cuuint32_t*, const cuuint32_t*,
                          CUtensorMapInterleave, CUtensorMapSwizzle, CUtensorMapL2promotion, CUtensorMapFloatOOBfill);
static EncFn g_enc;
static CUtensorMap mk(const void* p, uint64_t cols, uint64_t rows, uint64_t pitch_elems, uint32_t box_rows, uint32_t box_cols = 64) {
  CUtensorMap m;
  cuuint64_t dim[2] = {cols, rows}, str[1] = {pitch_elems * 2};
  cuuint32_t box[2] = {box_cols, box_rows}, es[2] = {1, 1};
  g_enc(&m, CU_TENSOR_MAP_DATA_TYPE_BFLOAT16, 2, (void*)p, dim, str, box, es, CU_TENSOR_MAP_INTERLEAVE_NONE, box_cols == 64 ? CU_TENSOR_MAP_SWIZZLE_128B : box_cols == 32 ? CU_TENSOR_MAP_SWIZZLE_64B : CU_TENSOR_MAP_SWIZZLE_NONE,
        CU_TENSOR_MAP_L2_PROMOTION_L2_256B, CU_TENSOR_MAP_FLOAT_OOB_FILL_NONE);
  return m;
}
static CUtensorMap mk3(const void* p, uint32_t g, uint32_t box_rows) {
  CUtensorMap m;
  cuuint64_t dim[3] = {g, HD, DM / g}, str[2] = {DM * 2, g * 2};
  cuuint32_t box[3] = {g, box_rows, 3}, es[3] = {1, 1, 1};
  g_enc(&m, CU_TENSOR_MAP_DATA_TYPE_BFLOAT16, 3, (void*)p, dim, str, box, es, CU_TENSOR_MAP_INTERLEAVE_NONE, g == 64 ? CU_TENSOR_MAP_SWIZZLE_128B : CU_TENSOR_MAP_SWIZZLE_64B,
        CU_TENSOR_MAP_L2_PROMOTION_L2_256B, CU_TENSOR_MAP_FLOAT_OOB_FILL_NONE);
  return m;
}
template <class T> static void* sym(T& s) { void* p; cudaGetSymbolAddress(&p, s); return p; }

#define FE 6
#define STG 10
#define FHC 24
#define FSL 5
#define NF2 20
template <class K, class A> static void launch(K k, int grid, int smem, int cluster, bool pdl, const A& arg) {
  cudaLaunchConfig_t c = {};
  cudaLaunchAttribute at[2];
  int n = 0;
  if (cluster > 1) { at[n].id = cudaLaunchAttributeClusterDimension; at[n].val.clusterDim.x = cluster; at[n].val.clusterDim.y = at[n].val.clusterDim.z = 1; n++; }
  if (pdl) { at[n].id = cudaLaunchAttributeProgrammaticStreamSerialization; at[n].val.programmaticStreamSerializationAllowed = 1; n++; }
  c.gridDim = grid; c.blockDim = 384; c.dynamicSmemBytes = smem; c.stream = cudaStreamPerThread; c.attrs = at; c.numAttrs = n;
  cudaLaunchKernelEx(&c, k, arg);
}

extern "C" void kernel_launch(void* const* d_in, const int* in_sizes, int n_in, void* d_out, int out_size) {
  static int nb, ng;
  if (!g_enc) {
    cudaDriverEntryPointQueryResult qr;
    cudaGetDriverEntryPoint("cuTensorMapEncodeTiled", (void**)&g_enc, cudaEnableDefault, &qr);
    cudaDeviceGetAttribute(&nb, cudaDevAttrMultiProcessorCount, 0);
    nb = nb - 64 < 54 ? 54 : nb - 64 > 96 ? 96 : (nb - 64) & ~1;
    cudaFuncSetAttribute(out_kernel, cudaFuncAttributeMaxDynamicSharedMemorySize, SM_O);
    cudaFuncSetAttribute(fa_kernel, cudaFuncAttributeMaxDynamicSharedMemorySize, SM_F);
    cudaFuncSetAttribute(rec_kernel, cudaFuncAttributeMaxDynamicSharedMemorySize, R_END);
    cudaFuncSetAttribute(rec_kernel, cudaFuncAttributeNonPortableClusterSizeAllowed, 1);
    cudaLaunchConfig_t c = {};
    cudaLaunchAttribute at; at.id = cudaLaunchAttributeClusterDimension; at.val.clusterDim.x = 16; at.val.clusterDim.y = at.val.clusterDim.z = 1;
    c.gridDim = 128; c.blockDim = 384; c.dynamicSmemBytes = R_END; c.attrs = &at; c.numAttrs = 1;
    cudaOccupancyMaxActiveClusters(&ng, rec_kernel, &c);
    ng = ng < 4 ? 0 : ng - 4 > nb / 16 ? nb / 16 : ng - 4;
  }
  const bf16 *Ax = (const bf16*)d_in[0], *Ac = (const bf16*)d_in[1], *Awq = (const bf16*)d_in[2], *Awk = (const bf16*)d_in[3], *Awv = (const bf16*)d_in[4],
             *Awo = (const bf16*)d_in[5], *Bx = (const bf16*)d_in[6], *Bm = (const bf16*)d_in[7], *Bwq = (const bf16*)d_in[8], *Bwk = (const bf16*)d_in[9],
             *Bwv = (const bf16*)d_in[10], *Bwo = (const bf16*)d_in[11];
  bf16* out = (bf16*)d_out;
  FaParams f;
  ProjParams& p = f.p;
  int nitems = 0;
  p.a[0] = mk(Ac, 512, SEQ, 512, 128); p.a[1] = mk(Ax, DM, SEQ, DM, 128);
  p.w[0] = mk(Awk, HD, 512, HD, 64); p.w[1] = mk(Awv, HD, 512, HD, 64); p.w[2] = mk(Awq, HD, DM, HD, 64);
  p.c[0] = mk(sym(g_kA), HD, SEQ, HD, 64); p.c[1] = mk(sym(g_vA), HD, SEQ, HD, 64); p.c[2] = mk(sym(g_qA), HD, SEQ, HD, 64);
  {
    int parts[16];
    for (int i = 0; i < 16; i++) parts[i] = 1;
    for (int e = 0; e < nb / 2 - 16; e++) parts[e % 24 < 16 ? e % 8 : 15 - (e % 24 - 16)]++;
    for (int i = 15; i >= 0; i--)
      for (int j = 0, nc = i < 8 ? 32 : 16, a = parts[i]; j < a; j++) {
        ProjItem& I = p.item[nitems++];
        I.pa = i >> 3; I.m = i & 7;
        I.c0[0] = j * nc / a; I.n[0] = (j + 1) * nc / a - I.c0[0];
        I.c0[1] = (j * nc + a - 1) / a; I.n[1] = ((j + 1) * nc + a - 1) / a - I.c0[1];
        if (i < 8 && a == 3) { const int d = STG * (i + 4) / 11, b1 = 11 - d, b2 = 22 - d + (i - 4) * STG / 16; I.c0[1] = j == 0 ? 0 : j == 1 ? b1 : b2; I.n[1] = (j == 0 ? b1 : j == 1 ? b2 : 32) - I.c0[1]; }
      }
  }
  for (int i = 0; i < nitems; i++) {
    auto len = [&](int j) { return (8 + p.item[j].pa) * (1 + p.item[j].n[0] + p.item[j].n[1]); };
    int longer = 0;
    for (int j = 0; j < nitems; j++) longer += len(j) > len(i) || (len(j) == len(i) && j < i);
    p.item[i].leave = longer < NF2 / 2;
    p.item[i].s0 = (PST - len(i) % PST) % PST;
  }
  OutParams o;
  for (int i = 0; i < 3; i++) {
    f.om[i].a = mk(i ? sym(g_ctxB) : sym(g_qA), HD, SEQ, HD, 128);
    f.om[i].b = i < 2 ? mk(i ? Bwo : Awo, DM, HD, DM, 32) : mk(Bwo, DM, HD, DM, 64, 32);
    f.om[i].c = mk(out + (i ? DM : 0), DM, SEQ, 2 * DM, 64, i < 2 ? 64 : 32);
  }
  o.p[0] = f.om[1]; o.p[0].b = mk(Bwo, DM, HD, DM, 64); o.p[1] = f.om[2];
  f.q = mk(sym(g_qA), HD, SEQ, HD, 128); f.k = mk(sym(g_kA), HD, SEQ, HD, 128); f.v = mk(sym(g_vA), HD, SEQ, HD, 128); f.o = mk(sym(g_qA), HD, SEQ, HD, 64);
  f.nctas = nb; f.ngroups = ng;
  for (int i = 0; i < 9; i++) f.nproj[i] = 0;
  for (int i = 0; i < nitems; i++) f.nproj[p.item[i].pa * (p.item[i].m + 1)] += 4;
  for (int key = -90, n = 0; n < 512; key++)
    for (int h = 0; h < 32; h++)
      for (int qt = 0; qt < 16; qt++)
        if ((h < FHC ? h : FHC) * FSL - qt * 2 - (qt >= 12 && h < FE ? 60 : 0) == key) f.order[n++] = qt * 32 + h;
  RecParams r;
  r.wq = mk(Bwq, HD, DM, HD, 192); r.wk = mk(Bwk, HD, DM, HD, 192); r.wv = mk(Bwv, HD, DM, HD, 192); r.wo = mk(Bwo, DM, HD, DM, 64, 144);
  r.x_raw = Bx;
  r.x = mk(Bx, DM, SEQ, DM, 32); r.ctx = mk(sym(g_ctxB), HD, SEQ, HD, 32); r.mem0 = Bm; r.o = f.om[2]; r.o.b = mk3(Bwo, 32, 64); r.out = out;

  f.om[2].a = mk(sym(g_ctxB), HD, SEQ, HD, 64);
  uint16_t* last = f.tile;
  int nl = 0;
  for (int m = 14; m >= 0; m -= 2)
    for (int n = 0; n < 3; n++) { last[nl++] = m * 8 + n; last[nl++] = m * 8 + 8 + n; }
  for (int n = 0; n < 6; n++) last[nl++] = 256 + (TAIL0 - 1) * 8 + n;
  bool done[16][3] = {};
  for (int m = TAIL0 - 3; m >= 0; m -= 2)
    for (int n = 2; n >= 0 && nl < nb; n--) { last[nl++] = 128 + m * 8 + n; last[nl++] = 128 + m * 8 + 8 + n; done[m][n] = done[m + 1][n] = true; }
  while (nl < nb) last[nl++] = 384;
  o.n = 2; o.odd = 0; o.tile[0] = 128; o.tile[1] = 129; done[0][0] = true;
  for (int m = 0; m < TAIL0 - 1; m++)
    for (int n = 0; n < 3; n++) if (!done[m][n]) o.tile[o.n++] = m * 8 + n;
  launch(rec_kernel, 64 + 16 * ng, R_END, 16, false, r);
  f.proj = 1;
  launch(fa_kernel, nb, SM_F, 2, true, f);
  launch(out_kernel, o.n, SM_O, 2, true, o);
  f.proj = 0;
  launch(fa_kernel, NF2, SM_F, 2, true, f);
}
```
